```python
import torch

def _softmax(x, axis=-1):
    return torch.softmax(x, dim=axis)

def _gelu(x):
    return torch.nn.functional.gelu(x, approximate='tanh')

def _silu(x):
    return torch.nn.functional.silu(x)

def _sigmoid(x):
    return torch.sigmoid(x)

def _layernorm(x, axis=-1, eps=1e-05):
    m = x.mean(dim=axis, keepdim=True)
    v = x.var(dim=axis, keepdim=True, unbiased=False)
    return (x - m) / torch.sqrt(v + eps)

def _scatter_add(tgt, idx, src, axis=0):
    return tgt.clone().index_add_(axis, idx, src)

def _segment_sum(src, seg, n):
    out = torch.zeros((n,) + src.shape[1:], dtype=src.dtype)
    return out.index_add_(0, seg, src)

def _pad(x, pw):
    flat = tuple((v for pair in reversed(pw) for v in pair))
    return torch.nn.functional.pad(x, flat)
kernel_name = 'adaLN_cond__sliding_block_cached__moe_arch_mod__decode'

def setup_inputs():

    _w = lambda a: (lambda t: t.to(torch.bfloat16) if t.is_floating_point() else t)(torch.as_tensor(a))

    def _A_setup():
        B, Sq, D = (8, 1, 576)
        Hq, Hkv, Sk, Dh = (32, 16, 8192, 128)
        assert Hq % Hkv == 0, (Hq, Hkv)
        return {'x': _w((lambda *s: torch.randn(*s, dtype=torch.bfloat16) * 0.1)(B, Sq, D)), 'k_cache': _w((lambda *s: torch.randn(*s, dtype=torch.bfloat16) * 0.8)(B, Hkv, Sk, Dh)), 'v_cache': _w((lambda *s: torch.randn(*s, dtype=torch.bfloat16) * 0.8)(B, Hkv, Sk, Dh)), 'wq': _w((lambda *s: torch.randn(*s, dtype=torch.bfloat16) * 0.8)(D, Hq * Dh) * D ** (-0.5)), 'wo': _w((lambda *s: torch.randn(*s, dtype=torch.bfloat16) * 0.8)(Hq * Dh, D) * (Hq * Dh) ** (-0.5))}
    _A_in = _A_setup()

    def _B_setup():
        B, S, D, F, C = (8, 1, 576, 4608, 1)
        return {'x': _w((lambda *s: torch.randn(*s, dtype=torch.bfloat16) * 0.1)(B, S, D)), 'w_r': _w((lambda *s: torch.randn(*s, dtype=torch.bfloat16) * 0.2)(D)), 'w_gate': _w((lambda *s: torch.randn(*s, dtype=torch.bfloat16) * 0.1)(D, F)), 'w_up': _w((lambda *s: torch.randn(*s, dtype=torch.bfloat16) * 0.1)(D, F)), 'w_down': _w((lambda *s: torch.randn(*s, dtype=torch.bfloat16) * 0.1)(F, D))}
    _B_in = _B_setup()
    return {'A_x': _A_in['x'], 'A_k_cache': _A_in['k_cache'], 'A_v_cache': _A_in['v_cache'], 'A_wq': _A_in['wq'], 'A_wo': _A_in['wo'], 'B_x': _B_in['x'], 'B_w_r': _B_in['w_r'], 'B_w_gate': _B_in['w_gate'], 'B_w_up': _B_in['w_up'], 'B_w_down': _B_in['w_down'], 'c': _w((lambda *s: torch.randn(*s, dtype=torch.bfloat16) * 0.4)(8, 576) * 8.0), 'w_mod': _w((lambda *s: torch.randn(*s, dtype=torch.bfloat16) * 0.4)(576, 6 * 576) * 576 ** (-0.5) * 8.0)}

def reference(A_x, A_k_cache, A_v_cache, A_wq, A_wo, B_x, B_w_r, B_w_gate, B_w_up, B_w_down, c, w_mod):

    def _A_ref(x, k_cache, v_cache, wq, wo):
        B, Sq, D = x.shape
        Hq, Dh = (32, 128)
        Hkv, Sk = (k_cache.shape[1], k_cache.shape[2])
        W = min(4096, max(256, Sk // 4))
        rep = Hq // Hkv
        q = (lambda x, *d: x.permute(*d))((x @ wq).reshape(B, Sq, Hq, Dh), 0, 2, 1, 3)
        k = (lambda x, n, axis: torch.repeat_interleave(x, n, dim=axis))(k_cache[:, :, Sk - W:, :], rep, axis=1)
        v = (lambda x, n, axis: torch.repeat_interleave(x, n, dim=axis))(v_cache[:, :, Sk - W:, :], rep, axis=1)
        scores = torch.einsum('bhqd,bhkd->bhqk', q, k) * Dh ** (-0.5)
        p = _softmax(scores, axis=-1)
        o = torch.einsum('bhqk,bhkd->bhqd', p, v)
        return (lambda x, *d: x.permute(*d))(o, 0, 2, 1, 3).reshape(B, Sq, Hq * Dh) @ wo

    def _B_ref(x, w_r, w_gate, w_up, w_down):
        B, S, D = x.shape
        C = 1
        r = x @ w_r
        idx = torch.argsort(-r, axis=-1)[:, :C]
        idx_e = (lambda x, n, axis: torch.repeat_interleave(x, n, dim=axis))(idx.reshape(B, C, 1), D, axis=2)
        x_sel = (lambda x, i, axis: torch.take_along_dim(x, i, dim=axis))(x, idx_e, axis=1)
        g = _silu(x_sel @ w_gate)
        u = x_sel @ w_up
        y = g * u @ w_down
        r_sel = _sigmoid((lambda x, i, axis: torch.take_along_dim(x, i, dim=axis))(r, idx, axis=1))
        y = y * r_sel.reshape(B, C, 1)
        b_off = (torch.arange(B) * S).reshape(B, 1)
        flat_idx = (idx + b_off).reshape(B * C)
        zero = (x * 0.0).reshape(B * S, D)
        upd = _scatter_add(zero, flat_idx, y.reshape(B * C, D), axis=0)
        return x + upd.reshape(B, S, D)
    x = A_x
    mod = (_silu(c) @ w_mod).reshape(c.shape[0], 6, 1, -1)
    sa, ca, ga, sb, cb, gb = (mod[:, 0].clone(), mod[:, 1].clone(), mod[:, 2].clone(), mod[:, 3].clone(), mod[:, 4].clone(), mod[:, 5].clone())
    h = _layernorm(x, axis=-1) * (1 + ca) + sa
    x = x + ga * _A_ref(h, A_k_cache, A_v_cache, A_wq, A_wo)
    h = _layernorm(x, axis=-1) * (1 + cb) + sb
    x = x + gb * _B_ref(h, B_w_r, B_w_gate, B_w_up, B_w_down)
    return x
```

```cpp
#include <cuda_runtime.h>
#include <cuda_bf16.h>
#include <cuda.h>
#include <stdint.h>

typedef unsigned long long u64;

#define W_FRONT 4
#define W_KV 5
#define W_TAIL 3

namespace {

constexpr int NB = 8, DM = 576, HQ = 32, HKV = 16, SK = 8192, WIN = 2048, DH = 128, FF = 4608;
constexpr int NCTA = 128;
constexpr int NCW = 10;
constexpr int NTHREADS = (NCW + 1) * 32;
constexpr int TILE_BYTES = 8192, NSLOT = 8, NT = 64;
constexpr int SPIN_LIMIT = 1 << 22;

constexpr int OFF_RING = 0;
constexpr int OFF_GU = 65536;
constexpr int GU_HALF = DM * 40 * 2;
constexpr int OFF_WQ = OFF_GU;
constexpr int OFF_WM = OFF_GU + 36864;
constexpr int OFF_WO = OFF_GU + 2 * GU_HALF;
constexpr int OFF_P = OFF_WO + 36864;
constexpr int P_PITCH = 528;
constexpr int OFF_RED = OFF_P + 16 * P_PITCH;
constexpr int OFF_H2 = OFF_RED + 9216;
constexpr int H2_PITCH = 1168;
constexpr int OFF_AF = OFF_H2 + 8 * H2_PITCH;
constexpr int OFF_ST = OFF_AF + 36 * 32 * 4;
constexpr int OFF_BAR = OFF_ST + 256;
constexpr int BAR_FULL = 0, BAR_EMPTY = 8, BAR_WQ = 16, BAR_WO = 20, BAR_GU = 24, BAR_WD = 36, NBAR = 42;
constexpr int SMEM_BYTES = OFF_BAR + NBAR * 8 + 1024;

__device__ unsigned g_epoch;
__device__ u64 g_h[72 * 32];
__device__ u64 g_sc[NB * DM];
__device__ u64 g_gg[NB * DM];
__device__ u64 g_q[NB * HQ * 64];
__device__ u64 g_o[512 * 32];
__device__ u64 g_p1[HKV * NB * DM];
__device__ u64 g_x1[NB * DM / 2];
__device__ u64 g_act[576 * 32];
__device__ u64 g_p2[HKV * NB * DM];

#define TS(i)
#define TSL(i)

struct Params {
    CUtensorMap mk, mv, mwq, mwo, mwg, mwu, mwd;
    const __nv_bfloat16 *x, *c, *wmod, *wr;
    __nv_bfloat16* out;
    int wfront, wkv, wtail;
};

__device__ __forceinline__ void mbar_init(uint32_t bar, int cnt) {
    asm volatile("mbarrier.init.shared::cta.b64 [%0], %1;" ::"r"(bar), "r"(cnt));
}
__device__ __forceinline__ void mbar_expect(uint32_t bar, uint32_t bytes) {
    asm volatile("mbarrier.arrive.expect_tx.shared::cta.b64 _, [%0], %1;" ::"r"(bar), "r"(bytes) : "memory");
}
__device__ __forceinline__ void mbar_arrive(uint32_t bar) {
    asm volatile("mbarrier.arrive.shared::cta.b64 _, [%0];" ::"r"(bar) : "memory");
}
__device__ __forceinline__ void mbar_wait(uint32_t bar, uint32_t parity) {
    uint32_t ok;
    int it = 0;
    do {
        asm volatile("{\n.reg .pred p;\nmbarrier.try_wait.parity.shared::cta.b64 p, [%1], %2;\nselp.u32 %0, 1, 0, p;\n}"
                     : "=r"(ok) : "r"(bar), "r"(parity) : "memory");
    } while (!ok && ++it < SPIN_LIMIT);
}
__device__ __forceinline__ void tma2d(uint32_t dst, const CUtensorMap* m, int x, int y, uint32_t bar) {
    asm volatile("cp.async.bulk.tensor.2d.shared::cluster.global.mbarrier::complete_tx::bytes [%0], [%1, {%2, %3}], [%4];"
                 ::"r"(dst), "l"(m), "r"(x), "r"(y), "r"(bar) : "memory");
}
__device__ __forceinline__ void tma3d_hint(uint32_t dst, const CUtensorMap* m, int x, int y, int z, uint32_t bar, u64 pol) {
    asm volatile("cp.async.bulk.tensor.3d.shared::cluster.global.mbarrier::complete_tx::bytes.L2::cache_hint"
                 " [%0], [%1, {%2, %3, %4}], [%5], %6;"
                 ::"r"(dst), "l"(m), "r"(x), "r"(y), "r"(z), "r"(bar), "l"(pol) : "memory");
}
__device__ __forceinline__ void bar_sync(int id, int n) { asm volatile("bar.sync %0, %1;" ::"r"(id), "r"(n) : "memory"); }
__device__ __forceinline__ void bar_arrive(int id, int n) { asm volatile("bar.arrive %0, %1;" ::"r"(id), "r"(n) : "memory"); }
__device__ __forceinline__ void ldsm4(uint32_t (&r)[4], uint32_t a) {
    asm volatile("ldmatrix.sync.aligned.m8n8.x4.shared.b16 {%0,%1,%2,%3}, [%4];"
                 : "=r"(r[0]), "=r"(r[1]), "=r"(r[2]), "=r"(r[3]) : "r"(a) : "memory");
}
__device__ __forceinline__ void ldsm4t(uint32_t (&r)[4], uint32_t a) {
    asm volatile("ldmatrix.sync.aligned.m8n8.x4.trans.shared.b16 {%0,%1,%2,%3}, [%4];"
                 : "=r"(r[0]), "=r"(r[1]), "=r"(r[2]), "=r"(r[3]) : "r"(a) : "memory");
}
__device__ __forceinline__ void mma(float (&c)[4], uint32_t a0, uint32_t a1, uint32_t a2, uint32_t a3, uint32_t b0, uint32_t b1) {
    asm volatile("mma.sync.aligned.m16n8k16.row.col.f32.bf16.bf16.f32 {%0,%1,%2,%3}, {%4,%5,%6,%7}, {%8,%9}, {%0,%1,%2,%3};"
                 : "+f"(c[0]), "+f"(c[1]), "+f"(c[2]), "+f"(c[3])
                 : "r"(a0), "r"(a1), "r"(a2), "r"(a3), "r"(b0), "r"(b1));
}
__device__ __forceinline__ uint32_t movm(uint32_t a) {
    uint32_t d;
    asm volatile("movmatrix.sync.aligned.m8n8.trans.b16 %0, %1;" : "=r"(d) : "r"(a));
    return d;
}
__device__ __forceinline__ uint32_t lds32(uint32_t a) { uint32_t v; asm volatile("ld.shared.b32 %0, [%1];" : "=r"(v) : "r"(a) : "memory"); return v; }
__device__ __forceinline__ float ldsf(uint32_t a) { return __uint_as_float(lds32(a)); }
__device__ __forceinline__ float2 lds64f(uint32_t a) { float2 v; asm volatile("ld.shared.v2.f32 {%0,%1}, [%2];" : "=f"(v.x), "=f"(v.y) : "r"(a) : "memory"); return v; }
__device__ __forceinline__ uint4 lds128(uint32_t a) { uint4 v; asm volatile("ld.shared.v4.b32 {%0,%1,%2,%3}, [%4];" : "=r"(v.x), "=r"(v.y), "=r"(v.z), "=r"(v.w) : "r"(a) : "memory"); return v; }
__device__ __forceinline__ void sts32(uint32_t a, uint32_t v) { asm volatile("st.shared.b32 [%0], %1;" ::"r"(a), "r"(v) : "memory"); }
__device__ __forceinline__ void sts16(uint32_t a, uint16_t v) { asm volatile("st.shared.b16 [%0], %1;" ::"r"(a), "h"(v) : "memory"); }
__device__ __forceinline__ void sts64(uint32_t a, uint32_t x, uint32_t y) { asm volatile("st.shared.v2.b32 [%0], {%1,%2};" ::"r"(a), "r"(x), "r"(y) : "memory"); }
__device__ __forceinline__ void sts128(uint32_t a, uint32_t x, uint32_t y, uint32_t z, uint32_t w) {
    asm volatile("st.shared.v4.b32 [%0], {%1,%2,%3,%4};" ::"r"(a), "r"(x), "r"(y), "r"(z), "r"(w) : "memory");
}
__device__ __forceinline__ void sts128f(uint32_t a, const float (&c)[4]) {
    sts128(a, __float_as_uint(c[0]), __float_as_uint(c[1]), __float_as_uint(c[2]), __float_as_uint(c[3]));
}

__device__ __forceinline__ u64 mkword(uint32_t payload, uint32_t tag) { return ((u64)tag << 32) | payload; }
__device__ __forceinline__ void ll_st1(u64* p, uint32_t payload, uint32_t tag) {
    asm volatile("st.relaxed.gpu.global.b64 [%0], %1;" ::"l"(p), "l"(mkword(payload, tag)) : "memory");
}
__device__ __forceinline__ void ll_st2(u64* p, uint32_t a, uint32_t b, uint32_t tag) {
    asm volatile("st.relaxed.gpu.global.v2.b64 [%0], {%1,%2};" ::"l"(p), "l"(mkword(a, tag)), "l"(mkword(b, tag)) : "memory");
}
__device__ __forceinline__ bool ll_ld1(const u64* p, uint32_t tag, uint32_t& a) {
    u64 v;
    asm volatile("ld.relaxed.gpu.global.b64 %0, [%1];" : "=l"(v) : "l"(p) : "memory");
    a = (uint32_t)v;
    return (uint32_t)(v >> 32) == tag;
}
__device__ __forceinline__ bool ll_ld2(const u64* p, uint32_t tag, uint32_t& a, uint32_t& b) {
    u64 v, w;
    asm volatile("ld.relaxed.gpu.global.v2.b64 {%0,%1}, [%2];" : "=l"(v), "=l"(w) : "l"(p) : "memory");
    a = (uint32_t)v;
    b = (uint32_t)w;
    return (uint32_t)(v >> 32) == tag && (uint32_t)(w >> 32) == tag;
}
__device__ __forceinline__ void ll_probe(const u64* p, uint32_t tag) {
    uint32_t a;
    int it = 0;
    while (!ll_ld1(p, tag, a) && ++it < SPIN_LIMIT) {}
    __syncwarp();
}
template <int N>
__device__ __forceinline__ void ll_get1(const u64* p, int stride, uint32_t tag, uint32_t (&a)[N]) {
    int it = 0;
    bool ok;
    do {
        ok = true;
#pragma unroll
        for (int i = 0; i < N; i++) ok &= ll_ld1(p + i * stride, tag, a[i]);
    } while (!ok && ++it < SPIN_LIMIT);
    __syncwarp();
}
template <int N>
__device__ __forceinline__ void ll_get2(const u64* p, int stride, uint32_t tag, uint32_t (&a)[N], uint32_t (&b)[N]) {
    int it = 0;
    bool ok;
    do {
        ok = true;
#pragma unroll
        for (int i = 0; i < N; i++) ok &= ll_ld2(p + i * stride, tag, a[i], b[i]);
    } while (!ok && ++it < SPIN_LIMIT);
    __syncwarp();
}

__device__ __forceinline__ float rbf(float x) { return __bfloat162float(__float2bfloat16_rn(x)); }
__device__ __forceinline__ uint32_t pack2(float lo, float hi) {
    uint32_t r;
    asm("cvt.rn.bf16x2.f32 %0, %1, %2;" : "=r"(r) : "f"(hi), "f"(lo));
    return r;
}
__device__ __forceinline__ float blo(uint32_t v) { return __uint_as_float(v << 16); }
__device__ __forceinline__ float bhi(uint32_t v) { return __uint_as_float(v & 0xffff0000u); }
__device__ __forceinline__ float silu_f(float x) { return x / (1.0f + __expf(-x)); }
__device__ __forceinline__ float warp_sum(float v) {
#pragma unroll
    for (int o = 16; o; o >>= 1) v += __shfl_xor_sync(0xffffffffu, v, o);
    return v;
}
__device__ __forceinline__ void ln_stats(const uint32_t (&v)[9], float& mean_b, float& den_b) {
    float s = 0.f;
#pragma unroll
    for (int i = 0; i < 9; i++) s += blo(v[i]) + bhi(v[i]);
    const float mean = warp_sum(s) * (1.0f / DM);
    float q = 0.f;
#pragma unroll
    for (int i = 0; i < 9; i++) {
        const float a = blo(v[i]) - mean, b = bhi(v[i]) - mean;
        q += a * a + b * b;
    }
    const float var = warp_sum(q) * (1.0f / DM);
    mean_b = rbf(mean);
    den_b = rbf(sqrtf(rbf(rbf(var) + 1e-5f)));
}
__device__ __forceinline__ float modulate(float x, float mean_b, float den_b, float shift, float scale) {
    const float n = rbf(rbf(x - mean_b) / den_b);
    return rbf(rbf(n * rbf(1.0f + scale)) + shift);
}

template <int NU>
__device__ __forceinline__ void proj72(uint32_t sm, uint32_t wbase, uint32_t wbar, int nwbar, const u64* src, u64* dst,
                                       int warp, int lane, uint32_t tag) {
    const int tid = warp * 32 + lane;
    if (tid < NU * 8) {
        uint32_t a[2], b[2];
        ll_get2<2>(src + tid * 2, NU * 16, tag, a, b);
        sts64(sm + OFF_AF + tid * 8, a[0], b[0]);
        sts64(sm + OFF_AF + NU * 64 + tid * 8, a[1], b[1]);
    }
    for (int i = 0; i < nwbar; i++) mbar_wait(wbar + i * 8, 0);
    uint32_t w[NU / 4][4];
#pragma unroll
    for (int i = 0; i < NU / 4; i++) ldsm4t(w[i], wbase + (i * 32 + lane) * 144 + warp * 16);
    bar_sync(3, 288);
    float acc[4][4] = {};
#pragma unroll
    for (int i = 0; i < NU / 4; i++) {
        const uint32_t a0 = lds32(sm + OFF_AF + (4 * i + 0) * 128 + lane * 4), a1 = lds32(sm + OFF_AF + (4 * i + 1) * 128 + lane * 4);
        const uint32_t a2 = lds32(sm + OFF_AF + (4 * i + 2) * 128 + lane * 4), a3 = lds32(sm + OFF_AF + (4 * i + 3) * 128 + lane * 4);
        mma(acc[(2 * i) & 3], a0, 0u, a1, 0u, w[i][0], w[i][1]);
        mma(acc[(2 * i + 1) & 3], a2, 0u, a3, 0u, w[i][2], w[i][3]);
    }
    const float c0 = (acc[0][0] + acc[1][0]) + (acc[2][0] + acc[3][0]);
    const float c1 = (acc[0][1] + acc[1][1]) + (acc[2][1] + acc[3][1]);
    ll_st2(dst + (lane >> 2) * DM + warp * 8 + (lane & 3) * 2, __float_as_uint(c0), __float_as_uint(c1), tag);
}

__device__ __forceinline__ void reduce16(const u64* part, int lane, uint32_t tag, float& s0, float& s1) {
    ll_probe(part + (lane & 15) * (NB * DM) + (lane >> 4) * 63, tag);
    uint32_t a[16], b[16];
    ll_get2<16>(part + lane * 2, NB * DM, tag, a, b);
    s0 = 0.f;
    s1 = 0.f;
#pragma unroll
    for (int i = 0; i < 16; i++) {
        s0 += __uint_as_float(a[i]);
        s1 += __uint_as_float(b[i]);
    }
}

__global__ void __launch_bounds__(NTHREADS, 1) fused_kernel(const __grid_constant__ Params P) {
    extern __shared__ char smem_raw[];
    const uint32_t sm = ((uint32_t)__cvta_generic_to_shared(smem_raw) + 1023u) & ~1023u;
    const int tid = threadIdx.x, warp = tid >> 5, lane = tid & 31;
    const int cta = blockIdx.x, grp = cta >> 3, sub = cta & 7;
    const uint32_t bars = sm + OFF_BAR;

    if (warp == NCW) {
        if (lane == 0) {
            TS(0);
            for (int i = 0; i < NBAR; i++) mbar_init(bars + i * 8, 1);
            asm volatile("fence.mbarrier_init.release.cluster;" ::: "memory");
        }
        if (lane < 7) asm volatile("prefetch.tensormap [%0];" ::"l"(&P.mk + lane) : "memory");
        __syncwarp();
        bar_arrive(15, NTHREADS);
        if (lane == 0) {
            u64 pol;
            asm volatile("createpolicy.fractional.L2::evict_first.b64 %0, 1.0;" : "=l"(pol));
            const int row0 = (sub * HKV + grp) * SK + (SK - WIN);
            const int fcol = grp * 288 + (sub >> 1) * 72 + (sub & 1) * 32;
            constexpr int I_KV = 4, I_WO = I_KV + 2 * NT, I_GU = I_WO + 4, I_WD = I_GU + 12, I_END = I_WD + 6;
            for (int n = 0; n < I_END; n++) {
                const int wn = n - (n < I_KV + NSLOT ? P.wfront : n < I_WO ? P.wkv : P.wtail);
                if (wn >= 0) {
                    if (wn < I_KV) mbar_wait(bars + (BAR_WQ + wn) * 8, 0);
                    else if (wn < I_WO) mbar_wait(bars + (BAR_FULL + ((wn - I_KV) & 7)) * 8, ((wn - I_KV) >> 3) & 1);
                    else mbar_wait(bars + (BAR_WO + wn - I_WO) * 8, 0);
                }
                if (n < I_KV) {
                    const uint32_t bar = bars + (BAR_WQ + n) * 8;
                    mbar_expect(bar, 9216);
                    tma2d(sm + OFF_WQ + n * 9216, &P.mwq, cta * 32, n * 144, bar);
                } else if (n < I_WO) {
                    const int t = n - I_KV, slot = t & 7;
                    if (t >= NSLOT) mbar_wait(bars + (BAR_EMPTY + slot) * 8, ((t >> 3) - 1) & 1);
                    const uint32_t bar = bars + (BAR_FULL + slot) * 8;
                    mbar_expect(bar, TILE_BYTES);
                    tma3d_hint(sm + OFF_RING + slot * TILE_BYTES, t < NT ? &P.mk : &P.mv, 0, row0 + (t & (NT - 1)) * 32, 0, bar, pol);
                } else if (n < I_GU) {
                    const int i = n - I_WO;
                    const uint32_t bar = bars + (BAR_WO + i) * 8;
                    mbar_expect(bar, 9216);
                    tma2d(sm + OFF_WO + i * 9216, &P.mwo, sub * 72, grp * 256 + i * 64, bar);
                } else if (n < I_WD) {
                    const int i = n - I_GU;
                    const uint32_t bar = bars + (BAR_GU + i) * 8;
                    mbar_expect(bar, 7680);
                    tma2d(sm + OFF_GU + (i & 1) * GU_HALF + (i >> 1) * 7680, (i & 1) ? &P.mwu : &P.mwg, fcol, (i >> 1) * 96, bar);
                } else {
                    const int i = n - I_WD;
                    mbar_wait(bars + (BAR_EMPTY + i) * 8, 1);
                    const uint32_t bar = bars + (BAR_WD + i) * 8;
                    mbar_expect(bar, 6912);
                    tma2d(sm + OFF_RING + i * 6912, &P.mwd, sub * 72, grp * 288 + i * 48, bar);
                }
            }
            TS(1);
        }
        return;
    }

    const int g = lane >> 2, t4 = lane & 3;
    int ucnt, ulo[2], uhi[2];
    {
        const int n0 = 2 * (cta - 72), n1 = cta < 72 ? 112 + cta : n0 + 1;
        ucnt = (cta >= 32 && cta < 72) ? 1 : 2;
        ulo[0] = cta < 72 ? 8 * cta : n0 < 72 ? 3 * DM + 8 * n0 : 2 * DM + 8 * (n0 - 72);
        uhi[0] = cta < 72 ? DM + 8 * cta : n0 < 72 ? 4 * DM + 8 * n0 : 5 * DM + 8 * (n0 - 72);
        ulo[1] = n1 < 72 ? 3 * DM + 8 * n1 : 2 * DM + 8 * (n1 - 72);
        uhi[1] = n1 < 72 ? 4 * DM + 8 * n1 : 5 * DM + 8 * (n1 - 72);
    }
#pragma unroll
    for (int u = 0; u < 2; u++) {
        if (u < ucnt) {
            for (int i = tid; i < 2 * DM; i += NCW * 32) {
                const int hi = i >= DM, r = i - hi * DM;
                const __nv_bfloat16* src = P.wmod + (size_t)r * (6 * DM) + (hi ? uhi[u] : ulo[u]);
                asm volatile("cp.async.cg.shared.global [%0], [%1], 16;" ::"r"(sm + OFF_WM + u * 18432 + i * 16), "l"(src) : "memory");
            }
        }
        asm volatile("cp.async.commit_group;" ::: "memory");
    }
    uint32_t tag;
    asm volatile("ld.relaxed.gpu.global.u32 %0, [%1];" : "=r"(tag) : "l"(&g_epoch) : "memory");
    tag += 1;

    uint32_t sfrag[8];
    float xa = 0.f, xb = 0.f;
    if (warp < 9) {
        const uint32_t* c32 = reinterpret_cast<const uint32_t*>(P.c) + g * (DM / 2) + warp * 32 + t4;
        uint32_t cv[8];
#pragma unroll
        for (int i = 0; i < 8; i++) cv[i] = __ldg(c32 + i * 4);
        if (warp < 8 && cta < 72) {
            const uint32_t* x32 = reinterpret_cast<const uint32_t*>(P.x) + warp * (DM / 2) + lane;
            uint32_t xv[9];
#pragma unroll
            for (int i = 0; i < 9; i++) xv[i] = __ldg(x32 + i * 32);
            float mb, db;
            ln_stats(xv, mb, db);
            if (lane == 0) sts64(sm + OFF_ST + warp * 8, __float_as_uint(mb), __float_as_uint(db));
        }
#pragma unroll
        for (int i = 0; i < 8; i++) sfrag[i] = pack2(silu_f(blo(cv[i])), silu_f(bhi(cv[i])));
    } else if (cta < 72) {
        xa = __bfloat162float(P.x[(2 * t4) * DM + 8 * cta + g]);
        xb = __bfloat162float(P.x[(2 * t4 + 1) * DM + 8 * cta + g]);
    }
    bar_sync(15, NTHREADS);
#pragma unroll
    for (int u = 0; u < 2; u++) {
        if (u < ucnt) {
            if (u == 0) asm volatile("cp.async.wait_group 1;" ::: "memory");
            else asm volatile("cp.async.wait_group 0;" ::: "memory");
            bar_sync(1, NCW * 32);
            if (warp < 9) {
                float acc[2][4] = {};
#pragma unroll
                for (int i = 0; i < 4; i++) {
                    uint32_t a[4];
                    ldsm4t(a, sm + OFF_WM + u * 18432 + ((lane >> 3) & 1) * 9216 + (warp * 64 + i * 16 + (lane >> 4) * 8 + (lane & 7)) * 16);
                    mma(acc[i & 1], a[0], a[1], a[2], a[3], sfrag[2 * i], sfrag[2 * i + 1]);
                }
#pragma unroll
                for (int j = 0; j < 4; j++) acc[0][j] += acc[1][j];
                sts128f(sm + OFF_RED + u * 4608 + warp * 512 + lane * 16, acc[0]);
                bar_arrive(4 + u, NCW * 32);
            } else {
                bar_sync(4 + u, NCW * 32);
                float c[4] = {};
#pragma unroll
                for (int w = 0; w < 9; w++) {
                    const uint4 v = lds128(sm + OFF_RED + u * 4608 + w * 512 + lane * 16);
                    c[0] += __uint_as_float(v.x); c[1] += __uint_as_float(v.y);
                    c[2] += __uint_as_float(v.z); c[3] += __uint_as_float(v.w);
                }
                if (u == 0 && cta < 72) {
                    const uint4 st = lds128(sm + OFF_ST + t4 * 16);
                    const float h0 = modulate(xa, __uint_as_float(st.x), __uint_as_float(st.y), rbf(c[0]), rbf(c[2]));
                    const float h1 = modulate(xb, __uint_as_float(st.z), __uint_as_float(st.w), rbf(c[1]), rbf(c[3]));
                    ll_st1(g_h + cta * 32 + lane, movm(pack2(h0, h1)), tag);
                    TSL(2);
                } else {
                    const uint32_t lo = movm(pack2(c[0], c[1])), hi = movm(pack2(c[2], c[3]));
                    const int col = ulo[u] % DM;
                    u64* dst = (ulo[u] >= 3 * DM ? g_sc : g_gg) + g * DM + col + 2 * t4;
                    ll_st2(dst, __byte_perm(lo, hi, 0x5410), __byte_perm(lo, hi, 0x7632), tag);
                }
            }
        }
    }

    if (warp < 9) {
#pragma unroll
        for (int i = 0; i < 4; i++) mbar_wait(bars + (BAR_WQ + i) * 8, 0);
        uint32_t a[4][2][4];
#pragma unroll
        for (int i = 0; i < 4; i++)
#pragma unroll
            for (int m = 0; m < 2; m++) {
                const int r = warp * 64 + i * 16 + (lane >> 4) * 8 + (lane & 7);
                const int ch = m * 2 + ((lane >> 3) & 1);
                ldsm4t(a[i][m], sm + OFF_WQ + r * 64 + ((ch ^ ((r >> 1) & 3)) << 4));
            }
        uint32_t hf[8];
        ll_get1<8>(g_h + warp * 256 + lane, 32, tag, hf);
        if (warp == 0) TSL(3);
        float acc[2][4] = {};
#pragma unroll
        for (int i = 0; i < 4; i++)
#pragma unroll
            for (int m = 0; m < 2; m++) mma(acc[m], a[i][m][0], a[i][m][1], a[i][m][2], a[i][m][3], hf[2 * i], hf[2 * i + 1]);
        sts128f(sm + OFF_H2 + warp * 1024 + lane * 16, acc[0]);
        sts128f(sm + OFF_H2 + warp * 1024 + 512 + lane * 16, acc[1]);
        bar_sync(3, 288);
        if (warp < 2) {
            float c[4] = {};
#pragma unroll
            for (int w = 0; w < 9; w++) {
                const uint4 v = lds128(sm + OFF_H2 + w * 1024 + warp * 512 + lane * 16);
                c[0] += __uint_as_float(v.x); c[1] += __uint_as_float(v.y);
                c[2] += __uint_as_float(v.z); c[3] += __uint_as_float(v.w);
            }
            const uint32_t lo = movm(pack2(c[0], c[1])), hi = movm(pack2(c[2], c[3]));
            ll_st2(g_q + ((g * HQ + (cta >> 2)) * 8 + (cta & 3) * 2 + warp) * 8 + t4 * 2, lo, hi, tag);
            if (warp == 0) TSL(4);
        }
    }

    if (warp < 8) {
        const uint32_t tile = sm + OFF_RING + warp * TILE_BYTES;
        const uint32_t fullb = bars + (BAR_FULL + warp) * 8, emptyb = bars + (BAR_EMPTY + warp) * 8;
        const uint32_t pw = sm + OFF_P + warp * (2 * P_PITCH);
        {
            uint32_t q0[8], q1[8];
            ll_get2<8>(g_q + (sub * HQ + 2 * grp + (g & 1)) * 64 + t4 * 2, 8, tag, q0, q1);
            if (warp == 0) TSL(5);
            const int key = (lane & 7) + ((lane >> 3) & 1) * 8, cs = lane >> 4;
            for (int it = 0; it < 8; it++) {
                mbar_wait(fullb, it & 1);
                float acc[2][2][4] = {};
#pragma unroll
                for (int ks = 0; ks < 8; ks++)
#pragma unroll
                    for (int m = 0; m < 2; m++) {
                        uint32_t a[4];
                        ldsm4(a, tile + (ks >> 2) * 4096 + (m * 16 + key) * 128 + ((((ks & 3) * 2 + cs) ^ (lane & 7)) << 4));
                        mma(acc[m][ks & 1], a[0], a[1], a[2], a[3], q0[ks], q1[ks]);
                    }
                __syncwarp();
                if (lane == 0) mbar_arrive(emptyb);
#pragma unroll
                for (int m = 0; m < 2; m++) {
                    const float s0 = acc[m][0][0] + acc[m][1][0], s1 = acc[m][0][1] + acc[m][1][1];
                    const float s2 = acc[m][0][2] + acc[m][1][2], s3 = acc[m][0][3] + acc[m][1][3];
                    const float s = (t4 & 2) ? ((t4 & 1) ? s3 : s2) : ((t4 & 1) ? s1 : s0);
                    const __nv_bfloat16 sb = __float2bfloat16_rn(rbf(s) * 0.08838834764831845f);
                    sts16(pw + (t4 & 1) * P_PITCH + (it * 32 + m * 16 + (t4 >> 1) * 8 + g) * 2, __bfloat16_as_ushort(sb));
                }
            }
        }
        __syncwarp();
        if (warp == 7) TSL(6);
        {
            const int h = lane >> 4;
            const uint32_t pa = pw + h * P_PITCH + (lane & 15) * 32;
            const uint4 v0 = lds128(pa), v1 = lds128(pa + 16);
            const uint32_t sv[8] = {v0.x, v0.y, v0.z, v0.w, v1.x, v1.y, v1.z, v1.w};
            float e[16];
            float m = -INFINITY;
#pragma unroll
            for (int i = 0; i < 8; i++) {
                e[2 * i] = blo(sv[i]);
                e[2 * i + 1] = bhi(sv[i]);
                m = fmaxf(m, fmaxf(e[2 * i], e[2 * i + 1]));
            }
#pragma unroll
            for (int o = 8; o; o >>= 1) m = fmaxf(m, __shfl_xor_sync(0xffffffffu, m, o));
            float l = 0.f;
#pragma unroll
            for (int i = 0; i < 16; i++) {
                e[i] = __expf(e[i] - m);
                l += e[i];
            }
#pragma unroll
            for (int o = 8; o; o >>= 1) l += __shfl_xor_sync(0xffffffffu, l, o);
            if ((lane & 15) == 0) sts64(sm + OFF_ST + 64 + h * 64 + warp * 8, __float_as_uint(m), __float_as_uint(l));
            bar_sync(2, 256);
            float mw[8], lw[8], M = -INFINITY, L = 0.f;
#pragma unroll
            for (int w = 0; w < 8; w++) {
                const float2 v = lds64f(sm + OFF_ST + 64 + h * 64 + w * 8);
                mw[w] = v.x;
                lw[w] = v.y;
                M = fmaxf(M, v.x);
            }
#pragma unroll
            for (int w = 0; w < 8; w++) L += lw[w] * __expf(mw[w] - M);
            const float sc = __expf(m - M) / L;
            sts128(pa, pack2(e[0] * sc, e[1] * sc), pack2(e[2] * sc, e[3] * sc), pack2(e[4] * sc, e[5] * sc), pack2(e[6] * sc, e[7] * sc));
            sts128(pa + 16, pack2(e[8] * sc, e[9] * sc), pack2(e[10] * sc, e[11] * sc), pack2(e[12] * sc, e[13] * sc), pack2(e[14] * sc, e[15] * sc));
            __syncwarp();
        }
        {
            float acc[8][4] = {};
            const int key = (lane & 7) + (lane >> 4) * 8, cs = (lane >> 3) & 1;
            for (int it = 0; it < 8; it++) {
                uint32_t pb[4];
#pragma unroll
                for (int i = 0; i < 4; i++) pb[i] = lds32(pw + (g & 1) * P_PITCH + (it * 32 + i * 8 + 2 * t4) * 2);
                mbar_wait(fullb, it & 1);
#pragma unroll
                for (int ks = 0; ks < 2; ks++)
#pragma unroll
                    for (int m = 0; m < 8; m++) {
                        uint32_t a[4];
                        ldsm4t(a, tile + (m >> 2) * 4096 + (ks * 16 + key) * 128 + ((((m & 3) * 2 + cs) ^ (lane & 7)) << 4));
                        mma(acc[m], a[0], a[1], a[2], a[3], pb[2 * ks], pb[2 * ks + 1]);
                    }
                __syncwarp();
                if (lane == 0) mbar_arrive(emptyb);
            }
            if (warp == 7) TSL(7);
#pragma unroll
            for (int m = 0; m < 8; m++) {
                const float s = (t4 & 2) ? ((t4 & 1) ? acc[m][3] : acc[m][2]) : ((t4 & 1) ? acc[m][1] : acc[m][0]);
                sts32(sm + OFF_RED + warp * 1088 + (t4 & 1) * 576 + (m * 16 + (t4 >> 1) * 8 + g) * 4, __float_as_uint(s));
            }
            bar_sync(2, 256);
            if (warp < 4) {
                float s0 = 0.f, s1 = 0.f;
#pragma unroll
                for (int w = 0; w < 8; w++) {
                    const float2 v = lds64f(sm + OFF_RED + w * 1088 + (tid >> 6) * 576 + (tid & 63) * 8);
                    s0 += v.x;
                    s1 += v.y;
                }
                ll_st1(g_o + (grp * 32 + (tid >> 2)) * 32 + sub * 4 + t4, pack2(s0, s1), tag);
                if (warp == 0) TSL(8);
            }
        }
    }

    const int rb = cta / 9, rc = (cta % 9) * 64 + 2 * lane;
    uint32_t x1pair = 0, gb0 = 0, gb1 = 0;
    if (warp < 9) {
        proj72<32>(sm, sm + OFF_WO, bars + BAR_WO * 8, 4, g_o + grp * 1024, g_p1 + grp * (NB * DM) + sub * 72, warp, lane, tag);
        if (warp == 0) TSL(9);
        if (warp < 8) {
            uint32_t m0[9], m1[9], wr[9], xv[9];
            ll_get2<9>(g_sc + warp * DM + 2 * lane, 64, tag, m0, m1);
#pragma unroll
            for (int i = 0; i < 9; i++) wr[i] = __ldg(reinterpret_cast<const uint32_t*>(P.wr) + lane + 32 * i);
            ll_probe(g_x1 + warp * (DM / 2), tag);
            ll_get1<9>(g_x1 + warp * (DM / 2) + lane, 32, tag, xv);
            if (warp == 0) TSL(11);
            float mb, db, r = 0.f;
            ln_stats(xv, mb, db);
#pragma unroll
            for (int i = 0; i < 9; i++) {
                const float h0 = modulate(blo(xv[i]), mb, db, blo(m0[i]), bhi(m0[i]));
                const float h1 = modulate(bhi(xv[i]), mb, db, blo(m1[i]), bhi(m1[i]));
                sts32(sm + OFF_H2 + warp * H2_PITCH + (lane + 32 * i) * 4, pack2(h0, h1));
                r += h0 * blo(wr[i]) + h1 * bhi(wr[i]);
            }
            if (warp == rb) {
                r = rbf(warp_sum(r));
                if (lane == 0) sts32(sm + OFF_ST + 192, __float_as_uint(rbf(1.0f / (1.0f + __expf(-r)))));
            }
        }
    } else if (cta < 72) {
        const uint32_t xp = __ldg(reinterpret_cast<const uint32_t*>(P.x + rb * DM + rc));
        uint32_t ga[1], gb[1];
        ll_get2<1>(g_gg + rb * DM + rc, 0, tag, ga, gb);
        gb0 = ga[0];
        gb1 = gb[0];
        mbar_wait(bars + (BAR_WO + 0) * 8, 0);
        float s0, s1;
        reduce16(g_p1 + rb * DM + (rc - 2 * lane), lane, tag, s0, s1);
        x1pair = pack2(blo(xp) + rbf(blo(gb0) * rbf(s0)), bhi(xp) + rbf(blo(gb1) * rbf(s1)));
        ll_st1(g_x1 + rb * (DM / 2) + (rc >> 1), x1pair, tag);
        TSL(10);
    }

    {
        const int mt = warp >> 1, kh = warp & 1;
#pragma unroll
        for (int i = 0; i < 6; i++) mbar_wait(bars + (BAR_GU + kh * 6 + i) * 8, 0);
        uint32_t a[18][4];
        const uint32_t abase = sm + OFF_GU + ((lane >> 3) & 1) * GU_HALF + (kh * 288 + (lane >> 4) * 8 + (lane & 7)) * 80 + mt * 16;
#pragma unroll
        for (int i = 0; i < 18; i++) ldsm4t(a[i], abase + i * 16 * 80);
        if (warp == 9) TSL(12);
        bar_sync(1, NCW * 32);
        float acc[2][4] = {};
#pragma unroll
        for (int i = 0; i < 9; i++) {
            uint32_t b[4];
            ldsm4(b, sm + OFF_H2 + (lane & 7) * H2_PITCH + kh * 576 + i * 64 + (lane >> 3) * 16);
            mma(acc[0], a[2 * i][0], a[2 * i][1], a[2 * i][2], a[2 * i][3], b[0], b[1]);
            mma(acc[1], a[2 * i + 1][0], a[2 * i + 1][1], a[2 * i + 1][2], a[2 * i + 1][3], b[2], b[3]);
        }
#pragma unroll
        for (int j = 0; j < 4; j++) acc[0][j] += acc[1][j];
        if (kh) {
            sts128f(sm + OFF_RED + mt * 512 + lane * 16, acc[0]);
            bar_arrive(6 + mt, 64);
        } else {
            bar_sync(6 + mt, 64);
            const uint4 v = lds128(sm + OFF_RED + mt * 512 + lane * 16);
            const float g0 = rbf(acc[0][0] + __uint_as_float(v.x)), g1 = rbf(acc[0][1] + __uint_as_float(v.y));
            const float u0 = rbf(acc[0][2] + __uint_as_float(v.z)), u1 = rbf(acc[0][3] + __uint_as_float(v.w));
            const uint32_t w = movm(pack2(rbf(silu_f(g0)) * u0, rbf(silu_f(g1)) * u1));
            if (mt + (sub & 1) * 4 != 4 || !(sub & 1))
                ll_st1(g_act + (grp * 36 + (sub >> 1) * 9 + (sub & 1) * 4 + mt) * 32 + lane, w, tag);
            if (warp == 0) TSL(13);
        }
    }

    if (warp < 9) {
        proj72<36>(sm, sm + OFF_RING, bars + BAR_WD * 8, 6, g_act + grp * 1152, g_p2 + grp * (NB * DM) + sub * 72, warp, lane, tag);
        if (warp == 0) TSL(14);
    } else if (cta < 72) {
        const uint32_t hp = lds32(sm + OFF_H2 + rb * H2_PITCH + rc * 2);
        const float rs = ldsf(sm + OFF_ST + 192);
        float s0, s1;
        reduce16(g_p2 + rb * DM + (rc - 2 * lane), lane, tag, s0, s1);
        const float y0 = rbf(blo(hp) + rbf(rbf(s0) * rs)), y1 = rbf(bhi(hp) + rbf(rbf(s1) * rs));
        *reinterpret_cast<uint32_t*>(P.out + rb * DM + rc) =
            pack2(blo(x1pair) + rbf(bhi(gb0) * y0), bhi(x1pair) + rbf(bhi(gb1) * y1));
        if (cta == 0 && lane == 0) g_epoch = tag;
        TSL(15);
    }
}

typedef CUresult (*EncodeFn)(CUtensorMap*, CUtensorMapDataType, cuuint32_t, void*, const cuuint64_t*, const cuuint64_t*,
                             const cuuint32_t*, const cuuint32_t*, CUtensorMapInterleave, CUtensorMapSwizzle,
                             CUtensorMapL2promotion, CUtensorMapFloatOOBfill);

#define PROMO_W CU_TENSOR_MAP_L2_PROMOTION_L2_256B
#define PROMO_KV CU_TENSOR_MAP_L2_PROMOTION_L2_256B
constexpr int dbg_wfront = W_FRONT, dbg_wkv = W_KV, dbg_wtail = W_TAIL, dbg_promo_w = PROMO_W, dbg_promo_kv = PROMO_KV;

void make2d(EncodeFn enc, CUtensorMap* m, void* p, int cols, int rows, int bc, int br, CUtensorMapSwizzle sw) {
    cuuint64_t dims[2] = {(cuuint64_t)cols, (cuuint64_t)rows};
    cuuint64_t strides[1] = {(cuuint64_t)cols * 2};
    cuuint32_t box[2] = {(cuuint32_t)bc, (cuuint32_t)br};
    cuuint32_t es[2] = {1, 1};
    enc(m, CU_TENSOR_MAP_DATA_TYPE_BFLOAT16, 2, p, dims, strides, box, es, CU_TENSOR_MAP_INTERLEAVE_NONE, sw,
        (CUtensorMapL2promotion)dbg_promo_w, CU_TENSOR_MAP_FLOAT_OOB_FILL_NONE);
}
void make_kv(EncodeFn enc, CUtensorMap* m, void* p) {
    cuuint64_t dims[3] = {64, (cuuint64_t)NB * HKV * SK, 2};
    cuuint64_t strides[2] = {DH * 2, 128};
    cuuint32_t box[3] = {64, 32, 2};
    cuuint32_t es[3] = {1, 1, 1};
    enc(m, CU_TENSOR_MAP_DATA_TYPE_BFLOAT16, 3, p, dims, strides, box, es, CU_TENSOR_MAP_INTERLEAVE_NONE,
        CU_TENSOR_MAP_SWIZZLE_128B, (CUtensorMapL2promotion)dbg_promo_kv, CU_TENSOR_MAP_FLOAT_OOB_FILL_NONE);
}

}

extern "C" void kernel_launch(void* const* d_in, const int* in_sizes, int n_in, void* d_out, int out_size) {
    static EncodeFn enc = nullptr;
    if (!enc) {
        void* fn = nullptr;
        cudaDriverEntryPointQueryResult st;
        cudaGetDriverEntryPoint("cuTensorMapEncodeTiled", &fn, cudaEnableDefault, &st);
        enc = (EncodeFn)fn;
        cudaFuncSetAttribute(fused_kernel, cudaFuncAttributeMaxDynamicSharedMemorySize, SMEM_BYTES);
    }
    Params P;
    make_kv(enc, &P.mk, d_in[1]);
    make_kv(enc, &P.mv, d_in[2]);
    make2d(enc, &P.mwq, d_in[3], HQ * DH, DM, 32, 144, CU_TENSOR_MAP_SWIZZLE_64B);
    make2d(enc, &P.mwo, d_in[4], DM, HQ * DH, 72, 64, CU_TENSOR_MAP_SWIZZLE_NONE);
    make2d(enc, &P.mwg, d_in[7], FF, DM, 40, 96, CU_TENSOR_MAP_SWIZZLE_NONE);
    make2d(enc, &P.mwu, d_in[8], FF, DM, 40, 96, CU_TENSOR_MAP_SWIZZLE_NONE);
    make2d(enc, &P.mwd, d_in[9], DM, FF, 72, 48, CU_TENSOR_MAP_SWIZZLE_NONE);
    P.x = (const __nv_bfloat16*)d_in[0];
    P.wr = (const __nv_bfloat16*)d_in[6];
    P.c = (const __nv_bfloat16*)d_in[10];
    P.wmod = (const __nv_bfloat16*)d_in[11];
    P.out = (__nv_bfloat16*)d_out;
    P.wfront = dbg_wfront;
    P.wkv = dbg_wkv;
    P.wtail = dbg_wtail;
    fused_kernel<<<NCTA, NTHREADS, SMEM_BYTES>>>(P);
}
```

```cpp
#include <cuda_runtime.h>
#include <cuda_bf16.h>
#include <cuda.h>
#include <stdint.h>

typedef unsigned long long u64;

#define W_FRONT 3
#define W_KV 5
#define W_TAIL 3

#define POS_WO 14
#define POS_TAIL 138

namespace {

constexpr int NB = 8, DM = 576, HQ = 32, HKV = 16, SK = 8192, WIN = 2048, DH = 128, FF = 4608;
constexpr int NCTA = 128;
constexpr int NCW = 10;
constexpr int NTHREADS = (NCW + 1) * 32;
constexpr int TILE_BYTES = 8192, NSLOT = 8, NT = 64;
constexpr int SPIN_LIMIT = 1 << 22;

constexpr int OFF_RING = 0;
constexpr int OFF_GU = 65536;
constexpr int GU_HALF = DM * 40 * 2;
constexpr int OFF_WQ = OFF_GU;
constexpr int OFF_WM = OFF_GU + 36864;
constexpr int OFF_WO = OFF_GU + 2 * GU_HALF;
constexpr int OFF_P = OFF_WO + 36864;
constexpr int P_PITCH = 528;
constexpr int OFF_RED = OFF_P + 16 * P_PITCH;
constexpr int OFF_H2 = OFF_RED + 9216;
constexpr int H2_PITCH = 1168;
constexpr int OFF_AF = OFF_H2 + 8 * H2_PITCH;
constexpr int OFF_ST = OFF_AF + 36 * 32 * 4;
constexpr int OFF_BAR = OFF_ST + 256;
constexpr int BAR_WM = 0, BAR_WQ = 3, BAR_WO = 6, BAR_GU = 10, BAR_WD = 22, BAR_FULL = 28, BAR_EMPTY = 36, BAR_IDLE = 44, NBAR = 45;
constexpr int I_WQ = 3, I_K0 = 6, I_GU = I_K0 + 2 * NT + 4, I_WD = I_GU + 12, I_END = I_WD + 6;
constexpr int SMEM_BYTES = OFF_BAR + NBAR * 8 + 1024;

constexpr int G_H = 0;
constexpr int G_M = G_H + 72 * 32;
constexpr int G_X1 = G_M + NB * 2 * DM;
constexpr int G_Q = G_X1 + NB * DM / 2;
constexpr int G_O = G_Q + NB * HQ * 64;
constexpr int G_ACT = G_O + 512 * 32;
constexpr int G_P = G_ACT + 576 * 32;
constexpr int G_END = G_P + 2 * HKV * NB * DM;
__device__ unsigned g_epoch;
__device__ __align__(256) u64 g_s[G_END];

#define TS(i)
#define TSL(i)

enum { M_K, M_V, M_WG, M_WU, M_WO, M_WD, M_WQ, M_WM, M_WA, NMAP };
struct Params {
    CUtensorMap m[NMAP];
    const __nv_bfloat16 *x, *c, *wr;
    __nv_bfloat16* out;
    int wfront, wkv, wtail, iwo, itail, mode;
};

__device__ __forceinline__ void mbar_init(uint32_t bar, int cnt) {
    asm volatile("mbarrier.init.shared::cta.b64 [%0], %1;" ::"r"(bar), "r"(cnt));
}
__device__ __forceinline__ void mbar_expect(uint32_t bar, uint32_t bytes) {
    asm volatile("mbarrier.arrive.expect_tx.shared::cta.b64 _, [%0], %1;" ::"r"(bar), "r"(bytes) : "memory");
}
__device__ __forceinline__ void mbar_arrive(uint32_t bar) {
    asm volatile("mbarrier.arrive.shared::cta.b64 _, [%0];" ::"r"(bar) : "memory");
}
__device__ __forceinline__ void mbar_wait(uint32_t bar, uint32_t parity) {
    uint32_t ok;
    int it = 0;
    do {
        asm volatile("{\n.reg .pred p;\nmbarrier.try_wait.parity.shared::cta.b64 p, [%1], %2;\nselp.u32 %0, 1, 0, p;\n}"
                     : "=r"(ok) : "r"(bar), "r"(parity) : "memory");
    } while (!ok && ++it < SPIN_LIMIT);
}
__device__ __forceinline__ bool mbar_test(uint32_t bar, uint32_t parity) {
    uint32_t ok;
    asm volatile("{\n.reg .pred p;\nmbarrier.test_wait.parity.shared::cta.b64 p, [%1], %2;\nselp.u32 %0, 1, 0, p;\n}"
                 : "=r"(ok) : "r"(bar), "r"(parity) : "memory");
    return ok;
}
__device__ __forceinline__ void mbar_wait_lanes(uint32_t bar) {
    mbar_wait(bar, 0);
    __syncwarp();
}
__device__ __forceinline__ void tma3d_hint(uint32_t dst, const CUtensorMap* m, int x, int y, int z, uint32_t bar, u64 pol) {
    asm volatile("cp.async.bulk.tensor.3d.shared::cluster.global.mbarrier::complete_tx::bytes.L2::cache_hint"
                 " [%0], [%1, {%2, %3, %4}], [%5], %6;"
                 ::"r"(dst), "l"(m), "r"(x), "r"(y), "r"(z), "r"(bar), "l"(pol) : "memory");
}
__device__ __forceinline__ void bar_sync(int id, int n) { asm volatile("bar.sync %0, %1;" ::"r"(id), "r"(n) : "memory"); }
__device__ __forceinline__ void bar_arrive(int id, int n) { asm volatile("bar.arrive %0, %1;" ::"r"(id), "r"(n) : "memory"); }
__device__ __forceinline__ void ldsm4(uint32_t (&r)[4], uint32_t a) {
    asm volatile("ldmatrix.sync.aligned.m8n8.x4.shared.b16 {%0,%1,%2,%3}, [%4];"
                 : "=r"(r[0]), "=r"(r[1]), "=r"(r[2]), "=r"(r[3]) : "r"(a) : "memory");
}
__device__ __forceinline__ void ldsm4t(uint32_t (&r)[4], uint32_t a) {
    asm volatile("ldmatrix.sync.aligned.m8n8.x4.trans.shared.b16 {%0,%1,%2,%3}, [%4];"
                 : "=r"(r[0]), "=r"(r[1]), "=r"(r[2]), "=r"(r[3]) : "r"(a) : "memory");
}
__device__ __forceinline__ void mma(float (&c)[4], uint32_t a0, uint32_t a1, uint32_t a2, uint32_t a3, uint32_t b0, uint32_t b1) {
    asm volatile("mma.sync.aligned.m16n8k16.row.col.f32.bf16.bf16.f32 {%0,%1,%2,%3}, {%4,%5,%6,%7}, {%8,%9}, {%0,%1,%2,%3};"
                 : "+f"(c[0]), "+f"(c[1]), "+f"(c[2]), "+f"(c[3])
                 : "r"(a0), "r"(a1), "r"(a2), "r"(a3), "r"(b0), "r"(b1));
}
__device__ __forceinline__ uint32_t movm(uint32_t a) {
    uint32_t d;
    asm volatile("movmatrix.sync.aligned.m8n8.trans.b16 %0, %1;" : "=r"(d) : "r"(a));
    return d;
}
__device__ __forceinline__ uint32_t lds32(uint32_t a) { uint32_t v; asm volatile("ld.shared.b32 %0, [%1];" : "=r"(v) : "r"(a) : "memory"); return v; }
__device__ __forceinline__ float ldsf(uint32_t a) { return __uint_as_float(lds32(a)); }
__device__ __forceinline__ float2 lds64f(uint32_t a) { float2 v; asm volatile("ld.shared.v2.f32 {%0,%1}, [%2];" : "=f"(v.x), "=f"(v.y) : "r"(a) : "memory"); return v; }
__device__ __forceinline__ uint4 lds128(uint32_t a) { uint4 v; asm volatile("ld.shared.v4.b32 {%0,%1,%2,%3}, [%4];" : "=r"(v.x), "=r"(v.y), "=r"(v.z), "=r"(v.w) : "r"(a) : "memory"); return v; }
__device__ __forceinline__ void sts32(uint32_t a, uint32_t v) { asm volatile("st.shared.b32 [%0], %1;" ::"r"(a), "r"(v) : "memory"); }
__device__ __forceinline__ void sts16(uint32_t a, uint16_t v) { asm volatile("st.shared.b16 [%0], %1;" ::"r"(a), "h"(v) : "memory"); }
__device__ __forceinline__ void sts64(uint32_t a, uint32_t x, uint32_t y) { asm volatile("st.shared.v2.b32 [%0], {%1,%2};" ::"r"(a), "r"(x), "r"(y) : "memory"); }
__device__ __forceinline__ void sts128(uint32_t a, uint32_t x, uint32_t y, uint32_t z, uint32_t w) {
    asm volatile("st.shared.v4.b32 [%0], {%1,%2,%3,%4};" ::"r"(a), "r"(x), "r"(y), "r"(z), "r"(w) : "memory");
}
__device__ __forceinline__ void sts128f(uint32_t a, const float (&c)[4]) {
    sts128(a, __float_as_uint(c[0]), __float_as_uint(c[1]), __float_as_uint(c[2]), __float_as_uint(c[3]));
}

__device__ __forceinline__ void cp16(uint32_t dst, const void* src) {
    asm volatile("cp.async.cg.shared.global [%0], [%1], 16;" ::"r"(dst), "l"(src) : "memory");
}
__device__ __forceinline__ float sel4(const float (&c)[4], int t) { return (t & 2) ? ((t & 1) ? c[3] : c[2]) : ((t & 1) ? c[1] : c[0]); }

__device__ __forceinline__ u64 mkword(uint32_t payload, uint32_t tag) { return ((u64)tag << 32) | payload; }
__device__ __forceinline__ void ll_st1(u64* p, uint32_t payload, uint32_t tag) {
    asm volatile("st.relaxed.gpu.global.b64 [%0], %1;" ::"l"(p), "l"(mkword(payload, tag)) : "memory");
}
__device__ __forceinline__ void ll_st2(u64* p, uint32_t a, uint32_t b, uint32_t tag) {
    asm volatile("st.relaxed.gpu.global.v2.b64 [%0], {%1,%2};" ::"l"(p), "l"(mkword(a, tag)), "l"(mkword(b, tag)) : "memory");
}
__device__ __forceinline__ uint32_t ll_ld1(const u64* p, uint32_t& a) {
    u64 v;
    asm volatile("ld.relaxed.gpu.global.b64 %0, [%1];" : "=l"(v) : "l"(p) : "memory");
    a = (uint32_t)v;
    return (uint32_t)(v >> 32);
}
__device__ __forceinline__ void ll_ld2(const u64* p, uint32_t& a, uint32_t& ta, uint32_t& b, uint32_t& tb) {
    u64 v, w;
    asm volatile("ld.relaxed.gpu.global.v2.b64 {%0,%1}, [%2];" : "=l"(v), "=l"(w) : "l"(p) : "memory");
    a = (uint32_t)v;
    ta = (uint32_t)(v >> 32);
    b = (uint32_t)w;
    tb = (uint32_t)(w >> 32);
}
__device__ __forceinline__ void ll_probe(const u64* p, uint32_t tag) {
    uint32_t v;
    int it = 0;
    do {
        asm volatile("ld.relaxed.gpu.global.b32 %0, [%1+4];" : "=r"(v) : "l"(p) : "memory");
    } while (!__all_sync(0xffffffffu, v == tag) && ++it < SPIN_LIMIT);
}
template <int N>
__device__ __forceinline__ void ll_get1(const u64* p, int stride, uint32_t tag, uint32_t (&a)[N]) {
    int it = 0;
    uint32_t bad;
    do {
        bad = 0;
#pragma unroll
        for (int i = 0; i < N; i++) bad |= ll_ld1(p + i * stride, a[i]) ^ tag;
    } while (__any_sync(0xffffffffu, bad != 0) && ++it < SPIN_LIMIT);
}
template <int N>
__device__ __forceinline__ void ll_get2(const u64* p, int stride, uint32_t tag, uint32_t (&a)[N], uint32_t (&b)[N]) {
    int it = 0;
    uint32_t bad;
    do {
        bad = 0;
#pragma unroll
        for (int i = 0; i < N; i++) {
            uint32_t t0, t1;
            ll_ld2(p + i * stride, a[i], t0, b[i], t1);
            bad |= (t0 ^ tag) | (t1 ^ tag);
        }
    } while (__any_sync(0xffffffffu, bad != 0) && ++it < SPIN_LIMIT);
}

__device__ __forceinline__ uint32_t pack2(float lo, float hi) {
    uint32_t r;
    asm("cvt.rn.bf16x2.f32 %0, %1, %2;" : "=r"(r) : "f"(hi), "f"(lo));
    return r;
}
__device__ __forceinline__ float rbf(float x) { return __uint_as_float(pack2(0.f, x)); }
__device__ __forceinline__ float blo(uint32_t v) { return __uint_as_float(v << 16); }
__device__ __forceinline__ float bhi(uint32_t v) { return __uint_as_float(v & 0xffff0000u); }
__device__ __forceinline__ uint32_t badd2(uint32_t a, uint32_t b) { uint32_t r; asm("add.rn.bf16x2 %0, %1, %2;" : "=r"(r) : "r"(a), "r"(b)); return r; }
__device__ __forceinline__ uint32_t bsub2(uint32_t a, uint32_t b) { uint32_t r; asm("sub.rn.bf16x2 %0, %1, %2;" : "=r"(r) : "r"(a), "r"(b)); return r; }
__device__ __forceinline__ uint32_t bmul2(uint32_t a, uint32_t b) { uint32_t r; asm("mul.rn.bf16x2 %0, %1, %2;" : "=r"(r) : "r"(a), "r"(b)); return r; }
__device__ __forceinline__ float ex2(float x) { float r; asm("ex2.approx.ftz.f32 %0, %1;" : "=f"(r) : "f"(x)); return r; }
__device__ __forceinline__ float rcp(float x) { float r; asm("rcp.approx.ftz.f32 %0, %1;" : "=f"(r) : "f"(x)); return r; }
__device__ __forceinline__ float sqrt_f(float x) { float r; asm("sqrt.approx.ftz.f32 %0, %1;" : "=f"(r) : "f"(x)); return r; }
constexpr float LOG2E = 1.4426950408889634f;
constexpr uint32_t ONE2 = 0x3f803f80u;
__device__ __forceinline__ float sigmoid_f(float x) { return rcp(1.0f + ex2(-LOG2E * x)); }
__device__ __forceinline__ uint32_t silu2(uint32_t v) {
    const float a = blo(v), b = bhi(v);
    return pack2(a * sigmoid_f(a), b * sigmoid_f(b));
}
__device__ __forceinline__ float warp_sum(float v) {
#pragma unroll
    for (int o = 16; o; o >>= 1) v += __shfl_xor_sync(0xffffffffu, v, o);
    return v;
}
__device__ __forceinline__ void ln_stats(const uint32_t (&v)[9], float& mean, float& inv) {
    float s0 = 0.f, s1 = 0.f;
#pragma unroll
    for (int i = 0; i < 9; i++) {
        s0 += blo(v[i]);
        s1 += bhi(v[i]);
    }
    mean = warp_sum(s0 + s1) * (1.0f / DM);
    s0 = s1 = 0.f;
#pragma unroll
    for (int i = 0; i < 9; i++) {
        const float a = blo(v[i]) - mean, b = bhi(v[i]) - mean;
        s0 = fmaf(a, a, s0);
        s1 = fmaf(b, b, s1);
    }
    const float var = warp_sum(s0 + s1) * (1.0f / DM);
    inv = rcp(rbf(sqrt_f(rbf(rbf(var) + 1e-5f))));
}
__device__ __forceinline__ uint32_t modulate2(uint32_t x, uint32_t mean2, float inv0, float inv1, uint32_t shift, uint32_t onep) {
    const uint32_t d = bsub2(x, mean2);
    return badd2(bmul2(pack2(blo(d) * inv0, bhi(d) * inv1), onep), shift);
}
template <int N>
__device__ __forceinline__ void sum_frags(float (&c)[4], uint32_t addr, int stride) {
#pragma unroll
    for (int w = 0; w < N; w++) {
        const uint4 v = lds128(addr + w * stride);
        c[0] += __uint_as_float(v.x); c[1] += __uint_as_float(v.y);
        c[2] += __uint_as_float(v.z); c[3] += __uint_as_float(v.w);
    }
}

__global__ void __launch_bounds__(NTHREADS, 1) fused_kernel(const __grid_constant__ Params P) {
    extern __shared__ char smem_raw[];
    const uint32_t sm = ((uint32_t)__cvta_generic_to_shared(smem_raw) + 1023u) & ~1023u;
    const int tid = threadIdx.x, lane = tid & 31;
    const int warp = __shfl_sync(0xffffffffu, tid >> 5, 0);
    const int cta = blockIdx.x, grp = cta >> 3, sub = cta & 7;
    const uint32_t bars = sm + OFF_BAR;

    if (warp == NCW) TSL(0);
    if (warp == NCW && lane < NMAP) asm volatile("prefetch.tensormap [%0];" ::"l"(&P.m[lane]) : "memory");
    if (lane == 0) {
#pragma unroll
        for (int i = 0; i < 4; i++) mbar_init(bars + warp * 32 + i * 8, 1);
        if (warp == 9) mbar_init(bars + BAR_IDLE * 8, 1);
        asm volatile("fence.mbarrier_init.release.cluster;" ::: "memory");
    }
    __syncwarp();

    if (warp == NCW) {
        u64 pol_kv, pol_w;
        asm volatile("createpolicy.fractional.L2::evict_first.b64 %0, 1.0;" : "=l"(pol_kv));
        asm volatile("createpolicy.fractional.L2::evict_normal.b64 %0, 1.0;" : "=l"(pol_w));
        const int row0 = (sub * HKV + grp) * SK + (SK - WIN);
        const uint32_t idle = bars + BAR_IDLE * 8 + 1;
        uint32_t watch = idle;
#pragma unroll 1
        for (int base = cta < 108 ? 0 : I_WQ; base < I_END; base += 32) {
            const int n = base + lane;
            int map, x = 72 * sub, y, bi = n - 2 * NT;
            uint32_t dst, bytes, need = idle, par = 0;
            if (n < I_WQ) {
                map = cta < 36 ? M_WA : M_WM, x = cta < 36 ? 16 * cta : 32 * cta, y = n * 192, bi = n;
                dst = OFF_WM + n * 12288, bytes = 12288;
            } else if (n < I_K0) {
                map = M_WQ, x = 32 * cta, y = (n - I_WQ) * 192, bi = n;
                dst = OFF_WQ + (n - I_WQ) * 12288, bytes = 12288;
            } else if (n >= P.iwo && n < P.iwo + 4) {
                map = M_WO, y = grp * 256 + (n - P.iwo) * 64, bi = BAR_WO + n - P.iwo;
                dst = OFF_WO + (n - P.iwo) * 9216, bytes = 9216;
            } else if (n < I_GU) {
                const int t = n - (n < P.iwo ? I_K0 : I_K0 + 4);
                par = (t >> 3) & 1;
                need = bars + (BAR_EMPTY + (t & 7)) * 8 + (par ^ 1);
                map = t >> 6, x = 0, y = row0 + (t & (NT - 1)) * 32, bi = BAR_FULL + (t & 7);
                dst = OFF_RING + (t & 7) * TILE_BYTES, bytes = TILE_BYTES;
            } else if (n < I_WD) {
                const int i = (n - I_GU) >> 1;
                map = M_WG + (n & 1), x = grp * 288 + (sub >> 1) * 72 + (sub & 1) * 32, y = i * 96;
                dst = OFF_GU + (n & 1) * GU_HALF + i * 7680, bytes = 7680;
            } else {
                const int i = n - I_WD;
                need = bars + (BAR_EMPTY + (i & 7)) * 8 + 1;
                map = M_WD, y = grp * 288 + i * 48;
                dst = OFF_RING + i * 6912, bytes = 6912;
            }
            const int win = n < I_K0 + NSLOT + 4 ? P.wfront : n < P.itail ? P.wkv : P.wtail;
            const uint32_t bar = bars + bi * 8;
            const CUtensorMap* mp = &P.m[map];
            const u64 pol = map <= M_V ? pol_kv : pol_w;
            if (base < 32) bar_sync(15, NTHREADS);
            const int cnt = min(32, I_END - base);
#pragma unroll 1
            for (int i = 0; i < cnt; i++) {
                if (lane == i) watch = need;
                const int wi = __shfl_sync(0xffffffffu, win, i);
                int it = 0;
                uint32_t busy;
                do {
                    const bool done = mbar_test(watch & ~7u, watch & 1);
                    if (done) watch = idle;
                    busy = __ballot_sync(0xffffffffu, !done);
                } while ((((busy >> i) & 1) | (__popc(busy) >= wi)) && ++it < SPIN_LIMIT);
                if (lane == i) {
                    mbar_expect(bar, bytes);
                    tma3d_hint(sm + dst, mp, x, y, 0, bar, pol);
                    watch = bar + par;
                }
            }
        }
        return;
    }

    const int g = lane >> 2, t4 = lane & 3;
    u64* const gs = g_s;
    uint32_t tag;
    asm volatile("ld.relaxed.gpu.global.u32 %0, [%1];" : "=r"(tag) : "l"(&g_epoch) : "memory");
    __syncwarp();
    bar_arrive(15, NTHREADS);
    u64* const dst_h = gs + G_H + (2 * cta + warp) * 32 + lane;
    u64* const dst_q = gs + G_Q + g * (HQ * 64) + cta * 16 + warp * 8 + t4 * 2;
    if (warp < 2) {
        ll_st2(dst_q, 0, 0, 0);
        if (cta < 36) ll_st1(dst_h, 0, 0);
    }

    if (warp < 9) {
        uint32_t bf[8], xp = 0;
        if (cta < 108) {
            const uint32_t* c32 = reinterpret_cast<const uint32_t*>(P.c) + g * (DM / 2) + warp * 32 + t4;
#pragma unroll
            for (int i = 0; i < 8; i++) bf[i] = __ldg(c32 + i * 4);
            if (warp < 8 && cta < 36) {
                const uint32_t* x32 = reinterpret_cast<const uint32_t*>(P.x);
                uint32_t xv[9];
#pragma unroll
                for (int i = 0; i < 9; i++) xv[i] = __ldg(x32 + warp * (DM / 2) + lane + i * 32);
                xp = __ldg(x32 + g * (DM / 2) + 8 * cta + 4 * (warp & 1) + t4);
                float mean, inv;
                ln_stats(xv, mean, inv);
                if (lane == 0) sts64(sm + OFF_ST + warp * 8, pack2(mean, mean), __float_as_uint(inv));
            }
#pragma unroll
            for (int i = 0; i < 8; i++) bf[i] = silu2(bf[i]);
        }
        tag += tag == 0xffffffffu ? 2 : 1;
        if (warp == 0) TSL(18);
        bar_sync(1, NCW * 32);
        const int r = warp * 64 + (lane >> 4) * 8 + (lane & 7), hi8 = (lane >> 3) & 1, box = warp / 3;
#pragma unroll 1
        for (int pass = cta < 108 ? 0 : 1; pass < 2; pass++) {
            const bool pa = pass == 0 && cta < 36;
            const uint32_t ab = sm + (pass ? OFF_WQ : OFF_WM) +
                                (pa ? (box + hi8) * 6144 + r * 32 + ((lane & 4) << 2) : r * 64 + (((2 * hi8) ^ ((r >> 1) & 3)) << 4));
            const uint32_t as = pa ? 512 : 1024, red = sm + (pass ? OFF_H2 : OFF_RED);
            mbar_wait(bars + (pass * 3 + box) * 8, 0);
            if (warp == 0 && pass == 0) TSL(19);
            uint32_t a[4][2][4];
#pragma unroll
            for (int i = 0; i < 4; i++) {
                ldsm4t(a[i][0], ab + i * as);
                ldsm4t(a[i][1], (ab ^ 16) + i * as);
            }
            if (pass) {
                ll_get1<8>(gs + G_H + warp * 256 + lane, 32, tag, bf);
                if (warp == 0) TSL(3);
            }
            float acc[2][4] = {};
#pragma unroll
            for (int i = 0; i < 4; i++)
#pragma unroll
                for (int m = 0; m < 2; m++) mma(acc[m], a[i][m][0], a[i][m][1], a[i][m][2], a[i][m][3], bf[2 * i], bf[2 * i + 1]);
            sts128f(red + tid * 16, acc[0]);
            sts128f(red + 4608 + tid * 16, acc[1]);
            bar_sync(3, 288);
            if (warp < 2) {
                float c[4] = {};
                sum_frags<9>(c, red + warp * 4608 + lane * 16, 512);
                uint32_t lo = movm(pack2(c[0], c[1])), hi = movm(pack2(c[2], c[3]));
                const uint32_t hi1 = badd2(hi, ONE2);
                if (pa) {
                    const float2 st = lds64f(sm + OFF_ST + g * 8);
                    ll_st1(dst_h, modulate2(xp, __float_as_uint(st.x), st.y, st.y, lo, hi1), tag);
                    if (warp == 0) TSL(2);
                } else {
                    if (!pass && cta >= 72 && cta < 90) lo = badd2(lo, ONE2), hi = hi1;
                    ll_st2(dst_q + (pass ? 0 : G_M - G_Q - 36 * 16 + g * (2 * DM - HQ * 64)), lo, hi, tag);
                    if (warp == 0 && pass) TSL(4);
                }
            }
        }
    } else {
        tag += tag == 0xffffffffu ? 2 : 1;
        bar_sync(1, NCW * 32);
    }

    const int rb = cta / 9, rp = (cta % 9) * 32 + warp * 8 + (lane & 7);
    const bool reducer = cta < 72 && warp < 4;
    const int mt = warp >> 1, kh = warp & 1;
    const bool act_writer = kh && (mt || !(sub & 1));
    const int off_o = G_O + (grp * 32 + (tid >> 2)) * 32 + sub * 4 + t4;
    const int off_p = G_P + (grp * NB + g) * DM + sub * 72 + warp * 8 + t4 * 2;
    const int off_x = G_X1 + rb * (DM / 2) + rp;
    const int off_a = G_ACT + (grp * 36 + (sub >> 1) * 9 + (sub & 1) * 4 + mt) * 32 + lane;
    auto clear_slots = [&]() {
        if (warp < 4) ll_st1(gs + off_o, 0, 0);
        if (warp < 9) {
            ll_st2(gs + off_p, 0, 0, 0);
            ll_st2(gs + off_p + HKV * NB * DM, 0, 0, 0);
        }
        if (reducer && lane < 8) ll_st1(gs + off_x, 0, 0);
        if (act_writer) ll_st1(gs + off_a, 0, 0);
    };

    if (warp < 8) {
        const uint32_t tile = sm + OFF_RING + warp * TILE_BYTES;
        const uint32_t fullb = bars + (BAR_FULL + warp) * 8, emptyb = bars + (BAR_EMPTY + warp) * 8;
        const uint32_t pw = sm + OFF_P + warp * (2 * P_PITCH);
        {
            uint32_t q0[8], q1[8];
            ll_get2<8>(gs + G_Q + (sub * HQ + 2 * grp + (g & 1)) * 64 + t4 * 2, 8, tag, q0, q1);
            if (warp == 0) TSL(5);
            const uint32_t ab = tile + (lane & 15) * 128 + (((lane >> 4) ^ (lane & 7)) << 4);
            uint32_t sp = pw + (t4 & 1) * P_PITCH + ((t4 >> 1) * 8 + g) * 2;
#pragma unroll 1
            for (int it = 0; it < 8; it++, sp += 64) {
                mbar_wait(fullb, it & 1);
                float acc[2][2][4] = {};
#pragma unroll
                for (int ks = 0; ks < 8; ks++)
#pragma unroll
                    for (int m = 0; m < 2; m++) {
                        uint32_t a[4];
                        ldsm4(a, (ab ^ ((ks & 3) << 5)) + (ks >> 2) * 4096 + m * 2048);
                        mma(acc[m][ks & 1], a[0], a[1], a[2], a[3], (ks & 1) ? q1[ks - 1] : q0[ks], (ks & 1) ? q1[ks] : q0[ks + 1]);
                    }
                __syncwarp();
                if (lane == 0) mbar_arrive(emptyb);
#pragma unroll
                for (int m = 0; m < 2; m++) {
                    const float s = sel4(acc[m][0], t4) + sel4(acc[m][1], t4);
                    sts16(sp + m * 32, (uint16_t)pack2(rbf(s) * 0.08838834764831845f, 0.f));
                }
            }
        }
        __syncwarp();
        if (warp == 7) TSL(6);
        {
            const uint32_t pa = pw + (lane >> 4) * P_PITCH + (lane & 15) * 32;
            const uint32_t sa = sm + OFF_ST + 64 + (lane >> 4) * 64;
            const uint4 v0 = lds128(pa), v1 = lds128(pa + 16);
            const uint32_t sv[8] = {v0.x, v0.y, v0.z, v0.w, v1.x, v1.y, v1.z, v1.w};
            float e[16];
            float m = -INFINITY;
#pragma unroll
            for (int i = 0; i < 8; i++) {
                e[2 * i] = blo(sv[i]);
                e[2 * i + 1] = bhi(sv[i]);
                m = fmaxf(m, fmaxf(e[2 * i], e[2 * i + 1]));
            }
#pragma unroll
            for (int o = 8; o; o >>= 1) m = fmaxf(m, __shfl_xor_sync(0xffffffffu, m, o));
            float l = 0.f;
#pragma unroll
            for (int i = 0; i < 16; i++) {
                e[i] = ex2((e[i] - m) * LOG2E);
                l += e[i];
            }
#pragma unroll
            for (int o = 8; o; o >>= 1) l += __shfl_xor_sync(0xffffffffu, l, o);
            if ((lane & 15) == 0) sts64(sa + warp * 8, __float_as_uint(m), __float_as_uint(l));
            bar_sync(2, NCW * 32);
            const float2 v = lds64f(sa + (lane & 7) * 8);
            float M = v.x;
#pragma unroll
            for (int o = 4; o; o >>= 1) M = fmaxf(M, __shfl_xor_sync(0xffffffffu, M, o));
            float L = v.y * ex2((v.x - M) * LOG2E);
#pragma unroll
            for (int o = 4; o; o >>= 1) L += __shfl_xor_sync(0xffffffffu, L, o);
            const float sc = ex2((m - M) * LOG2E) * rcp(L);
            sts128(pa, pack2(e[0] * sc, e[1] * sc), pack2(e[2] * sc, e[3] * sc), pack2(e[4] * sc, e[5] * sc), pack2(e[6] * sc, e[7] * sc));
            sts128(pa + 16, pack2(e[8] * sc, e[9] * sc), pack2(e[10] * sc, e[11] * sc), pack2(e[12] * sc, e[13] * sc), pack2(e[14] * sc, e[15] * sc));
            __syncwarp();
        }
    } else {
        bar_sync(2, NCW * 32);
    }
    clear_slots();
    if (warp < 8) {
        const uint32_t tile = sm + OFF_RING + warp * TILE_BYTES;
        const uint32_t fullb = bars + (BAR_FULL + warp) * 8, emptyb = bars + (BAR_EMPTY + warp) * 8;
        const uint32_t pw = sm + OFF_P + warp * (2 * P_PITCH);
        {
            float acc[8][4] = {};
            const uint32_t ab = tile + ((lane & 7) + (lane >> 4) * 8) * 128 + ((((lane >> 3) & 1) ^ (lane & 7)) << 4);
            uint32_t pp = pw + (lane & 1) * P_PITCH + (lane >> 3) * 16;
#pragma unroll 1
            for (int it = 0; it < 8; it++, pp += 64) {
                uint32_t pb[4];
                ldsm4(pb, pp);
                mbar_wait(fullb, it & 1);
#pragma unroll
                for (int ks = 0; ks < 2; ks++)
#pragma unroll
                    for (int m = 0; m < 8; m++) {
                        uint32_t a[4];
                        ldsm4t(a, (ab ^ ((m & 3) << 5)) + (m >> 2) * 4096 + ks * 2048);
                        mma(acc[m], a[0], a[1], a[2], a[3], pb[2 * ks], pb[2 * ks + 1]);
                    }
                __syncwarp();
                if (lane == 0) mbar_arrive(emptyb);
            }
            if (warp == 7) TSL(7);
            const uint32_t ra = sm + OFF_RED + warp * 1088 + (t4 & 1) * 576 + ((t4 >> 1) * 8 + g) * 4;
#pragma unroll
            for (int m = 0; m < 8; m++) sts32(ra + m * 64, __float_as_uint(sel4(acc[m], t4)));
            bar_sync(5, NCW * 32);
            if (warp < 4) {
                float s0 = 0.f, s1 = 0.f;
#pragma unroll
                for (int w = 0; w < 8; w++) {
                    const float2 v = lds64f(sm + OFF_RED + w * 1088 + (tid >> 6) * 64 + tid * 8);
                    s0 += v.x;
                    s1 += v.y;
                }
                ll_st1(gs + off_o, pack2(s0, s1), tag);
                if (warp == 0) TSL(8);
            }
        }
    } else {
        bar_sync(5, NCW * 32);
    }

    uint32_t rx = 0, rg[2] = {0, 0};
#pragma unroll
    for (int st = 0; st < 2; st++) {
        u64* const part = gs + G_P + st * (HKV * NB * DM);
        if (warp < 9) {
            const u64* src = gs + (st ? G_ACT + grp * 1152 : G_O + grp * 1024) + tid * 2;
            const int d2 = st || tid < 224 ? 576 : 0;
            const uint32_t wbar = bars + (st ? BAR_WD + lane % 6 : BAR_WO + t4) * 8;
            const uint32_t wb = sm + (st ? OFF_RING : OFF_WO) + lane * 144 + warp * 16;
            uint32_t w[9][4];
            const bool pre = __all_sync(0xffffffffu, mbar_test(wbar, 0));
#pragma unroll
            for (int i = 0; i < 9; i++) ldsm4t(w[i], wb + i * 4608);
            {
                uint32_t a0, a1, b0, b1, t0, t1, t2, t3;
                int it = 0;
                do {
                    ll_ld2(src, a0, t0, b0, t1);
                    ll_ld2(src + d2, a1, t2, b1, t3);
                } while ((((t0 ^ tag) | (t1 ^ tag)) | ((t2 ^ tag) | (t3 ^ tag))) && ++it < SPIN_LIMIT);
                sts64(sm + OFF_AF + tid * 8, a0, b0);
                sts64(sm + OFF_AF + tid * 8 + d2 * 4, a1, b1);
                __syncwarp();
            }
            if (warp == 0) TSL(st ? 24 : 21);
            bar_sync(3, st ? 320 : 288);
            uint32_t f[9][4];
            const uint32_t fa = sm + OFF_AF + (lane & 7) * 16 + ((lane >> 3) & 1) * 256 + (lane >> 4) * 128;
#pragma unroll
            for (int i = 0; i < 9; i++) ldsm4(f[i], fa + i * 512);
            if (!pre) {
                mbar_wait_lanes(wbar);
#pragma unroll
                for (int i = 0; i < 9; i++) ldsm4t(w[i], wb + i * 4608);
            }
            float acc[4][4] = {};
#pragma unroll
            for (int i = 0; i < 9; i++) {
                if (i < 8 || st) {
                    mma(acc[(2 * i) & 3], f[i][0], f[i][1], f[i][2], f[i][3], w[i][0], w[i][1]);
                    mma(acc[(2 * i + 1) & 3], f[i][0], f[i][1], f[i][2], f[i][3], w[i][2], w[i][3]);
                }
            }
            const float c0 = (acc[0][0] + acc[1][2]) + (acc[2][0] + acc[3][2]);
            const float c1 = (acc[0][1] + acc[1][3]) + (acc[2][1] + acc[3][3]);
            ll_st2(gs + off_p + st * (HKV * NB * DM), __float_as_uint(c0), __float_as_uint(c1), tag);
            if (warp == 0) TSL(st ? 14 : 9);
        }
        uint32_t sh[9] = {}, op[9] = {};
        const uint32_t ab = sm + OFF_GU + ((lane >> 3) & 1) * GU_HALF + (kh * 288 + (lane >> 4) * 8 + (lane & 7)) * 80 + mt * 16;
        const uint32_t gbar = bars + (BAR_GU + kh * 6 + (lane & 1)) * 8;
        uint32_t a[18][4], gpre = 0;
        if (st == 0) {
            if (warp < 8) {
                const u64* mp = gs + G_M + warp * (2 * DM) + (lane & 16) + (lane & 7) * 2 + ((lane >> 3) & 1);
                ll_get1<9>(mp + 288, 32, tag, sh);
                ll_get1<9>(mp + 576, 32, tag, op);
                if (reducer) {
                    rx = __ldg(reinterpret_cast<const uint32_t*>(P.x) + rb * (DM / 2) + rp);
                    ll_get1<2>(gs + G_M + rb * (2 * DM) + (rp & ~15) + (rp & 7) * 2 + ((rp >> 3) & 1), 864, tag, rg);
                }
            } else if (warp == 9) {
                ll_probe(part + (lane & 15) * (NB * DM) + sub * 72, tag);
                TSL(27);
            }
#pragma unroll
            for (int j = 0; j < 3; j++) {
                if (__all_sync(0xffffffffu, mbar_test(gbar + j * 16, 0))) gpre |= 1 << j;
            }
#pragma unroll
            for (int i = 0; i < 18; i++) ldsm4t(a[i], ab + i * 1280);
            bar_sync(1, NCW * 32);
        }
        if (reducer) {
            uint32_t rh = 0, rs = 0;
            if (st) {
                rh = lds32(sm + OFF_H2 + rb * H2_PITCH + rp * 4);
                rs = lds32(sm + OFF_ST + 192);
            }
            uint32_t pa[4], pb[4];
            ll_get2<4>(part + ((lane >> 3) * 4 * NB + rb) * DM + rp * 2, NB * DM, tag, pa, pb);
            float s0 = (__uint_as_float(pa[0]) + __uint_as_float(pa[1])) + (__uint_as_float(pa[2]) + __uint_as_float(pa[3]));
            float s1 = (__uint_as_float(pb[0]) + __uint_as_float(pb[1])) + (__uint_as_float(pb[2]) + __uint_as_float(pb[3]));
#pragma unroll
            for (int o = 8; o < 32; o <<= 1) {
                s0 += __shfl_xor_sync(0xffffffffu, s0, o);
                s1 += __shfl_xor_sync(0xffffffffu, s1, o);
            }
            uint32_t y = pack2(s0, s1);
            if (st) y = badd2(rh, bmul2(y, rs));
            rx = badd2(rx, bmul2(st ? rg[1] : rg[0], y));
            if (lane < 8) {
                if (st) reinterpret_cast<uint32_t*>(P.out)[rb * (DM / 2) + rp] = rx;
                else ll_st1(gs + off_x, rx, tag);
            }
            if (st && cta == 0 && tid == 0) g_epoch = tag;
            if (warp == 0) TSL(st ? 15 : 10);
        }
        if (st) break;

        uint32_t xv[9];
        if (warp < 8) {
            ll_get1<9>(gs + G_X1 + warp * (DM / 2) + lane, 32, tag, xv);
            if (warp == 0) TSL(11);
            float mean, inv;
            ln_stats(xv, mean, inv);
            const uint32_t mean2 = pack2(mean, mean);
#pragma unroll
            for (int i = 0; i < 9; i++)
                sts32(sm + OFF_H2 + warp * H2_PITCH + (lane + 32 * i) * 4, modulate2(xv[i], mean2, inv, inv, sh[i], op[i]));
            if (warp == 0) TSL(12);
        } else {
#pragma unroll
            for (int i = 0; i < 9; i++) xv[i] = __ldg(reinterpret_cast<const uint32_t*>(P.wr) + lane + 32 * i);
        }
        bar_sync(1, NCW * 32);

        const uint32_t bb = sm + OFF_H2 + (lane & 7) * H2_PITCH + kh * 576 + (lane >> 3) * 16;
        float acc[2][4] = {};
#pragma unroll
        for (int j = 0; j < 3; j++) {
            uint32_t b[3][4];
#pragma unroll
            for (int i = 0; i < 3; i++) ldsm4(b[i], bb + (j * 3 + i) * 64);
            if (!((gpre >> j) & 1)) {
                mbar_wait_lanes(gbar + j * 16);
#pragma unroll
                for (int i = 0; i < 6; i++) ldsm4t(a[j * 6 + i], ab + (j * 6 + i) * 1280);
            }
#pragma unroll
            for (int i = 0; i < 6; i++)
                mma(acc[i & 1], a[j * 6 + i][0], a[j * 6 + i][1], a[j * 6 + i][2], a[j * 6 + i][3], b[i >> 1][2 * (i & 1)], b[i >> 1][2 * (i & 1) + 1]);
        }
#pragma unroll
        for (int j = 0; j < 4; j++) acc[0][j] += acc[1][j];
        if (!kh) {
            sts128f(sm + OFF_RED + mt * 512 + lane * 16, acc[0]);
            bar_arrive(6 + mt, 64);
        } else {
            bar_sync(6 + mt, 64);
            sum_frags<1>(acc[0], sm + OFF_RED + mt * 512 + lane * 16, 0);
            const uint32_t w = movm(bmul2(silu2(pack2(acc[0][0], acc[0][1])), pack2(acc[0][2], acc[0][3])));
            if (act_writer) ll_st1(gs + off_a, w, tag);
            if (warp == 1) TSL(13);
        }
        if (warp == 9) {
            float r = 0.f;
#pragma unroll
            for (int i = 0; i < 9; i++) {
                const uint32_t h = lds32(sm + OFF_H2 + (rb & 7) * H2_PITCH + (lane + 32 * i) * 4);
                r = fmaf(blo(h), blo(xv[i]), fmaf(bhi(h), bhi(xv[i]), r));
            }
            r = sigmoid_f(rbf(warp_sum(r)));
            if (lane == 0) sts32(sm + OFF_ST + 192, pack2(r, r));
            __syncwarp();
            bar_arrive(3, 320);
        }
    }
}

typedef CUresult (*EncodeFn)(CUtensorMap*, CUtensorMapDataType, cuuint32_t, void*, const cuuint64_t*, const cuuint64_t*,
                             const cuuint32_t*, const cuuint32_t*, CUtensorMapInterleave, CUtensorMapSwizzle,
                             CUtensorMapL2promotion, CUtensorMapFloatOOBfill);

#define PROMO_W CU_TENSOR_MAP_L2_PROMOTION_L2_128B
#define PROMO_KV CU_TENSOR_MAP_L2_PROMOTION_L2_256B
constexpr int dbg_wfront = W_FRONT, dbg_wkv = W_KV, dbg_wtail = W_TAIL, dbg_promo_w = PROMO_W, dbg_promo_kv = PROMO_KV, dbg_iwo = POS_WO, dbg_itail = POS_TAIL, dbg_mode = 0;

void make_map(EncodeFn enc, CUtensorMap* m, void* p, int cols, int rows, int pitch, int bc, int br, int planes, int pstride,
              CUtensorMapSwizzle sw, int promo) {
    cuuint64_t dims[3] = {(cuuint64_t)cols, (cuuint64_t)rows, (cuuint64_t)planes};
    cuuint64_t strides[2] = {(cuuint64_t)pitch * 2, (cuuint64_t)pstride};
    cuuint32_t box[3] = {(cuuint32_t)bc, (cuuint32_t)br, (cuuint32_t)planes};
    cuuint32_t es[3] = {1, 1, 1};
    enc(m, CU_TENSOR_MAP_DATA_TYPE_BFLOAT16, 3, p, dims, strides, box, es, CU_TENSOR_MAP_INTERLEAVE_NONE, sw,
        (CUtensorMapL2promotion)promo, CU_TENSOR_MAP_FLOAT_OOB_FILL_NONE);
}

}

extern "C" void kernel_launch(void* const* d_in, const int* in_sizes, int n_in, void* d_out, int out_size) {
    static EncodeFn enc = nullptr;
    if (!enc) {
        void* fn = nullptr;
        cudaDriverEntryPointQueryResult st;
        cudaGetDriverEntryPoint("cuTensorMapEncodeTiled", &fn, cudaEnableDefault, &st);
        enc = (EncodeFn)fn;
        cudaFuncSetAttribute(fused_kernel, cudaFuncAttributeMaxDynamicSharedMemorySize, SMEM_BYTES);
    }
    Params P;
    const CUtensorMapSwizzle none = CU_TENSOR_MAP_SWIZZLE_NONE;
    make_map(enc, &P.m[M_K], d_in[1], 64, NB * HKV * SK, DH, 64, 32, 2, 128, CU_TENSOR_MAP_SWIZZLE_128B, dbg_promo_kv);
    make_map(enc, &P.m[M_V], d_in[2], 64, NB * HKV * SK, DH, 64, 32, 2, 128, CU_TENSOR_MAP_SWIZZLE_128B, dbg_promo_kv);
    make_map(enc, &P.m[M_WQ], d_in[3], HQ * DH, DM, HQ * DH, 32, 192, 1, 16, CU_TENSOR_MAP_SWIZZLE_64B, dbg_promo_w);
    make_map(enc, &P.m[M_WO], d_in[4], DM, HQ * DH, DM, 72, 64, 1, 16, none, dbg_promo_w);
    make_map(enc, &P.m[M_WG], d_in[7], FF, DM, FF, 40, 96, 1, 16, none, dbg_promo_w);
    make_map(enc, &P.m[M_WU], d_in[8], FF, DM, FF, 40, 96, 1, 16, none, dbg_promo_w);
    make_map(enc, &P.m[M_WD], d_in[9], DM, FF, DM, 72, 48, 1, 16, none, dbg_promo_w);
    make_map(enc, &P.m[M_WM], d_in[11], 6 * DM, DM, 6 * DM, 32, 192, 1, 16, CU_TENSOR_MAP_SWIZZLE_64B, dbg_promo_w);
    make_map(enc, &P.m[M_WA], d_in[11], DM, DM, 6 * DM, 16, 192, 2, DM * 2, CU_TENSOR_MAP_SWIZZLE_32B, dbg_promo_w);
    P.x = (const __nv_bfloat16*)d_in[0];
    P.wr = (const __nv_bfloat16*)d_in[6];
    P.c = (const __nv_bfloat16*)d_in[10];
    P.out = (__nv_bfloat16*)d_out;
    P.wfront = dbg_wfront;
    P.wkv = dbg_wkv;
    P.wtail = dbg_wtail;
    P.iwo = dbg_iwo;
    P.itail = dbg_itail;
    P.mode = dbg_mode;
    fused_kernel<<<NCTA, NTHREADS, SMEM_BYTES>>>(P);
}
```

```cpp
#include <cuda_runtime.h>
#include <cuda_bf16.h>
#include <cuda.h>
#include <stdint.h>

typedef unsigned long long u64;

#define W_FRONT 4
#define W_KV 5
#define W_TAIL 4
#define POS_WO 134
#define POS_TAIL 134

namespace {

constexpr int NB = 8, DM = 576, HQ = 32, HKV = 16, SK = 8192, WIN = 2048, DH = 128, FF = 4608;
constexpr int NCTA = 128;
constexpr int NCW = 10;
constexpr int NTHREADS = (NCW + 2) * 32;
constexpr int TILE_BYTES = 8192, NSLOT = 16, NT = 64;
constexpr int SPIN_LIMIT = 1 << 22;

constexpr int OFF_RING = 0;
constexpr int OFF_WM = 120832;
constexpr int OFF_WQ = OFF_WM + 36864;
constexpr int OFF_GU = 0;
constexpr int GU_HALF = DM * 40 * 2;
constexpr int OFF_WD = 98304;
constexpr int OFF_WO = OFF_WD + 41472;
constexpr int OFF_ORED = OFF_WO + 36864;
constexpr int OFF_P = OFF_WQ + 36864;
constexpr int P_PITCH = 528;
constexpr int OFF_RED = OFF_P + 16 * P_PITCH;
constexpr int OFF_ST = OFF_RED + 5 * 4608;
constexpr int OFF_SM = OFF_ST + 640;
constexpr int OFF_RT = OFF_SM + 128;
constexpr int OFF_HU = OFF_RT + 384;
constexpr int OFF_QS = OFF_HU + 128;
constexpr int OFF_BAR = OFF_QS + 512;
constexpr int BAR_IDLE = 6, BAR_WMF = 7, BAR_GATE = 8, BAR_WO = 9, BAR_GU = 13, BAR_WD = 31, BAR_FULL = 40, BAR_EMPTY = 56, NBAR = 77;
constexpr int SMEM_BYTES = OFF_BAR + NBAR * 8;

constexpr int G_H = 0;
constexpr int G_M = G_H + 72 * 32;
constexpr int G_X1 = G_M + 288 * 32;
constexpr int G_Q = G_X1 + 72 * 32;
constexpr int G_O = G_Q + NB * HQ * 64;
constexpr int G_ACT = G_O + 512 * 32;
constexpr int G_P = G_ACT + 576 * 32;
constexpr int G_END = G_P + 2 * HKV * NB * DM;
__device__ unsigned g_epoch;
__device__ __align__(256) u64 g_s[G_END];

#define TS(i)
#define TSL(i)

enum { M_K, M_V, M_WG, M_WU, M_WO, M_WD, M_WQ, M_WM, M_WA, NMAP };
struct Params {
    CUtensorMap m[NMAP];
    const __nv_bfloat16 *x, *c, *wr;
    __nv_bfloat16* out;
    int wfront, wkv, wtail, iwo, itail, mode, wwo, slack;
};

__device__ __forceinline__ void mbar_init(uint32_t bar, int cnt) {
    asm volatile("mbarrier.init.shared::cta.b64 [%0], %1;" ::"r"(bar), "r"(cnt));
}
__device__ __forceinline__ void mbar_expect(uint32_t bar, uint32_t bytes) {
    asm volatile("mbarrier.arrive.expect_tx.shared::cta.b64 _, [%0], %1;" ::"r"(bar), "r"(bytes) : "memory");
}
__device__ __forceinline__ void mbar_arrive(uint32_t bar) {
    asm volatile("mbarrier.arrive.shared::cta.b64 _, [%0];" ::"r"(bar) : "memory");
}
__device__ __forceinline__ void mbar_wait(uint32_t bar, uint32_t parity) {
    asm volatile("{\n.reg .pred p;\n.reg .u32 c;\n"
                 "mbarrier.try_wait.parity.shared::cta.b64 p, [%0], %1;\n@p bra DONE;\nmov.u32 c, %2;\n"
                 "AGAIN:\nmbarrier.try_wait.parity.shared::cta.b64 p, [%0], %1;\nsub.u32 c, c, 1;\n"
                 "setp.eq.or.u32 p, c, 0, p;\n@!p bra AGAIN;\nDONE:\n}"
                 ::"r"(bar), "r"(parity), "n"(SPIN_LIMIT) : "memory");
}
__device__ __forceinline__ bool mbar_test(uint32_t bar, uint32_t parity) {
    uint32_t ok;
    asm volatile("{\n.reg .pred p;\nmbarrier.test_wait.parity.shared::cta.b64 p, [%1], %2;\nselp.u32 %0, 1, 0, p;\n}"
                 : "=r"(ok) : "r"(bar), "r"(parity) : "memory");
    return ok;
}
__device__ __forceinline__ void mbar_wait_lanes(uint32_t bar) {
    mbar_wait(bar, 0);
    __syncwarp();
}
__device__ __forceinline__ void tma3d_hint(uint32_t dst, const CUtensorMap* m, int x, int y, int z, uint32_t bar, u64 pol) {
    asm volatile("cp.async.bulk.tensor.3d.shared::cluster.global.mbarrier::complete_tx::bytes.L2::cache_hint"
                 " [%0], [%1, {%2, %3, %4}], [%5], %6;"
                 ::"r"(dst), "l"(m), "r"(x), "r"(y), "r"(z), "r"(bar), "l"(pol) : "memory");
}
__device__ __forceinline__ void tma3d(uint32_t dst, const CUtensorMap* m, int x, int y, int z, uint32_t bar) {
    asm volatile("cp.async.bulk.tensor.3d.shared::cluster.global.mbarrier::complete_tx::bytes [%0], [%1, {%2, %3, %4}], [%5];"
                 ::"r"(dst), "l"(m), "r"(x), "r"(y), "r"(z), "r"(bar) : "memory");
}
__device__ __forceinline__ void bar_sync(int id, int n) { asm volatile("bar.sync %0, %1;" ::"r"(id), "r"(n) : "memory"); }
__device__ __forceinline__ void bar_arrive(int id, int n) { asm volatile("bar.arrive %0, %1;" ::"r"(id), "r"(n) : "memory"); }
__device__ __forceinline__ void ldsm4(uint32_t (&r)[4], uint32_t a) {
    asm volatile("ldmatrix.sync.aligned.m8n8.x4.shared.b16 {%0,%1,%2,%3}, [%4];"
                 : "=r"(r[0]), "=r"(r[1]), "=r"(r[2]), "=r"(r[3]) : "r"(a) : "memory");
}
__device__ __forceinline__ void ldsm4t(uint32_t (&r)[4], uint32_t a) {
    asm volatile("ldmatrix.sync.aligned.m8n8.x4.trans.shared.b16 {%0,%1,%2,%3}, [%4];"
                 : "=r"(r[0]), "=r"(r[1]), "=r"(r[2]), "=r"(r[3]) : "r"(a) : "memory");
}
__device__ __forceinline__ void mma(float (&c)[4], uint32_t a0, uint32_t a1, uint32_t a2, uint32_t a3, uint32_t b0, uint32_t b1) {
    asm volatile("mma.sync.aligned.m16n8k16.row.col.f32.bf16.bf16.f32 {%0,%1,%2,%3}, {%4,%5,%6,%7}, {%8,%9}, {%0,%1,%2,%3};"
                 : "+f"(c[0]), "+f"(c[1]), "+f"(c[2]), "+f"(c[3])
                 : "r"(a0), "r"(a1), "r"(a2), "r"(a3), "r"(b0), "r"(b1));
}
__device__ __forceinline__ uint32_t movm(uint32_t a) {
    uint32_t d;
    asm volatile("movmatrix.sync.aligned.m8n8.trans.b16 %0, %1;" : "=r"(d) : "r"(a));
    return d;
}
__device__ __forceinline__ uint32_t lds32(uint32_t a) { uint32_t v; asm volatile("ld.shared.b32 %0, [%1];" : "=r"(v) : "r"(a) : "memory"); return v; }
__device__ __forceinline__ float2 lds64f(uint32_t a) { float2 v; asm volatile("ld.shared.v2.f32 {%0,%1}, [%2];" : "=f"(v.x), "=f"(v.y) : "r"(a) : "memory"); return v; }
__device__ __forceinline__ uint4 lds128(uint32_t a) { uint4 v; asm volatile("ld.shared.v4.b32 {%0,%1,%2,%3}, [%4];" : "=r"(v.x), "=r"(v.y), "=r"(v.z), "=r"(v.w) : "r"(a) : "memory"); return v; }
__device__ __forceinline__ void sts32(uint32_t a, uint32_t v) { asm volatile("st.shared.b32 [%0], %1;" ::"r"(a), "r"(v) : "memory"); }
__device__ __forceinline__ void sts16(uint32_t a, uint16_t v) { asm volatile("st.shared.b16 [%0], %1;" ::"r"(a), "h"(v) : "memory"); }
__device__ __forceinline__ void sts64(uint32_t a, uint32_t x, uint32_t y) { asm volatile("st.shared.v2.b32 [%0], {%1,%2};" ::"r"(a), "r"(x), "r"(y) : "memory"); }
__device__ __forceinline__ void sts128(uint32_t a, uint32_t x, uint32_t y, uint32_t z, uint32_t w) {
    asm volatile("st.shared.v4.b32 [%0], {%1,%2,%3,%4};" ::"r"(a), "r"(x), "r"(y), "r"(z), "r"(w) : "memory");
}
__device__ __forceinline__ void sts128f(uint32_t a, const float (&c)[4]) {
    sts128(a, __float_as_uint(c[0]), __float_as_uint(c[1]), __float_as_uint(c[2]), __float_as_uint(c[3]));
}

__device__ __forceinline__ float sel4(const float (&c)[4], int t) { return (t & 2) ? ((t & 1) ? c[3] : c[2]) : ((t & 1) ? c[1] : c[0]); }

__device__ __forceinline__ u64 mkword(uint32_t payload, uint32_t tag) { return ((u64)tag << 32) | payload; }
__device__ __forceinline__ void ll_st1(u64* p, uint32_t payload, uint32_t tag) {
    asm volatile("st.relaxed.gpu.global.b64 [%0], %1;" ::"l"(p), "l"(mkword(payload, tag)) : "memory");
}
__device__ __forceinline__ void ll_st2(u64* p, uint32_t a, uint32_t b, uint32_t tag) {
    asm volatile("st.relaxed.gpu.global.v2.b64 [%0], {%1,%2};" ::"l"(p), "l"(mkword(a, tag)), "l"(mkword(b, tag)) : "memory");
}
__device__ __forceinline__ void ll_probe(const u64* p, uint32_t tag, int slack) {
    uint32_t v;
    int it = 0;
    do {
        asm volatile("ld.relaxed.gpu.global.b32 %0, [%1+4];" : "=r"(v) : "l"(p) : "memory");
    } while (__popc(__ballot_sync(0xffffffffu, v != tag)) > slack && ++it < SPIN_LIMIT);
}
template <int N>
__device__ __forceinline__ void ll_get1(const u64* p, int stride, uint32_t tag, uint32_t (&a)[N]) {
    uint32_t t[N], bad;
    int it = 0;
#pragma unroll
    for (int i = 0; i < N; i++) t[i] = ~tag, a[i] = 0;
    do {
        bad = 0;
#pragma unroll
        for (int i = 0; i < N; i++)
            asm volatile("{\n.reg .pred p;\n.reg .b64 v;\nsetp.ne.u32 p, %1, %3;\nmov.b64 v, {%0,%1};\n"
                         "@p ld.relaxed.gpu.global.b64 v, [%2];\nmov.b64 {%0,%1}, v;\n}"
                         : "+r"(a[i]), "+r"(t[i]) : "l"(p + i * stride), "r"(tag) : "memory");
#pragma unroll
        for (int i = 0; i < N; i++) bad |= t[i] ^ tag;
    } while (__any_sync(0xffffffffu, bad != 0) && ++it < SPIN_LIMIT);
}
template <int N>
__device__ __forceinline__ void ll_get2(const u64* p, int stride, uint32_t tag, uint32_t (&a)[N], uint32_t (&b)[N]) {
    uint32_t t[N], u[N], bad;
    int it = 0;
#pragma unroll
    for (int i = 0; i < N; i++) t[i] = u[i] = ~tag, a[i] = b[i] = 0;
    do {
        bad = 0;
#pragma unroll
        for (int i = 0; i < N; i++)
            asm volatile("{\n.reg .pred p;\n.reg .b64 v, w;\nsetp.ne.u32 p, %1, %5;\nsetp.ne.or.u32 p, %3, %5, p;\n"
                         "mov.b64 v, {%0,%1};\nmov.b64 w, {%2,%3};\n@p ld.relaxed.gpu.global.v2.b64 {v, w}, [%4];\n"
                         "mov.b64 {%0,%1}, v;\nmov.b64 {%2,%3}, w;\n}"
                         : "+r"(a[i]), "+r"(t[i]), "+r"(b[i]), "+r"(u[i]) : "l"(p + i * stride), "r"(tag) : "memory");
#pragma unroll
        for (int i = 0; i < N; i++) bad |= (t[i] ^ tag) | (u[i] ^ tag);
    } while (__any_sync(0xffffffffu, bad != 0) && ++it < SPIN_LIMIT);
}

__device__ __forceinline__ uint32_t pack2(float lo, float hi) {
    uint32_t r;
    asm("cvt.rn.bf16x2.f32 %0, %1, %2;" : "=r"(r) : "f"(hi), "f"(lo));
    return r;
}
__device__ __forceinline__ float rbf(float x) { return __uint_as_float(pack2(0.f, x)); }
__device__ __forceinline__ float blo(uint32_t v) { return __uint_as_float(v << 16); }
__device__ __forceinline__ float bhi(uint32_t v) { return __uint_as_float(v & 0xffff0000u); }
__device__ __forceinline__ uint32_t badd2(uint32_t a, uint32_t b) { uint32_t r; asm("add.rn.bf16x2 %0, %1, %2;" : "=r"(r) : "r"(a), "r"(b)); return r; }
__device__ __forceinline__ uint32_t bsub2(uint32_t a, uint32_t b) { uint32_t r; asm("sub.rn.bf16x2 %0, %1, %2;" : "=r"(r) : "r"(a), "r"(b)); return r; }
__device__ __forceinline__ uint32_t bmul2(uint32_t a, uint32_t b) { uint32_t r; asm("mul.rn.bf16x2 %0, %1, %2;" : "=r"(r) : "r"(a), "r"(b)); return r; }
__device__ __forceinline__ float ex2(float x) { float r; asm("ex2.approx.ftz.f32 %0, %1;" : "=f"(r) : "f"(x)); return r; }
__device__ __forceinline__ float rcp(float x) { float r; asm("rcp.approx.ftz.f32 %0, %1;" : "=f"(r) : "f"(x)); return r; }
__device__ __forceinline__ float sqrt_f(float x) { float r; asm("sqrt.approx.ftz.f32 %0, %1;" : "=f"(r) : "f"(x)); return r; }
constexpr float LOG2E = 1.4426950408889634f;
constexpr uint32_t ONE2 = 0x3f803f80u;
__device__ __forceinline__ float sigmoid_f(float x) { return rcp(1.0f + ex2(-LOG2E * x)); }
__device__ __forceinline__ uint32_t silu2(uint32_t v) {
    const float a = blo(v), b = bhi(v);
    return pack2(a * sigmoid_f(a), b * sigmoid_f(b));
}
__device__ __forceinline__ float quad_sum(float v) {
    v += __shfl_xor_sync(0xffffffffu, v, 1);
    return v + __shfl_xor_sync(0xffffffffu, v, 2);
}
__device__ __forceinline__ void ln_partial(const uint32_t (&v)[8], uint32_t dst, bool writer) {
    float s0 = 0.f, s1 = 0.f;
#pragma unroll
    for (int i = 0; i < 8; i++) {
        s0 += blo(v[i]);
        s1 += bhi(v[i]);
    }
    const float mean = quad_sum(s0 + s1) * (1.0f / 64);
    s0 = s1 = 0.f;
#pragma unroll
    for (int i = 0; i < 8; i++) {
        const float a = blo(v[i]) - mean, b = bhi(v[i]) - mean;
        s0 = fmaf(a, a, s0);
        s1 = fmaf(b, b, s1);
    }
    s0 = quad_sum(s0 + s1);
    if (writer) sts64(dst, __float_as_uint(mean), __float_as_uint(s0));
}
__device__ __forceinline__ void ln_combine(uint32_t src, uint32_t& mean2, float& inv) {
    float m[10], q0 = 0.f, q1 = 0.f, s = 0.f;
#pragma unroll
    for (int i = 0; i < 5; i++) {
        const uint4 v = lds128(src + i * 16);
        m[2 * i] = __uint_as_float(v.x);
        m[2 * i + 1] = __uint_as_float(v.z);
        q0 += __uint_as_float(v.y);
        if (i < 4) q1 += __uint_as_float(v.w);
    }
    const float mean = (((m[0] + m[1]) + (m[2] + m[3])) + ((m[4] + m[5]) + (m[6] + m[7])) + m[8]) * (1.0f / 9);
#pragma unroll
    for (int i = 0; i < 9; i++) s = fmaf(m[i] - mean, m[i] - mean, s);
    const float var = fmaf(s, 64.f, q0 + q1) * (1.0f / DM);
    mean2 = pack2(mean, mean);
    inv = rcp(rbf(sqrt_f(rbf(rbf(var) + 1e-5f))));
}
__device__ __forceinline__ uint32_t modulate2(uint32_t x, uint32_t mean2, float inv, uint32_t shift, uint32_t onep) {
    const uint32_t d = bsub2(x, mean2);
    return badd2(bmul2(pack2(blo(d) * inv, bhi(d) * inv), onep), shift);
}
template <int N>
__device__ __forceinline__ void sum_frags(float (&c)[4], uint32_t addr, int stride) {
#pragma unroll
    for (int w = 0; w < N; w++) {
        const uint4 v = lds128(addr + w * stride);
        c[0] += __uint_as_float(v.x); c[1] += __uint_as_float(v.y);
        c[2] += __uint_as_float(v.z); c[3] += __uint_as_float(v.w);
    }
}

template <int ST>
__device__ __forceinline__ void project(uint32_t sm, const u64* src, u64* dst, int warp, int lane, uint32_t tag) {
    constexpr int NW = ST ? 9 : 8;
    const uint32_t red = sm + (ST ? OFF_WO : OFF_RED) + lane * 8;
    if (warp < NW) {
        const uint32_t wbar = sm + OFF_BAR + (ST ? BAR_WD + warp : BAR_WO + (warp >> 1)) * 8;
        const uint32_t ab = sm + (ST ? OFF_WD : OFF_WO) + (warp * 32 + (lane >> 4) * 8 + (lane & 7)) * 144 + ((lane >> 3) & 1) * 16;
        uint32_t a[10][4], b[4];
        const bool pre = __all_sync(0xffffffffu, mbar_test(wbar, 0));
#pragma unroll
        for (int i = 0; i < 10; i++) ldsm4t(a[i], ab + (i / 5) * 2304 + (i % 5) * 32);
        if (ST) {
            ll_get1<4>(src, 32, tag, b);
        } else {
            uint32_t x[2], y[2];
            ll_get2<2>(src, 2, tag, x, y);
            b[0] = x[0], b[1] = y[0], b[2] = x[1], b[3] = y[1];
        }
        if (warp == 0) TSL(ST ? 24 : 21);
        if (!pre) {
            mbar_wait_lanes(wbar);
#pragma unroll
            for (int i = 0; i < 10; i++) ldsm4t(a[i], ab + (i / 5) * 2304 + (i % 5) * 32);
        }
        float acc[5][4] = {};
#pragma unroll
        for (int i = 0; i < 10; i++) mma(acc[i % 5], a[i][0], a[i][1], a[i][2], a[i][3], b[2 * (i / 5)], b[2 * (i / 5) + 1]);
#pragma unroll
        for (int u = 0; u < 9; u++)
            sts64(red + u * 2304 + warp * 256, __float_as_uint(acc[u >> 1][2 * (u & 1)]), __float_as_uint(acc[u >> 1][2 * (u & 1) + 1]));
    }
    bar_sync(3, 288);
    float s[2][2] = {};
#pragma unroll
    for (int w = 0; w < NW; w++) {
        const float2 v = lds64f(red + warp * 2304 + w * 256);
        s[w & 1][0] += v.x;
        s[w & 1][1] += v.y;
    }
    ll_st2(dst, __float_as_uint(s[0][0] + s[1][0]), __float_as_uint(s[0][1] + s[1][1]), tag);
}

__device__ __forceinline__ uint32_t reduce16(const u64* src, int lane, uint32_t tag) {
    uint32_t a[4], b[4];
    ll_get2<4>(src, NB * DM, tag, a, b);
    float s0 = (__uint_as_float(a[0]) + __uint_as_float(a[1])) + (__uint_as_float(a[2]) + __uint_as_float(a[3]));
    float s1 = (__uint_as_float(b[0]) + __uint_as_float(b[1])) + (__uint_as_float(b[2]) + __uint_as_float(b[3]));
#pragma unroll
    for (int o = 8; o < 32; o <<= 1) {
        s0 += __shfl_xor_sync(0xffffffffu, s0, o);
        s1 += __shfl_xor_sync(0xffffffffu, s1, o);
    }
    const uint32_t y = pack2(s0, s1);
    return __byte_perm(y, __shfl_xor_sync(0xffffffffu, y, 4), (lane & 4) ? 0x3276 : 0x5410);
}

__global__ void __launch_bounds__(NTHREADS, 1) fused_kernel(const __grid_constant__ Params P) {
    extern __shared__ __align__(1024) char smem_raw[];
    const uint32_t sm = (uint32_t)__cvta_generic_to_shared(smem_raw);
    const int tid = threadIdx.x, lane = tid & 31;
    const int warp = __shfl_sync(0xffffffffu, tid >> 5, 0);
    const int cta = blockIdx.x, grp = cta >> 3, sub = cta & 7;
    const uint32_t bars = sm + OFF_BAR;

    if (lane == 0 && warp <= NCW) {
        if (warp == NCW) TS(0);
#pragma unroll
        for (int i = 0; i < 7; i++) mbar_init(bars + (warp == NCW ? 0 : 56 + warp * 56) + i * 8, 1);
        asm volatile("fence.mbarrier_init.release.cluster;" ::: "memory");
    }

    if (warp >= NCW) {
        const int pw = warp - NCW, n0 = cta < 108 ? 0 : 3;
        if (pw == 0) {
            if (lane == 0) {
#pragma unroll
                for (int i = 0; i < 3; i++) {
                    mbar_expect(bars + (n0 + i) * 8, 12288);
                    tma3d(sm + OFF_WM + (n0 + i) * 12288, &P.m[cta < 36 ? M_WA : cta < 108 ? M_WM : M_WQ],
                          cta < 36 ? 16 * cta : 32 * cta, i * 192, 0, bars + (n0 + i) * 8);
                }
                TS(26);
            }
            __syncwarp();
            bar_arrive(1, (NCW + 1) * 32);
        } else if (lane <= M_WQ) {
            asm volatile("prefetch.tensormap [%0];" ::"l"(&P.m[M_WQ - lane]) : "memory");
        }
        __syncwarp();
        bar_sync(15, NTHREADS);
        if (lane == 0) {
            u64 pol;
            asm volatile("createpolicy.fractional.L2::evict_first.b64 %0, 1.0;" : "=l"(pol));
            const int row0 = (sub * HKV + grp) * SK + (SK - WIN);
            if (n0 == 0) {
#pragma unroll 1
                for (int n = 3 + pw; n < 6; n += 2) {
                    mbar_expect(bars + n * 8, 12288);
                    if (n >= P.wfront) mbar_wait(bars + (n - P.wfront) * 8, 0);
                    tma3d(sm + OFF_WM + n * 12288, &P.m[M_WQ], 32 * cta, (n - 3) * 192, 0, bars + n * 8);
                }
            }
#pragma unroll 1
            for (int t = pw ^ 1; t < NSLOT; t += 2) {
                const int m = t - P.wfront;
                if (t >= 14 && n0 == 0) mbar_wait(bars + BAR_WMF * 8, 0);
                mbar_expect(bars + (BAR_FULL + t) * 8, TILE_BYTES);
                if (m + 6 >= n0) mbar_wait(bars + (m + (m < 0 ? 6 : BAR_FULL)) * 8, 0);
                tma3d_hint(sm + OFF_RING + t * TILE_BYTES, &P.m[M_K], 0, row0 + t * 32, 0, bars + (BAR_FULL + t) * 8, pol);
            }
            TS(30);
#pragma unroll 1
            for (int t = NSLOT + (pw ^ 1); t < 2 * NT; t += 2) {
                const int m = t - P.wkv;
                const uint32_t fb = bars + (BAR_FULL + (t & 15)) * 8;
                mbar_wait(fb + (BAR_EMPTY - BAR_FULL) * 8, (~t >> 4) & 1);
                mbar_expect(fb, TILE_BYTES);
                mbar_wait(bars + (BAR_FULL + (m & 15)) * 8, (m >> 4) & 1);
                tma3d_hint(sm + OFF_RING + (t & 15) * TILE_BYTES, &P.m[t >> 6], 0, row0 + (t & (NT - 1)) * 32, 0, fb, pol);
            }
#pragma unroll 1
            for (int j = pw ^ 1; j < 4; j += 2) {
                const int m = j - P.wwo;
                mbar_expect(bars + (BAR_WO + j) * 8, 9216);
                mbar_wait(bars + (m + (m < 0 ? BAR_FULL + 16 : BAR_WO)) * 8, m < 0);
                tma3d(sm + OFF_WO + j * 9216, &P.m[M_WO], 72 * sub, grp * 256 + j * 64, 0, bars + (BAR_WO + j) * 8);
            }
        }
        __syncwarp();
        bar_sync(14, 64);
        if (lane < 12) mbar_wait(bars + (BAR_EMPTY + lane) * 8, 1);
        __syncwarp();
        if (lane == 0) {
            if (P.mode & 2) mbar_wait(bars + BAR_GATE * 8, 0);
            TS(28);
#pragma unroll 1
            for (int i = 0; i < 9; i++) {
                const int j = BAR_GU + 2 * i + pw, m = j - P.wtail;
                mbar_expect(bars + j * 8, 5120);
                mbar_wait(bars + (m + (m < BAR_WO ? BAR_FULL + 16 - BAR_WO : 0)) * 8, m < BAR_WO);
                tma3d(sm + OFF_GU + pw * GU_HALF + i * 5120, &P.m[M_WG + pw], grp * 288 + (sub >> 1) * 72 + (sub & 1) * 32, i * 64, 0, bars + j * 8);
            }
            TS(29);
#pragma unroll
            for (int i = 12; i < 16; i++) mbar_wait(bars + (BAR_EMPTY + i) * 8, 1);
#pragma unroll 1
            for (int i = pw; i < 9; i += 2) {
                mbar_expect(bars + (BAR_WD + i) * 8, 4608);
                mbar_wait(bars + (BAR_WD + i - P.wtail) * 8, 0);
                tma3d(sm + OFF_WD + i * 4608, &P.m[M_WD], 72 * sub, grp * 288 + i * 32, 0, bars + (BAR_WD + i) * 8);
            }
        }
        return;
    }

    __syncwarp();
    bar_arrive(15, NTHREADS);
    const int g = lane >> 2, t4 = lane & 3;
    u64* const gs = g_s;
    uint32_t tag;
    asm volatile("ld.relaxed.gpu.global.u32 %0, [%1];" : "=r"(tag) : "l"(&g_epoch) : "memory");

    if (warp < 9) {
        u64* const dst_h = gs + (cta < 36 ? G_H + 2 * cta * 32 : G_M + 4 * (cta - 36) * 32) + tid;
        u64* const dst_q = gs + G_Q + g * (HQ * 64) + cta * 16 + warp * 8 + t4 * 2;
        uint32_t bf[8] = {}, xp = 0, mean2 = 0;
        float inv = 0.f;
        const int fo = g * (DM / 2) + warp * 32 + t4;
        if (cta < 108) {
#pragma unroll
            for (int i = 0; i < 8; i++) bf[i] = __ldg(reinterpret_cast<const uint32_t*>(P.c) + fo + i * 4);
        }
        if (warp < 2) ll_st2(dst_q, 0, 0, 0);
        if (cta < 36) {
            const uint32_t* x32 = reinterpret_cast<const uint32_t*>(P.x);
            uint32_t xv[8];
#pragma unroll
            for (int i = 0; i < 8; i++) xv[i] = __ldg(x32 + fo + i * 4);
            xp = __ldg(x32 + g * (DM / 2) + 8 * cta + 4 * (warp & 1) + t4);
            if (warp < 2) ll_st1(dst_h, 0, 0);
            ln_partial(xv, sm + OFF_ST + g * 80 + warp * 8, t4 == 0);
        }
#pragma unroll
        for (int i = 0; i < 8; i++) bf[i] = silu2(bf[i]);
        tag += tag == 0xffffffffu ? 2 : 1;
        if (warp == 0) TSL(18);
        bar_sync(1, (NCW + 1) * 32);
        if (cta < 36 && warp < 2) ln_combine(sm + OFF_ST + g * 80, mean2, inv);
        const int r = warp * 64 + (lane >> 4) * 8 + (lane & 7), hi8 = (lane >> 3) & 1, box = warp / 3;
#pragma unroll 1
        for (int pass = cta < 108 ? 0 : 1; pass < 2; pass++) {
            const bool pa = pass == 0 && cta < 36;
            const uint32_t ab = sm + OFF_WM + pass * 36864 +
                                (pa ? (box + hi8) * 6144 + r * 32 + ((lane & 4) << 2) : r * 64 + (((2 * hi8) ^ ((r >> 1) & 3)) << 4));
            const uint32_t as = pa ? 512 : 1024, red = sm + OFF_RED + pass * 9216;
            mbar_wait(bars + (pass * 3 + box) * 8, 0);
            if (warp == 8) TSL(pass ? 31 : 19);
            uint32_t a[4][2][4];
#pragma unroll
            for (int i = 0; i < 4; i++) {
                ldsm4t(a[i][0], ab + i * as);
                ldsm4t(a[i][1], (ab ^ 16) + i * as);
            }
            if (pass) {
                if (P.mode & 4) ll_probe(gs + G_H + warp * 256, tag, 0);
                ll_get1<8>(gs + G_H + warp * 256 + lane, 32, tag, bf);
                if (warp == 0) TSL(3);
            }
            float acc[2][4] = {};
#pragma unroll
            for (int i = 0; i < 4; i++)
#pragma unroll
                for (int m = 0; m < 2; m++) mma(acc[m], a[i][m][0], a[i][m][1], a[i][m][2], a[i][m][3], bf[2 * i], bf[2 * i + 1]);
            sts128f(red + tid * 16, acc[0]);
            sts128f(red + 4608 + tid * 16, acc[1]);
            bar_sync(3, 288);
            if (warp < 2) {
                float c[4] = {};
                sum_frags<9>(c, red + warp * 4608 + lane * 16, 512);
                uint32_t lo = movm(pack2(c[0], c[1])), hi = movm(pack2(c[2], c[3]));
                if (pass) {
                    ll_st2(dst_q, lo, hi, tag);
                    if (warp == 0) TSL(4);
                } else {
                    const uint32_t hi1 = badd2(hi, ONE2);
                    if (pa) lo = modulate2(xp, mean2, inv, lo, hi1);
                    if (cta >= 72 && cta < 90) lo = badd2(lo, ONE2), hi = hi1;
                    ll_st1(dst_h, lo, tag);
                    if (!pa) ll_st1(dst_h + 64, hi, tag);
                    if (warp == 0 && pa) TSL(2);
                }
            } else if (tid == 64 && pass == 0) {
                mbar_arrive(bars + BAR_WMF * 8);
            }
        }
    } else {
        tag += tag == 0xffffffffu ? 2 : 1;
        bar_sync(1, (NCW + 1) * 32);
        mbar_wait(bars + 5 * 8, 0);
        uint32_t a[2], b[2];
        ll_get2<2>(gs + G_Q + (sub * HQ + 2 * grp) * 64 + lane * 2, 64, tag, a, b);
        sts64(sm + OFF_QS + lane * 8, a[0], b[0]);
        sts64(sm + OFF_QS + 256 + lane * 8, a[1], b[1]);
        __syncwarp();
        TSL(5);
        bar_arrive(4, 288);
    }

    const uint32_t tile = sm + OFF_RING + warp * TILE_BYTES;
    const uint32_t fullb = bars + (BAR_FULL + warp) * 8;
    const uint32_t pw = sm + OFF_P + warp * (2 * P_PITCH);
    if (warp < 8) {
        {
            uint32_t q0[8], q1[8];
            bar_sync(4, 288);
#pragma unroll
            for (int i = 0; i < 8; i++) {
                const float2 v = lds64f(sm + OFF_QS + (g & 1) * 256 + i * 32 + t4 * 8);
                q0[i] = __float_as_uint(v.x), q1[i] = __float_as_uint(v.y);
            }
            uint32_t sp = pw + (t4 & 1) * P_PITCH + ((t4 >> 1) * 8 + g) * 2;
#pragma unroll 1
            for (int it = 0; it < 8; it++, sp += 64) {
                const uint32_t ab = tile + (it & 1) * (8 * TILE_BYTES) + (lane & 15) * 128 + (((lane >> 4) ^ (lane & 7)) << 4);
                mbar_wait(fullb + (it & 1) * 64, (it >> 1) & 1);
                float acc[2][2][4] = {};
#pragma unroll
                for (int ks = 0; ks < 8; ks++)
#pragma unroll
                    for (int m = 0; m < 2; m++) {
                        uint32_t a[4];
                        ldsm4(a, (ab ^ ((ks & 3) << 5)) + (ks >> 2) * 4096 + m * 2048);
                        mma(acc[m][ks & 1], a[0], a[1], a[2], a[3], (ks & 1) ? q1[ks - 1] : q0[ks], (ks & 1) ? q1[ks] : q0[ks + 1]);
                    }
                __syncwarp();
                if (lane == 0) mbar_arrive(fullb + (it & 1) * 64 + (BAR_EMPTY - BAR_FULL) * 8);
#pragma unroll
                for (int m = 0; m < 2; m++) {
                    const float s = sel4(acc[m][0], t4) + sel4(acc[m][1], t4);
                    sts16(sp + m * 32, (uint16_t)pack2(rbf(s) * 0.08838834764831845f, 0.f));
                }
            }
        }
        __syncwarp();
        if (warp == 7) TSL(6);
        const uint32_t pa = pw + (lane >> 4) * P_PITCH + (lane & 15) * 32;
        const uint32_t sa = sm + OFF_SM + (lane >> 4) * 64;
        const uint4 v0 = lds128(pa), v1 = lds128(pa + 16);
        const uint32_t sv[8] = {v0.x, v0.y, v0.z, v0.w, v1.x, v1.y, v1.z, v1.w};
        float e[16];
        float m = -INFINITY;
#pragma unroll
        for (int i = 0; i < 8; i++) {
            e[2 * i] = blo(sv[i]);
            e[2 * i + 1] = bhi(sv[i]);
            m = fmaxf(m, fmaxf(e[2 * i], e[2 * i + 1]));
        }
#pragma unroll
        for (int o = 8; o; o >>= 1) m = fmaxf(m, __shfl_xor_sync(0xffffffffu, m, o));
        float l = 0.f;
#pragma unroll
        for (int i = 0; i < 16; i++) {
            e[i] = ex2((e[i] - m) * LOG2E);
            l += e[i];
        }
#pragma unroll
        for (int o = 8; o; o >>= 1) l += __shfl_xor_sync(0xffffffffu, l, o);
        if ((lane & 15) == 0) sts64(sa + warp * 8, __float_as_uint(m), __float_as_uint(l));
        bar_sync(2, NCW * 32);
        const float2 v = lds64f(sa + (lane & 7) * 8);
        float M = v.x;
#pragma unroll
        for (int o = 4; o; o >>= 1) M = fmaxf(M, __shfl_xor_sync(0xffffffffu, M, o));
        float L = v.y * ex2((v.x - M) * LOG2E);
#pragma unroll
        for (int o = 4; o; o >>= 1) L += __shfl_xor_sync(0xffffffffu, L, o);
        const float sc = ex2((m - M) * LOG2E) * rcp(L);
        sts128(pa, pack2(e[0] * sc, e[1] * sc), pack2(e[2] * sc, e[3] * sc), pack2(e[4] * sc, e[5] * sc), pack2(e[6] * sc, e[7] * sc));
        sts128(pa + 16, pack2(e[8] * sc, e[9] * sc), pack2(e[10] * sc, e[11] * sc), pack2(e[12] * sc, e[13] * sc), pack2(e[14] * sc, e[15] * sc));
        __syncwarp();
    } else {
        bar_sync(2, NCW * 32);
    }

    const bool reducer = cta < 72 && warp < 4;
    const bool act_writer = warp < 5 && (warp || !(sub & 1));
    const int rbat = 2 * t4 + (g & 1);
    u64* const dst_o = gs + G_O + cta * 128 + (tid & 0x70) + (tid & 3) * 4 + ((tid >> 2) & 3);
    u64* const dst_p = gs + G_P + (grp * DM + sub * 72) * 8 + tid * 2;
    u64* const dst_x = gs + G_X1 + cta * 32 + warp * 8 + lane;
    u64* const dst_a = gs + G_ACT + (grp * 36 + (sub >> 1) * 9 + (sub & 1) * 4) * 32 + tid;
    uint32_t sh[8] = {}, op[8] = {}, wr[8] = {}, rx = 0, rg[2] = {};
    if (warp < 9) {
        if (warp < 4) ll_st1(dst_o, 0, 0);
        ll_st2(dst_p, 0, 0, 0);
        ll_st2(dst_p + HKV * NB * DM, 0, 0, 0);
        if (act_writer) ll_st1(dst_a, 0, 0);
#pragma unroll
        for (int i = 0; i < 8; i++) wr[i] = __ldg(reinterpret_cast<const uint32_t*>(P.wr) + warp * 32 + i * 4 + t4);
        if (reducer) {
            if (lane < 8) ll_st1(dst_x, 0, 0);
            rx = __ldg(reinterpret_cast<const uint32_t*>(P.x) + rbat * (DM / 2) + 4 * cta + warp);
            ll_get1<2>(gs + G_M + cta * 32 + rbat * 4 + warp, 216 * 32, tag, rg);
        }
        ll_get1<8>(gs + G_M + (72 + warp * 8) * 32 + lane, 32, tag, sh);
        ll_get1<8>(gs + G_M + (144 + warp * 8) * 32 + lane, 32, tag, op);
    }

    if (warp < 8) {
        float acc[8][4] = {};
        uint32_t pp = pw + (lane & 1) * P_PITCH + (lane >> 3) * 16;
#pragma unroll 1
        for (int it = 0; it < 8; it++, pp += 64) {
            const uint32_t ab = tile + (it & 1) * (8 * TILE_BYTES) + ((lane & 7) + (lane >> 4) * 8) * 128 + ((((lane >> 3) & 1) ^ (lane & 7)) << 4);
            uint32_t pb[4];
            ldsm4(pb, pp);
            mbar_wait(fullb + (it & 1) * 64, (it >> 1) & 1);
#pragma unroll
            for (int ks = 0; ks < 2; ks++)
#pragma unroll
                for (int m = 0; m < 8; m++) {
                    uint32_t a[4];
                    ldsm4t(a, (ab ^ ((m & 3) << 5)) + (m >> 2) * 4096 + ks * 2048);
                    mma(acc[m], a[0], a[1], a[2], a[3], pb[2 * ks], pb[2 * ks + 1]);
                }
            __syncwarp();
            if (lane == 0) mbar_arrive(fullb + (it & 1) * 64 + (BAR_EMPTY - BAR_FULL) * 8);
        }
        if (warp == 7) TSL(7);
        const uint32_t ra = sm + OFF_ORED + warp * 1088 + (t4 & 1) * 576 + ((t4 >> 1) * 8 + g) * 4;
#pragma unroll
        for (int m = 0; m < 8; m++) sts32(ra + m * 64, __float_as_uint(sel4(acc[m], t4)));
    }
    bar_sync(5, NCW * 32);
    if (warp < 4) {
        float s[2][2] = {};
#pragma unroll
        for (int w = 0; w < 8; w++) {
            const float2 v = lds64f(sm + OFF_ORED + w * 1088 + (tid >> 6) * 64 + tid * 8);
            s[w & 1][0] += v.x;
            s[w & 1][1] += v.y;
        }
        ll_st1(dst_o, pack2(s[0][0] + s[1][0], s[0][1] + s[1][1]), tag);
        if (warp == 0) TSL(8);
    }
    if (warp == 9) {
        const u64* pp = gs + G_P + ((lane & 15) * DM + (cta < 72 ? cta * 8 : cta * 8 - DM + 7)) * 8;
        if (cta < 72) {
            ll_probe(pp, tag, P.slack);
            bar_arrive(6, 160);
        }
        ll_probe(pp, tag, 0);
        TSL(27);
        bar_arrive(7, NCW * 32);
        return;
    }

    project<0>(sm, gs + G_O + (grp * 8 + g) * 128 + warp * 16 + t4 * 4, dst_p, warp, lane, tag);
    if (warp == 0) TSL(9);
    if (tid == 0) mbar_arrive(bars + BAR_GATE * 8);
    const uint32_t gbar = bars + (BAR_GU + 2 * warp + (lane & 1)) * 8;
    const uint32_t ab = sm + OFF_GU + ((lane >> 3) & 1) * GU_HALF + (warp * 64 + (lane >> 4) * 8 + (lane & 7)) * 80;
    const u64* const src_p = gs + G_P + ((lane >> 3) * 4 * DM + cta * 8 + 2 * warp) * 8 + (lane & 7) * 2;
    if (reducer) {
        bar_sync(6, 160);
        rx = badd2(rx, bmul2(rg[0], reduce16(src_p, lane, tag)));
        if (lane < 8) ll_st1(dst_x, rx, tag);
        if (warp == 0) TSL(10);
    }
    bar_sync(7, NCW * 32);
    uint32_t a[20][4];
    const bool gpre = __all_sync(0xffffffffu, mbar_test(gbar, 0));
#pragma unroll
    for (int i = 0; i < 20; i++) ldsm4t(a[i], ab + (i / 5) * 1280 + (i % 5) * 16);

    uint32_t h[8];
    ll_get1<8>(gs + G_X1 + warp * 256 + t4 * 8 + (g & 1) * 4 + (g >> 1), 32, tag, h);
    if (warp == 0) TSL(11);
    ln_partial(h, sm + OFF_ST + g * 80 + warp * 8, t4 == 0);
    bar_sync(3, 288);
    {
        uint32_t mean2;
        float inv;
        ln_combine(sm + OFF_ST + g * 80, mean2, inv);
#pragma unroll
        for (int i = 0; i < 8; i++) h[i] = modulate2(h[i], mean2, inv, sh[i], op[i]);
    }
    if (warp == 0) TSL(12);
    if (!gpre) {
        mbar_wait_lanes(gbar);
#pragma unroll
        for (int i = 0; i < 20; i++) ldsm4t(a[i], ab + (i / 5) * 1280 + (i % 5) * 16);
    }
    if (warp == 8) TSL(17);
    {
        float acc[5][4] = {};
#pragma unroll
        for (int i = 0; i < 20; i++) mma(acc[i % 5], a[i][0], a[i][1], a[i][2], a[i][3], h[2 * (i / 5)], h[2 * (i / 5) + 1]);
#pragma unroll
        for (int m = 0; m < 5; m++) sts128f(sm + OFF_RED + m * 4608 + tid * 16, acc[m]);
    }
    bar_sync(3, 288);
    if (warp < 5) {
        float c[4] = {};
        sum_frags<9>(c, sm + OFF_RED + warp * 4608 + lane * 16, 512);
        const uint32_t w = movm(bmul2(silu2(pack2(c[0], c[1])), pack2(c[2], c[3])));
        if (act_writer) ll_st1(dst_a, w, tag);
        if (warp == 1) TSL(13);
    }
    if (cta < 72) {
        float r = 0.f;
#pragma unroll
        for (int i = 0; i < 8; i++) {
            r = fmaf(blo(h[i]), blo(wr[i]), fmaf(bhi(h[i]), bhi(wr[i]), r));
            if (warp * 8 + i == cta) sts32(sm + OFF_HU + lane * 4, h[i]);
        }
        r = quad_sum(r);
        if (t4 == 0) sts32(sm + OFF_RT + g * 48 + warp * 4, __float_as_uint(r));
    }

    project<1>(sm, gs + G_ACT + (grp * 36 + 4 * warp) * 32 + lane, dst_p + HKV * NB * DM, warp, lane, tag);
    if (warp == 0) TSL(14);
    if (reducer) {
        const uint4 r0 = lds128(sm + OFF_RT + rbat * 48), r1 = lds128(sm + OFF_RT + rbat * 48 + 16);
        float r = __uint_as_float(lds32(sm + OFF_RT + rbat * 48 + 32));
        r += ((__uint_as_float(r0.x) + __uint_as_float(r0.y)) + (__uint_as_float(r0.z) + __uint_as_float(r0.w))) +
             ((__uint_as_float(r1.x) + __uint_as_float(r1.y)) + (__uint_as_float(r1.z) + __uint_as_float(r1.w)));
        r = sigmoid_f(rbf(r));
        const uint32_t rh = lds32(sm + OFF_HU + (rbat * 4 + warp) * 4);
        const uint32_t y = badd2(rh, bmul2(reduce16(src_p + HKV * NB * DM, lane, tag), pack2(r, r)));
        if (lane < 8) reinterpret_cast<uint32_t*>(P.out)[rbat * (DM / 2) + 4 * cta + warp] = badd2(rx, bmul2(rg[1], y));
        if (cta == 0 && tid == 0) g_epoch = tag;
        if (warp == 0) TSL(15);
    }
}

typedef CUresult (*EncodeFn)(CUtensorMap*, CUtensorMapDataType, cuuint32_t, void*, const cuuint64_t*, const cuuint64_t*,
                             const cuuint32_t*, const cuuint32_t*, CUtensorMapInterleave, CUtensorMapSwizzle,
                             CUtensorMapL2promotion, CUtensorMapFloatOOBfill);

#define PROMO_W CU_TENSOR_MAP_L2_PROMOTION_L2_128B
#define PROMO_KV CU_TENSOR_MAP_L2_PROMOTION_L2_256B
constexpr int dbg_wfront = W_FRONT, dbg_wkv = W_KV, dbg_wtail = W_TAIL, dbg_promo_w = PROMO_W, dbg_promo_kv = PROMO_KV, dbg_iwo = POS_WO, dbg_itail = POS_TAIL, dbg_mode = 0, dbg_wwo = 3, dbg_slack = 4;

void make_map(EncodeFn enc, CUtensorMap* m, void* p, int cols, int rows, int pitch, int bc, int br, int planes, int pstride,
              CUtensorMapSwizzle sw, int promo) {
    cuuint64_t dims[3] = {(cuuint64_t)cols, (cuuint64_t)rows, (cuuint64_t)planes};
    cuuint64_t strides[2] = {(cuuint64_t)pitch * 2, (cuuint64_t)pstride};
    cuuint32_t box[3] = {(cuuint32_t)bc, (cuuint32_t)br, (cuuint32_t)planes};
    cuuint32_t es[3] = {1, 1, 1};
    enc(m, CU_TENSOR_MAP_DATA_TYPE_BFLOAT16, 3, p, dims, strides, box, es, CU_TENSOR_MAP_INTERLEAVE_NONE, sw,
        (CUtensorMapL2promotion)promo, CU_TENSOR_MAP_FLOAT_OOB_FILL_NONE);
}

}

extern "C" void kernel_launch(void* const* d_in, const int* in_sizes, int n_in, void* d_out, int out_size) {
    static EncodeFn enc = nullptr;
    if (!enc) {
        void* fn = nullptr;
        cudaDriverEntryPointQueryResult st;
        cudaGetDriverEntryPoint("cuTensorMapEncodeTiled", &fn, cudaEnableDefault, &st);
        enc = (EncodeFn)fn;
        cudaFuncSetAttribute(fused_kernel, cudaFuncAttributeMaxDynamicSharedMemorySize, SMEM_BYTES);
    }
    Params P;
    const CUtensorMapSwizzle none = CU_TENSOR_MAP_SWIZZLE_NONE;
    make_map(enc, &P.m[M_K], d_in[1], 64, NB * HKV * SK, DH, 64, 32, 2, 128, CU_TENSOR_MAP_SWIZZLE_128B, dbg_promo_kv);
    make_map(enc, &P.m[M_V], d_in[2], 64, NB * HKV * SK, DH, 64, 32, 2, 128, CU_TENSOR_MAP_SWIZZLE_128B, dbg_promo_kv);
    make_map(enc, &P.m[M_WQ], d_in[3], HQ * DH, DM, HQ * DH, 32, 192, 1, 16, CU_TENSOR_MAP_SWIZZLE_64B, dbg_promo_w);
    make_map(enc, &P.m[M_WO], d_in[4], DM, HQ * DH, DM, 72, 64, 1, 16, none, dbg_promo_w);
    make_map(enc, &P.m[M_WG], d_in[7], FF, DM, FF, 40, 64, 1, 16, none, dbg_promo_w);
    make_map(enc, &P.m[M_WU], d_in[8], FF, DM, FF, 40, 64, 1, 16, none, dbg_promo_w);
    make_map(enc, &P.m[M_WD], d_in[9], DM, FF, DM, 72, 32, 1, 16, none, dbg_promo_w);
    make_map(enc, &P.m[M_WM], d_in[11], 6 * DM, DM, 6 * DM, 32, 192, 1, 16, CU_TENSOR_MAP_SWIZZLE_64B, dbg_promo_w);
    make_map(enc, &P.m[M_WA], d_in[11], DM, DM, 6 * DM, 16, 192, 2, DM * 2, CU_TENSOR_MAP_SWIZZLE_32B, dbg_promo_w);
    P.x = (const __nv_bfloat16*)d_in[0];
    P.wr = (const __nv_bfloat16*)d_in[6];
    P.c = (const __nv_bfloat16*)d_in[10];
    P.out = (__nv_bfloat16*)d_out;
    P.wfront = dbg_wfront;
    P.wkv = dbg_wkv;
    P.wtail = dbg_wtail;
    P.iwo = dbg_iwo;
    P.itail = dbg_itail;
    P.mode = dbg_mode;
    P.wwo = dbg_wwo;
    P.slack = dbg_slack;
    fused_kernel<<<NCTA, NTHREADS, SMEM_BYTES>>>(P);
}
```

```cpp
#include <cuda_runtime.h>
#include <cuda_bf16.h>
#include <cuda.h>
#include <stdint.h>

typedef unsigned long long u64;

#define W_FRONT 4
#define W_KV 5
#define W_WO 4
#define W_GU 4
#define W_WD 6

namespace {

constexpr int NB = 8, DM = 576, HQ = 32, HKV = 16, SK = 8192, WIN = 2048, DH = 128, FF = 4608;
constexpr int NCTA = 128;
constexpr int NCW = 10;
constexpr int NTHREADS = (NCW + 2) * 32;
constexpr int TILE_BYTES = 8192, NSLOT = 16, NT = 64;
constexpr int SPIN_LIMIT = 1 << 22;

constexpr int OFF_RING = 0;
constexpr int OFF_WM = 120832;
constexpr int OFF_WQ = OFF_WM + 36864;
constexpr int OFF_GU = 0;
constexpr int OFF_WD = 73728;
constexpr int OFF_WO = 131072;
constexpr int OFF_OX = OFF_WO + 32768;
constexpr int OFF_DX = OFF_OX + 4096;
constexpr int OFF_GX = OFF_DX + 4608;
constexpr int OFF_P = OFF_WQ + 36864;
constexpr int P_PITCH = 528;
constexpr int OFF_RED = OFF_P + 16 * P_PITCH;
constexpr int OFF_ORED = OFF_RED + 5 * 4608 - 8704;
constexpr int OFF_ST = OFF_RED + 5 * 4608;
constexpr int OFF_SM = OFF_ST + 640;
constexpr int OFF_RT = OFF_SM + 128;
constexpr int OFF_HU = OFF_RT + 384;
constexpr int OFF_QS = OFF_HU + 128;
constexpr int OFF_WIN = OFF_QS + 512;
constexpr int OFF_BAR = OFF_WIN + 16;
constexpr int BAR_SYNC = 6, BAR_WMF = 8, BAR_X = 9, BAR_WO = 10, BAR_FULL = 18, BAR_GU = 34, BAR_WD = 43, BAR_EMPTY = 52, NBAR = 68;
constexpr int SMEM_BYTES = OFF_BAR + NBAR * 8;

constexpr int D_X1 = 0;
constexpr int D_O = 3072;
constexpr int D_ACT = D_O + 512 * 32;
constexpr int D_P = D_ACT + 576 * 32;
constexpr int D_PING = D_P + 2 * 72 * 1024;
constexpr int G_H = 2 * (D_PING + 1024);
constexpr int G_M = G_H + 72 * 32;
constexpr int G_Q = G_M + 288 * 32;
constexpr int G_CNT = G_Q + NB * HQ * 64;
constexpr int G_PAGE = 1 << 19;
static_assert(G_CNT < G_PAGE, "scratch exceeds a page");
__device__ unsigned g_epoch;
__device__ uint32_t g_scratch[3 * G_PAGE];
__device__ __forceinline__ int dual(int w) { return w + (w & ~1023); }
__device__ __forceinline__ int near(int w, int side) { return dual(w) + (((__popc(w & 0x16400) ^ side) & 1) << 10); }

#define TS(i)
#define TSL(i)

enum { M_K, M_V, M_GU, M_GX, M_OD, M_OX, M_WQ, M_WM, M_WA, NMAP };
struct Params {
    CUtensorMap m[NMAP];
    const __nv_bfloat16 *x, *c, *wr;
    __nv_bfloat16* out;
    uint32_t* scratch;
    int zg, zo;
    int wfront, wkv, wgu, wwd, mode, wwo, slack, gain, wmin, wmax, tx, two, nping, slack2;
};

__device__ __forceinline__ void mbar_init(uint32_t bar, int cnt) {
    asm volatile("mbarrier.init.shared::cta.b64 [%0], %1;" ::"r"(bar), "r"(cnt));
}
__device__ __forceinline__ void mbar_expect(uint32_t bar, uint32_t bytes) {
    asm volatile("mbarrier.arrive.expect_tx.shared::cta.b64 _, [%0], %1;" ::"r"(bar), "r"(bytes) : "memory");
}
__device__ __forceinline__ void mbar_arrive(uint32_t bar) {
    asm volatile("mbarrier.arrive.shared::cta.b64 _, [%0];" ::"r"(bar) : "memory");
}
__device__ __forceinline__ void mbar_wait(uint32_t bar, uint32_t parity) {
    asm volatile("{\n.reg .pred p;\n.reg .u32 c;\n"
                 "mbarrier.try_wait.parity.shared::cta.b64 p, [%0], %1;\n@p bra DONE;\nmov.u32 c, %2;\n"
                 "AGAIN:\nmbarrier.try_wait.parity.shared::cta.b64 p, [%0], %1;\nsub.u32 c, c, 1;\n"
                 "setp.eq.or.u32 p, c, 0, p;\n@!p bra AGAIN;\nDONE:\n}"
                 ::"r"(bar), "r"(parity), "n"(SPIN_LIMIT) : "memory");
}
__device__ __forceinline__ bool mbar_test(uint32_t bar, uint32_t parity) {
    uint32_t ok;
    asm volatile("{\n.reg .pred p;\nmbarrier.test_wait.parity.shared::cta.b64 p, [%1], %2;\nselp.u32 %0, 1, 0, p;\n}"
                 : "=r"(ok) : "r"(bar), "r"(parity) : "memory");
    return ok;
}
__device__ __forceinline__ void mbar_wait_lanes(uint32_t bar) {
    mbar_wait(bar, 0);
    __syncwarp();
}
__device__ __forceinline__ void tma3d_hint(uint32_t dst, const CUtensorMap* m, int x, int y, int z, uint32_t bar, u64 pol) {
    asm volatile("cp.async.bulk.tensor.3d.shared::cluster.global.mbarrier::complete_tx::bytes.L2::cache_hint"
                 " [%0], [%1, {%2, %3, %4}], [%5], %6;"
                 ::"r"(dst), "l"(m), "r"(x), "r"(y), "r"(z), "r"(bar), "l"(pol) : "memory");
}
__device__ __forceinline__ void tma3d(uint32_t dst, const CUtensorMap* m, int x, int y, int z, uint32_t bar) {
    asm volatile("cp.async.bulk.tensor.3d.shared::cluster.global.mbarrier::complete_tx::bytes [%0], [%1, {%2, %3, %4}], [%5];"
                 ::"r"(dst), "l"(m), "r"(x), "r"(y), "r"(z), "r"(bar) : "memory");
}
__device__ __forceinline__ void bar_sync(int id, int n) { asm volatile("bar.sync %0, %1;" ::"r"(id), "r"(n) : "memory"); }
__device__ __forceinline__ void bar_arrive(int id, int n) { asm volatile("bar.arrive %0, %1;" ::"r"(id), "r"(n) : "memory"); }
__device__ __forceinline__ void ldsm4(uint32_t (&r)[4], uint32_t a) {
    asm volatile("ldmatrix.sync.aligned.m8n8.x4.shared.b16 {%0,%1,%2,%3}, [%4];"
                 : "=r"(r[0]), "=r"(r[1]), "=r"(r[2]), "=r"(r[3]) : "r"(a) : "memory");
}
__device__ __forceinline__ void ldsm4t(uint32_t (&r)[4], uint32_t a) {
    asm volatile("ldmatrix.sync.aligned.m8n8.x4.trans.shared.b16 {%0,%1,%2,%3}, [%4];"
                 : "=r"(r[0]), "=r"(r[1]), "=r"(r[2]), "=r"(r[3]) : "r"(a) : "memory");
}
__device__ __forceinline__ void mma(float (&c)[4], uint32_t a0, uint32_t a1, uint32_t a2, uint32_t a3, uint32_t b0, uint32_t b1) {
    asm volatile("mma.sync.aligned.m16n8k16.row.col.f32.bf16.bf16.f32 {%0,%1,%2,%3}, {%4,%5,%6,%7}, {%8,%9}, {%0,%1,%2,%3};"
                 : "+f"(c[0]), "+f"(c[1]), "+f"(c[2]), "+f"(c[3])
                 : "r"(a0), "r"(a1), "r"(a2), "r"(a3), "r"(b0), "r"(b1));
}
__device__ __forceinline__ uint32_t movm(uint32_t a) {
    uint32_t d;
    asm volatile("movmatrix.sync.aligned.m8n8.trans.b16 %0, %1;" : "=r"(d) : "r"(a));
    return d;
}
__device__ __forceinline__ uint32_t lds32(uint32_t a) { uint32_t v; asm volatile("ld.shared.b32 %0, [%1];" : "=r"(v) : "r"(a) : "memory"); return v; }
__device__ __forceinline__ float2 lds64f(uint32_t a) { float2 v; asm volatile("ld.shared.v2.f32 {%0,%1}, [%2];" : "=f"(v.x), "=f"(v.y) : "r"(a) : "memory"); return v; }
__device__ __forceinline__ uint4 lds128(uint32_t a) { uint4 v; asm volatile("ld.shared.v4.b32 {%0,%1,%2,%3}, [%4];" : "=r"(v.x), "=r"(v.y), "=r"(v.z), "=r"(v.w) : "r"(a) : "memory"); return v; }
__device__ __forceinline__ void sts32(uint32_t a, uint32_t v) { asm volatile("st.shared.b32 [%0], %1;" ::"r"(a), "r"(v) : "memory"); }
__device__ __forceinline__ void sts16(uint32_t a, uint16_t v) { asm volatile("st.shared.b16 [%0], %1;" ::"r"(a), "h"(v) : "memory"); }
__device__ __forceinline__ void sts64(uint32_t a, uint32_t x, uint32_t y) { asm volatile("st.shared.v2.b32 [%0], {%1,%2};" ::"r"(a), "r"(x), "r"(y) : "memory"); }
__device__ __forceinline__ void sts128(uint32_t a, uint32_t x, uint32_t y, uint32_t z, uint32_t w) {
    asm volatile("st.shared.v4.b32 [%0], {%1,%2,%3,%4};" ::"r"(a), "r"(x), "r"(y), "r"(z), "r"(w) : "memory");
}
__device__ __forceinline__ void sts128f(uint32_t a, const float (&c)[4]) {
    sts128(a, __float_as_uint(c[0]), __float_as_uint(c[1]), __float_as_uint(c[2]), __float_as_uint(c[3]));
}

__device__ __forceinline__ float sel4(const float (&c)[4], int t) { return (t & 2) ? ((t & 1) ? c[3] : c[2]) : ((t & 1) ? c[1] : c[0]); }

__device__ __forceinline__ uint32_t clock32(uint32_t dep) {
    uint32_t t;
    asm volatile("{\n.reg .pred p;\nsetp.eq.u32 p, %1, 0x9e3779b9;\n@p nanosleep.u32 1;\nmov.u32 %0, %clock;\n}" : "=r"(t) : "r"(dep) : "memory");
    return t;
}

__device__ __forceinline__ uint32_t nz(uint32_t v) { return v ? v : 0x80000000u; }
__device__ __forceinline__ void st1(uint32_t* p, uint32_t a) { asm volatile("st.relaxed.gpu.global.b32 [%0], %1;" ::"l"(p), "r"(a) : "memory"); }
__device__ __forceinline__ void st2(uint32_t* p, uint32_t a, uint32_t b) {
    asm volatile("st.relaxed.gpu.global.v2.b32 [%0], {%1,%2};" ::"l"(p), "r"(a), "r"(b) : "memory");
}
__device__ __forceinline__ void put1(uint32_t* p, uint32_t a) { st1(p, nz(a)); }
__device__ __forceinline__ void put2(uint32_t* p, uint32_t a, uint32_t b) { st2(p, nz(a), nz(b)); }
__device__ __forceinline__ void put1d(uint32_t* p, uint32_t a) { a = nz(a), st1(p, a), st1(p + 1024, a); }
__device__ __forceinline__ void put2d(uint32_t* p, uint32_t a, uint32_t b) { a = nz(a), b = nz(b), st2(p, a, b), st2(p + 1024, a, b); }
__device__ __forceinline__ void clear1(uint32_t* p) { st1(p, 0), st1(p + G_PAGE, 0); }
__device__ __forceinline__ void clear2(uint32_t* p) { st2(p, 0, 0), st2(p + G_PAGE, 0, 0); }
__device__ __forceinline__ void clear1d(uint32_t* p) { clear1(p), clear1(p + 1024); }
__device__ __forceinline__ void clear2d(uint32_t* p) { clear2(p), clear2(p + 1024); }
__device__ __forceinline__ void probe(const uint32_t* p, int slack) {
    uint32_t v;
    int it = 0;
    do {
        asm volatile("ld.relaxed.gpu.global.b32 %0, [%1];" : "=r"(v) : "l"(p) : "memory");
    } while (__popc(__ballot_sync(0xffffffffu, v == 0)) > slack && ++it < SPIN_LIMIT);
}
__device__ __forceinline__ uint32_t ld1(const uint32_t* p) {
    uint32_t v;
    asm volatile("ld.relaxed.gpu.global.b32 %0, [%1];" : "=r"(v) : "l"(p) : "memory");
    return v;
}
template <int N>
__device__ __forceinline__ void reget1(const uint32_t* p, int stride, uint32_t (&a)[N]) {
#pragma unroll 1
    for (int it = 0; it < SPIN_LIMIT; it++) {
        uint32_t lo = a[0];
#pragma unroll
        for (int i = 1; i < N; i++) lo = min(lo, a[i]);
        if (!__any_sync(0xffffffffu, lo == 0)) break;
#pragma unroll
        for (int i = 0; i < N; i++)
            asm volatile("{\n.reg .pred p;\nsetp.eq.u32 p, %0, 0;\n@p ld.relaxed.gpu.global.b32 %0, [%1];\n}"
                         : "+r"(a[i]) : "l"(p + i * stride) : "memory");
    }
}
template <int N>
__device__ __forceinline__ void get1(const uint32_t* p, int stride, uint32_t (&a)[N]) {
#pragma unroll
    for (int i = 0; i < N; i++) a[i] = 0;
    reget1<N>(p, stride, a);
}
template <int N>
__device__ __forceinline__ void get2(const uint32_t* p, int stride, uint32_t (&a)[N], uint32_t (&b)[N]) {
    uint32_t m[N], lo;
    int it = 0;
#pragma unroll
    for (int i = 0; i < N; i++) m[i] = a[i] = b[i] = 0;
    do {
#pragma unroll
        for (int i = 0; i < N; i++)
            asm volatile("{\n.reg .pred p;\nsetp.eq.u32 p, %2, 0;\n@p ld.relaxed.gpu.global.v2.b32 {%0,%1}, [%3];\n}"
                         : "+r"(a[i]), "+r"(b[i]) : "r"(m[i]), "l"(p + i * stride) : "memory");
        lo = 1;
#pragma unroll
        for (int i = 0; i < N; i++) m[i] = min(a[i], b[i]), lo = min(lo, m[i]);
    } while (__any_sync(0xffffffffu, lo == 0) && ++it < SPIN_LIMIT);
}
__device__ __forceinline__ void get4(const uint32_t* p, uint32_t (&a)[4]) {
    uint32_t lo = 0;
    int it = 0;
    a[0] = a[1] = a[2] = a[3] = 0;
    do {
        asm volatile("{\n.reg .pred p;\nsetp.eq.u32 p, %4, 0;\n@p ld.relaxed.gpu.global.v4.b32 {%0,%1,%2,%3}, [%5];\n}"
                     : "+r"(a[0]), "+r"(a[1]), "+r"(a[2]), "+r"(a[3]) : "r"(lo), "l"(p) : "memory");
        lo = min(min(a[0], a[1]), min(a[2], a[3]));
    } while (__any_sync(0xffffffffu, lo == 0) && ++it < SPIN_LIMIT);
}
__device__ __forceinline__ void cp16(uint32_t dst, const void* src) {
    asm volatile("cp.async.cg.shared.global [%0], [%1], 16;" ::"r"(dst), "l"(src) : "memory");
}

__device__ __forceinline__ uint32_t pack2(float lo, float hi) {
    uint32_t r;
    asm("cvt.rn.bf16x2.f32 %0, %1, %2;" : "=r"(r) : "f"(hi), "f"(lo));
    return r;
}
__device__ __forceinline__ float rbf(float x) { return __uint_as_float(pack2(0.f, x)); }
__device__ __forceinline__ float blo(uint32_t v) { return __uint_as_float(v << 16); }
__device__ __forceinline__ float bhi(uint32_t v) { return __uint_as_float(v & 0xffff0000u); }
__device__ __forceinline__ uint32_t badd2(uint32_t a, uint32_t b) { uint32_t r; asm("add.rn.bf16x2 %0, %1, %2;" : "=r"(r) : "r"(a), "r"(b)); return r; }
__device__ __forceinline__ uint32_t bsub2(uint32_t a, uint32_t b) { uint32_t r; asm("sub.rn.bf16x2 %0, %1, %2;" : "=r"(r) : "r"(a), "r"(b)); return r; }
__device__ __forceinline__ uint32_t bmul2(uint32_t a, uint32_t b) { uint32_t r; asm("mul.rn.bf16x2 %0, %1, %2;" : "=r"(r) : "r"(a), "r"(b)); return r; }
__device__ __forceinline__ float ex2(float x) { float r; asm("ex2.approx.ftz.f32 %0, %1;" : "=f"(r) : "f"(x)); return r; }
__device__ __forceinline__ float rcp(float x) { float r; asm("rcp.approx.ftz.f32 %0, %1;" : "=f"(r) : "f"(x)); return r; }
__device__ __forceinline__ float sqrt_f(float x) { float r; asm("sqrt.approx.ftz.f32 %0, %1;" : "=f"(r) : "f"(x)); return r; }
constexpr float LOG2E = 1.4426950408889634f;
constexpr uint32_t ONE2 = 0x3f803f80u;
__device__ __forceinline__ float sigmoid_f(float x) { return rcp(1.0f + ex2(-LOG2E * x)); }
__device__ __forceinline__ uint32_t silu2(uint32_t v) {
    const float a = blo(v), b = bhi(v);
    return pack2(a * sigmoid_f(a), b * sigmoid_f(b));
}
__device__ __forceinline__ float quad_sum(float v) {
    v += __shfl_xor_sync(0xffffffffu, v, 1);
    return v + __shfl_xor_sync(0xffffffffu, v, 2);
}
__device__ __forceinline__ void ln_partial(const uint32_t (&v)[8], uint32_t dst, bool writer) {
    float s0 = 0.f, s1 = 0.f;
#pragma unroll
    for (int i = 0; i < 8; i++) {
        s0 += blo(v[i]);
        s1 += bhi(v[i]);
    }
    const float mean = quad_sum(s0 + s1) * (1.0f / 64);
    s0 = s1 = 0.f;
#pragma unroll
    for (int i = 0; i < 8; i++) {
        const float a = blo(v[i]) - mean, b = bhi(v[i]) - mean;
        s0 = fmaf(a, a, s0);
        s1 = fmaf(b, b, s1);
    }
    s0 = quad_sum(s0 + s1);
    if (writer) sts64(dst, __float_as_uint(mean), __float_as_uint(s0));
}
__device__ __forceinline__ void ln_combine(uint32_t src, uint32_t& mean2, float& inv) {
    float m[10], q0 = 0.f, q1 = 0.f, s = 0.f;
#pragma unroll
    for (int i = 0; i < 5; i++) {
        const uint4 v = lds128(src + i * 16);
        m[2 * i] = __uint_as_float(v.x);
        m[2 * i + 1] = __uint_as_float(v.z);
        q0 += __uint_as_float(v.y);
        if (i < 4) q1 += __uint_as_float(v.w);
    }
    const float mean = (((m[0] + m[1]) + (m[2] + m[3])) + ((m[4] + m[5]) + (m[6] + m[7])) + m[8]) * (1.0f / 9);
#pragma unroll
    for (int i = 0; i < 9; i++) s = fmaf(m[i] - mean, m[i] - mean, s);
    const float var = fmaf(s, 64.f, q0 + q1) * (1.0f / DM);
    mean2 = pack2(mean, mean);
    inv = rcp(rbf(sqrt_f(rbf(rbf(var) + 1e-5f))));
}
__device__ __forceinline__ uint32_t modulate2(uint32_t x, uint32_t mean2, float inv, uint32_t shift, uint32_t onep) {
    const uint32_t d = bsub2(x, mean2);
    return badd2(bmul2(pack2(blo(d) * inv, bhi(d) * inv), onep), shift);
}
template <int N>
__device__ __forceinline__ void sum_frags(float (&c)[4], uint32_t addr, int stride) {
#pragma unroll
    for (int w = 0; w < N; w++) {
        const uint4 v = lds128(addr + w * stride);
        c[0] += __uint_as_float(v.x); c[1] += __uint_as_float(v.y);
        c[2] += __uint_as_float(v.z); c[3] += __uint_as_float(v.w);
    }
}

template <int ST>
__device__ __forceinline__ void project(uint32_t sm, const uint32_t* src, uint32_t* dst, int warp, int lane) {
    constexpr int NW = ST ? 9 : 8;
    const uint32_t red = sm + (ST ? OFF_WO : OFF_P) + lane * 8;
    if (warp < NW) {
        const uint32_t wbar = sm + OFF_BAR + ((ST ? BAR_WD : BAR_WO) + warp) * 8;
        const int r = warp * 32 + (lane >> 4) * 8 + (lane & 7);
        const uint32_t ab = sm + (ST ? OFF_WD : OFF_WO) + r * 128 + ((((lane >> 3) & 1) ^ (lane & 7)) << 4);
        const uint32_t ax = sm + (ST ? OFF_DX : OFF_OX) + r * 16;
        uint32_t a[10][4], b[4];
        auto load_w = [&]() {
#pragma unroll
            for (int i = 0; i < 10; i++) ldsm4t(a[i], i % 5 < 4 ? (ab ^ ((i % 5) << 5)) + (i / 5) * 2048 : ax + (i / 5) * 256);
        };
        const bool pre = __all_sync(0xffffffffu, mbar_test(wbar, 0));
        load_w();
        if (ST) get1<4>(src, 32, b);
        else get4(src, b);
        if (warp == 0) TSL(ST ? 24 : 21);
        if (!pre) {
            mbar_wait_lanes(wbar);
            load_w();
        }
        float acc[5][4] = {};
#pragma unroll
        for (int i = 0; i < 10; i++) mma(acc[i % 5], a[i][0], a[i][1], a[i][2], a[i][3], b[2 * (i / 5)], b[2 * (i / 5) + 1]);
#pragma unroll
        for (int u = 0; u < 9; u++)
            sts64(red + u * 2304 + warp * 256, __float_as_uint(acc[u >> 1][2 * (u & 1)]), __float_as_uint(acc[u >> 1][2 * (u & 1) + 1]));
    }
    bar_sync(3, 288);
    float s[2][2] = {};
#pragma unroll
    for (int w = 0; w < NW; w++) {
        const float2 v = lds64f(red + warp * 2304 + w * 256);
        s[w & 1][0] += v.x;
        s[w & 1][1] += v.y;
    }
    put2d(dst, __float_as_uint(s[0][0] + s[1][0]), __float_as_uint(s[0][1] + s[1][1]));
}

__device__ __forceinline__ uint32_t reduce16(const uint32_t* src, int lane) {
    uint32_t a[4], b[4];
    get2<4>(src, 64, a, b);
    float s0 = (__uint_as_float(a[0]) + __uint_as_float(a[1])) + (__uint_as_float(a[2]) + __uint_as_float(a[3]));
    float s1 = (__uint_as_float(b[0]) + __uint_as_float(b[1])) + (__uint_as_float(b[2]) + __uint_as_float(b[3]));
#pragma unroll
    for (int o = 8; o < 32; o <<= 1) {
        s0 += __shfl_xor_sync(0xffffffffu, s0, o);
        s1 += __shfl_xor_sync(0xffffffffu, s1, o);
    }
    const uint32_t y = pack2(s0, s1);
    return __byte_perm(y, __shfl_xor_sync(0xffffffffu, y, 4), (lane & 4) ? 0x3276 : 0x5410);
}

__global__ void __launch_bounds__(NTHREADS, 1) fused_kernel(const __grid_constant__ Params P) {
    extern __shared__ __align__(1024) char smem_raw[];
    const uint32_t sm = (uint32_t)__cvta_generic_to_shared(smem_raw);
    const int tid = threadIdx.x, lane = tid & 31;
    const int warp = __shfl_sync(0xffffffffu, tid >> 5, 0);
    const int cta = blockIdx.x, grp = cta >> 3, sub = cta & 7;
    const uint32_t bars = sm + OFF_BAR;

    if (lane == 0 && warp <= NCW) {
        if (warp == NCW) TS(0);
#pragma unroll
        for (int i = 0; i < 6; i++) mbar_init(bars + (warp == NCW ? 0 : 64 + warp * 48) + i * 8, 1);
        if (warp == 9) mbar_init(bars + 48, 1), mbar_init(bars + 56, 1);
        asm volatile("fence.mbarrier_init.release.cluster;" ::: "memory");
    }

    if (warp >= NCW) {
        const int pw = warp - NCW, n0 = cta < 108 ? 0 : 3;
        if (pw == 0) {
            if (lane == 0) {
#pragma unroll
                for (int i = 0; i < 3; i++) {
                    mbar_expect(bars + (n0 + i) * 8, 12288);
                    tma3d(sm + OFF_WM + (n0 + i) * 12288, &P.m[cta < 36 ? M_WA : cta < 108 ? M_WM : M_WQ],
                          cta < 36 ? 16 * cta : 32 * cta, i * 192, 0, bars + (n0 + i) * 8);
                }
                TS(26);
                sts32(sm + OFF_WIN, P.wkv);
            }
            __syncwarp();
            bar_arrive(1, (NCW + 1) * 32);
        } else if (lane <= M_WQ) {
            asm volatile("prefetch.tensormap [%0];" ::"l"(&P.m[M_WQ - lane]) : "memory");
        }
        __syncwarp();
        bar_sync(15, NTHREADS);
        if (lane == 0) {
            u64 pol;
            asm volatile("createpolicy.fractional.L2::evict_first.b64 %0, 1.0;" : "=l"(pol));
            const int row0 = (sub * HKV + grp) * SK + (SK - WIN);
            if (n0 == 0) {
#pragma unroll 1
                for (int n = 3 + pw; n < 6; n += 2) {
                    mbar_expect(bars + n * 8, 12288);
                    if (n >= P.wfront) mbar_wait(bars + (n - P.wfront) * 8, 0);
                    tma3d(sm + OFF_WM + n * 12288, &P.m[M_WQ], 32 * cta, (n - 3) * 192, 0, bars + n * 8);
                }
            }
#pragma unroll 1
            for (int t = pw ^ 1; t < NSLOT; t += 2) {
                const int m = t - P.wfront;
                if (t >= 14 && n0 == 0) mbar_wait(bars + BAR_WMF * 8, 0);
                mbar_expect(bars + (BAR_FULL + t) * 8, TILE_BYTES);
                if (m + 6 >= n0) mbar_wait(bars + (m + (m < 0 ? 6 : BAR_FULL)) * 8, 0);
                tma3d_hint(sm + OFF_RING + t * TILE_BYTES, &P.m[M_K], 0, row0 + t * 32, 0, bars + (BAR_FULL + t) * 8, pol);
            }
            TS(30);
            if (pw == 0) {
#pragma unroll 1
                for (int t = NSLOT; t < 2 * NT; t++) {
                    const int m = t - (int)lds32(sm + OFF_WIN);
                    const uint32_t fb = bars + (BAR_FULL + (t & 15)) * 8;
                    mbar_wait(fb + (BAR_EMPTY - BAR_FULL) * 8, (~t >> 4) & 1);
                    mbar_expect(fb, TILE_BYTES);
                    mbar_wait(bars + (BAR_FULL + (m & 15)) * 8, (m >> 4) & 1);
                    tma3d_hint(sm + OFF_RING + (t & 15) * TILE_BYTES, &P.m[t >> 6], 0, row0 + (t & (NT - 1)) * 32, 0, fb, pol);
                    if (t == P.tx || t == P.two) mbar_arrive(bars + (BAR_SYNC + (t == P.two)) * 8);
                }
            } else {
                mbar_wait(bars + BAR_SYNC * 8, 0);
#pragma unroll 1
                for (int i = 0; i < (sub < 4 ? 7 : 4); i++) {
                    const int r = (i & 1) * (i < 2 ? 112 : 144);
                    mbar_expect(bars + BAR_X * 8, i < 4 ? 2304 : 6144);
                    if (i < 4) tma3d(sm + OFF_OX + (i >> 1) * 4096 + r * 16, &P.m[M_OX], 512 + 8 * sub, grp * (i < 2 ? 256 : 288) + r, P.zo ^ (i >> 1), bars + BAR_X * 8);
                    else tma3d(sm + OFF_GX + (i - 4) * 6144, &P.m[M_GX], grp * 288 + 256 + 8 * sub, (i - 4) * 192, 0, bars + BAR_X * 8);
                    mbar_wait(bars + BAR_X * 8, i & 1);
                }
                mbar_wait(bars + (BAR_SYNC + 1) * 8, 0);
#pragma unroll 1
                for (int i = 0; i < 8; i++) {
                    mbar_expect(bars + (BAR_WO + i) * 8, 4096);
                    if (i >= P.wwo) mbar_wait(bars + (BAR_WO + i - P.wwo) * 8, 0);
                    tma3d(sm + OFF_WO + i * 4096, &P.m[M_OD], 64 * sub, grp * 256 + i * 32, P.zo, bars + (BAR_WO + i) * 8);
                }
            }
        }
        __syncwarp();
        bar_sync(14, 64);
        if (lane == 0) {
            TS(28);
#pragma unroll 1
            for (int i = pw; i < 18; i += 2) {
                const uint32_t bar = bars + (BAR_GU + i) * 8;
                const int w = i < 9 ? P.wgu : P.wwd;
                mbar_wait(bars + (BAR_EMPTY + (i < 9 ? i : (i + 9) >> 1)) * 8, 1);
                mbar_expect(bar, i < 9 ? 8192 : 4096);
                mbar_wait(bar - w * 8, i < w);
                if (i < 9) tma3d(sm + OFF_GU + i * 8192, &P.m[M_GU], grp * 288 + 32 * sub, i * 64, 0, bar);
                else tma3d(sm + OFF_WD + (i - 9) * 4096, &P.m[M_OD], 64 * sub, grp * 288 + (i - 9) * 32, P.zo ^ 1, bar);
                if (i == 9) TS(29);
            }
        }
        return;
    }

    __syncwarp();
    bar_arrive(15, NTHREADS);
    const int g = lane >> 2, t4 = lane & 3;
    uint32_t epoch;
    asm volatile("ld.relaxed.gpu.global.u32 %0, [%1];" : "=r"(epoch) : "l"(&g_epoch) : "memory");
    uint32_t* const g0 = P.scratch;
    uint32_t* const gs = g0 + (epoch & 1) * G_PAGE;

    if (warp < 9) {
        const int off_h = (cta < 36 ? G_H + 2 * cta * 32 : G_M + 4 * (cta - 36) * 32) + tid;
        const int off_q = G_Q + g * (HQ * 64) + cta * 16 + warp * 8 + t4 * 2;
        uint32_t bf[8] = {}, xp = 0, mean2 = 0;
        float inv = 0.f;
        if (cta < 108) {
            const uint32_t stage = sm + OFF_RED + warp * 2048;
#pragma unroll
            for (int i = 0; i < 2; i++) {
                const int row = (lane >> 3) + 4 * i, so = row * DM + warp * 64 + (lane & 7) * 8;
                const uint32_t d = stage + row * 128 + (((lane & 7) ^ row) << 4);
                cp16(d, P.c + so);
                if (cta < 36) cp16(d + 1024, P.x + so);
            }
            if (cta < 36) xp = __ldg(reinterpret_cast<const uint32_t*>(P.x) + g * (DM / 2) + 8 * cta + 4 * (warp & 1) + t4);
        }
        if (warp < 2) {
            clear2(g0 + off_q);
            if (cta < 108) clear1(g0 + off_h);
            if (cta >= 36 && cta < 108) clear1(g0 + off_h + 64);
        }
        if (cta < 108) {
            asm volatile("cp.async.wait_all;" ::: "memory");
            __syncwarp();
            const uint32_t fa = sm + OFF_RED + warp * 2048 + (lane & 7) * 128 + (((lane >> 3) ^ (lane & 7)) << 4);
            ldsm4(reinterpret_cast<uint32_t(&)[4]>(bf[0]), fa);
            ldsm4(reinterpret_cast<uint32_t(&)[4]>(bf[4]), fa ^ 64);
            if (cta < 36) {
                uint32_t xv[8];
                ldsm4(reinterpret_cast<uint32_t(&)[4]>(xv[0]), fa + 1024);
                ldsm4(reinterpret_cast<uint32_t(&)[4]>(xv[4]), (fa ^ 64) + 1024);
                ln_partial(xv, sm + OFF_ST + g * 80 + warp * 8, t4 == 0);
            }
#pragma unroll
            for (int i = 0; i < 8; i++) bf[i] = silu2(bf[i]);
        }
        if (warp == 0) TSL(18);
        bar_sync(1, (NCW + 1) * 32);
        if (cta < 36 && warp < 2) ln_combine(sm + OFF_ST + g * 80, mean2, inv);
        const int r = warp * 64 + (lane >> 4) * 8 + (lane & 7), hi8 = (lane >> 3) & 1, box = warp / 3;
#pragma unroll 1
        for (int pass = cta < 108 ? 0 : 1; pass < 2; pass++) {
            const bool pa = pass == 0 && cta < 36;
            const uint32_t ab = sm + OFF_WM + pass * 36864 +
                                (pa ? (box + hi8) * 6144 + r * 32 + ((lane & 4) << 2) : r * 64 + (((2 * hi8) ^ ((r >> 1) & 3)) << 4));
            const uint32_t as = pa ? 512 : 1024, red = sm + OFF_RED + pass * 9216;
            mbar_wait(bars + (pass * 3 + box) * 8, 0);
            if (warp == 8) TSL(pass ? 31 : 19);
            uint32_t a[4][2][4];
#pragma unroll
            for (int i = 0; i < 4; i++) {
                ldsm4t(a[i][0], ab + i * as);
                ldsm4t(a[i][1], (ab ^ 16) + i * as);
            }
            if (pass) {
                if (P.mode & 4) probe(gs + G_H + warp * 256, 0);
                get1<8>(gs + G_H + warp * 256 + lane, 32, bf);
                if (warp == 0) TSL(3);
            }
            float acc[2][4] = {};
#pragma unroll
            for (int i = 0; i < 4; i++)
#pragma unroll
                for (int m = 0; m < 2; m++) mma(acc[m], a[i][m][0], a[i][m][1], a[i][m][2], a[i][m][3], bf[2 * i], bf[2 * i + 1]);
            sts128f(red + tid * 16, acc[0]);
            sts128f(red + 4608 + tid * 16, acc[1]);
            bar_sync(3, 288);
            if (warp < 2) {
                float c[4] = {};
                sum_frags<9>(c, red + warp * 4608 + lane * 16, 512);
                uint32_t lo = movm(pack2(c[0], c[1])), hi = movm(pack2(c[2], c[3]));
                if (pass) {
                    put2(gs + off_q, lo, hi);
                    if (warp == 0) TSL(4);
                } else {
                    const uint32_t hi1 = badd2(hi, ONE2);
                    if (pa) lo = modulate2(xp, mean2, inv, lo, hi1);
                    if (cta >= 72 && cta < 90) lo = badd2(lo, ONE2), hi = hi1;
                    put1(gs + off_h, lo);
                    if (!pa) put1(gs + off_h + 64, hi);
                    if (warp == 0 && pa) TSL(2);
                }
            } else if (tid == 64 && pass == 0) {
                mbar_arrive(bars + BAR_WMF * 8);
            }
        }
    } else {
        bar_sync(1, (NCW + 1) * 32);
        mbar_wait(bars + 5 * 8, 0);
        uint32_t a[4];
        get4(gs + G_Q + (sub * HQ + 2 * grp) * 64 + lane * 4, a);
        sts128(sm + OFF_QS + lane * 16, a[0], a[1], a[2], a[3]);
        __syncwarp();
        TSL(5);
        bar_arrive(4, 288);
    }

    const uint32_t tile = sm + OFF_RING + warp * TILE_BYTES;
    const uint32_t fullb = bars + (BAR_FULL + warp) * 8;
    const uint32_t pw = sm + OFF_P + warp * (2 * P_PITCH);
    auto pace = [&](int t) {
        if ((tid & 127) == 96 && t >= 16) {
            const int d = (int)atomicAdd(gs + G_CNT, 1u) - 32 * (t - 19) - 64;
            sts32(sm + OFF_WIN, min(max(P.wkv + ((d * P.gain + 128) >> 8), P.wmin), P.wmax));
        }
    };
    if (cta == 0 && tid == 288) st1(g0 + (~epoch & 1) * G_PAGE + G_CNT, 0);
    if (warp < 8) {
        {
            uint32_t q0[8], q1[8];
            bar_sync(4, 288);
#pragma unroll
            for (int i = 0; i < 8; i++) {
                const float2 v = lds64f(sm + OFF_QS + (g & 1) * 256 + i * 32 + t4 * 8);
                q0[i] = __float_as_uint(v.x), q1[i] = __float_as_uint(v.y);
            }
            uint32_t sp = pw + (t4 & 1) * P_PITCH + ((t4 >> 1) * 8 + g) * 2;
#pragma unroll 1
            for (int it = 0; it < 8; it++, sp += 64) {
                const uint32_t ab = tile + (it & 1) * (8 * TILE_BYTES) + (lane & 15) * 128 + (((lane >> 4) ^ (lane & 7)) << 4);
                mbar_wait(fullb + (it & 1) * 64, (it >> 1) & 1);
                float acc[2][2][4] = {};
#pragma unroll
                for (int ks = 0; ks < 8; ks++)
#pragma unroll
                    for (int m = 0; m < 2; m++) {
                        uint32_t a[4];
                        ldsm4(a, (ab ^ ((ks & 3) << 5)) + (ks >> 2) * 4096 + m * 2048);
                        mma(acc[m][ks & 1], a[0], a[1], a[2], a[3], (ks & 1) ? q1[ks - 1] : q0[ks], (ks & 1) ? q1[ks] : q0[ks + 1]);
                    }
                __syncwarp();
                if (lane == 0) mbar_arrive(fullb + (it & 1) * 64 + (BAR_EMPTY - BAR_FULL) * 8);
#pragma unroll
                for (int m = 0; m < 2; m++) {
                    const float s = sel4(acc[m][0], t4) + sel4(acc[m][1], t4);
                    sts16(sp + m * 32, (uint16_t)pack2(rbf(s) * 0.08838834764831845f, 0.f));
                }
                pace(it * 8 + warp);
                __syncwarp();
            }
        }
        __syncwarp();
        if (warp == 7) TSL(6);
        const uint32_t pa = pw + (lane >> 4) * P_PITCH + (lane & 15) * 32;
        const uint32_t sa = sm + OFF_SM + (lane >> 4) * 64;
        const uint4 v0 = lds128(pa), v1 = lds128(pa + 16);
        const uint32_t sv[8] = {v0.x, v0.y, v0.z, v0.w, v1.x, v1.y, v1.z, v1.w};
        float e[16];
        float m = -INFINITY;
#pragma unroll
        for (int i = 0; i < 8; i++) {
            e[2 * i] = blo(sv[i]);
            e[2 * i + 1] = bhi(sv[i]);
            m = fmaxf(m, fmaxf(e[2 * i], e[2 * i + 1]));
        }
#pragma unroll
        for (int o = 8; o; o >>= 1) m = fmaxf(m, __shfl_xor_sync(0xffffffffu, m, o));
        float l = 0.f;
#pragma unroll
        for (int i = 0; i < 16; i++) {
            e[i] = ex2((e[i] - m) * LOG2E);
            l += e[i];
        }
#pragma unroll
        for (int o = 8; o; o >>= 1) l += __shfl_xor_sync(0xffffffffu, l, o);
        if ((lane & 15) == 0) sts64(sa + warp * 8, __float_as_uint(m), __float_as_uint(l));
        bar_sync(2, NCW * 32);
        const float2 v = lds64f(sa + (lane & 7) * 8);
        float M = v.x;
#pragma unroll
        for (int o = 4; o; o >>= 1) M = fmaxf(M, __shfl_xor_sync(0xffffffffu, M, o));
        float L = v.y * ex2((v.x - M) * LOG2E);
#pragma unroll
        for (int o = 4; o; o >>= 1) L += __shfl_xor_sync(0xffffffffu, L, o);
        const float sc = ex2((m - M) * LOG2E) * rcp(L);
        sts128(pa, pack2(e[0] * sc, e[1] * sc), pack2(e[2] * sc, e[3] * sc), pack2(e[4] * sc, e[5] * sc), pack2(e[6] * sc, e[7] * sc));
        sts128(pa + 16, pack2(e[8] * sc, e[9] * sc), pack2(e[10] * sc, e[11] * sc), pack2(e[12] * sc, e[13] * sc), pack2(e[14] * sc, e[15] * sc));
        __syncwarp();
    } else {
        if (tid == 256) {
            uint32_t* const ping = gs + dual(D_PING) + cta * 8;
            uint32_t best[2] = {~0u, ~0u}, v = 0;
#pragma unroll 1
            for (int r = 0; r < P.nping; r++) {
#pragma unroll
                for (int k = 0; k < 2; k++) {
                    const uint32_t t0 = clock32(v);
                    v = atomicExch(ping + k * 1024, t0);
                    best[k] = min(best[k], clock32(v) - t0);
                }
            }
            sts32(sm + OFF_WIN + 4, ((best[1] < best[0]) ^ __popc(D_PING & 0x16400) ^ (P.mode >> 4)) & 1);
        }
        __syncwarp();
        bar_sync(2, NCW * 32);
    }
    const int side = lds32(sm + OFF_WIN + 4);

    const bool reducer = cta < 72 && warp < 4;
    const bool act_writer = warp < 4 || (warp == 4 && sub < 4);
    const int rbat = 2 * t4 + (g & 1);
    const int off_o = dual(D_O + cta * 128) + (tid & 0x70) + (tid & 3) * 4 + ((tid >> 2) & 3);
    const int off_p = dual(D_P + (warp < 8 ? 8 * sub + warp : 64 + sub) * 1024) + grp * 64 + lane * 2;
    const int off_x = dual(D_X1 + cta * 32) + warp * 8 + lane;
    const int off_a = dual(D_ACT + (grp * 36 + (warp < 4 ? 4 * sub + warp : 32 + sub)) * 32) + lane;
    uint32_t sh[8] = {}, op[8] = {}, wr[8] = {}, rx = 0, rg[2] = {};
    if (warp < 9) {
        if (warp < 4) clear1d(g0 + off_o);
        clear2d(g0 + off_p);
        clear2d(g0 + off_p + 72 * 2048);
        if (act_writer) clear1d(g0 + off_a);
#pragma unroll
        for (int i = 0; i < 8; i++) wr[i] = __ldg(reinterpret_cast<const uint32_t*>(P.wr) + warp * 32 + i * 4 + t4);
        if (reducer) {
            if (lane < 8) clear1d(g0 + off_x);
            rx = __ldg(reinterpret_cast<const uint32_t*>(P.x) + rbat * (DM / 2) + 4 * cta + warp);
            get1<2>(gs + G_M + cta * 32 + rbat * 4 + warp, 216 * 32, rg);
        }
        get1<8>(gs + G_M + (72 + warp * 8) * 32 + lane, 32, sh);
        get1<8>(gs + G_M + (144 + warp * 8) * 32 + lane, 32, op);
    }

    if (warp < 8) {
        float acc[8][4] = {};
        uint32_t pp = pw + (lane & 1) * P_PITCH + (lane >> 3) * 16;
#pragma unroll 1
        for (int it = 0; it < 8; it++, pp += 64) {
            const uint32_t ab = tile + (it & 1) * (8 * TILE_BYTES) + ((lane & 7) + (lane >> 4) * 8) * 128 + ((((lane >> 3) & 1) ^ (lane & 7)) << 4);
            uint32_t pb[4];
            ldsm4(pb, pp);
            mbar_wait(fullb + (it & 1) * 64, (it >> 1) & 1);
#pragma unroll
            for (int ks = 0; ks < 2; ks++)
#pragma unroll
                for (int m = 0; m < 8; m++) {
                    uint32_t a[4];
                    ldsm4t(a, (ab ^ ((m & 3) << 5)) + (m >> 2) * 4096 + ks * 2048);
                    mma(acc[m], a[0], a[1], a[2], a[3], pb[2 * ks], pb[2 * ks + 1]);
                }
            __syncwarp();
            if (lane == 0) mbar_arrive(fullb + (it & 1) * 64 + (BAR_EMPTY - BAR_FULL) * 8);
            if (it < 7) pace(NT + it * 8 + warp);
            __syncwarp();
        }
        if (warp == 7) TSL(7);
        const uint32_t ra = sm + OFF_ORED + warp * 1088 + (t4 & 1) * 576 + ((t4 >> 1) * 8 + g) * 4;
#pragma unroll
        for (int m = 0; m < 8; m++) sts32(ra + m * 64, __float_as_uint(sel4(acc[m], t4)));
    }
    bar_sync(5, NCW * 32);
    if (warp < 4) {
        float s[2][2] = {};
#pragma unroll
        for (int w = 0; w < 8; w++) {
            const float2 v = lds64f(sm + OFF_ORED + w * 1088 + (tid >> 6) * 64 + tid * 8);
            s[w & 1][0] += v.x;
            s[w & 1][1] += v.y;
        }
        put1d(gs + off_o, pack2(s[0][0] + s[1][0], s[0][1] + s[1][1]));
        if (warp == 0) TSL(8);
    }
    if (warp == 9) {
        const uint32_t* pp = gs + near(D_P + (cta < 72 ? cta : cta - 72) * 1024, side) + (lane & 15) * 64;
        if (cta < 72) {
            probe(pp, P.slack);
            bar_arrive(6, 160);
        }
        probe(pp, P.slack2);
        TSL(27);
        bar_arrive(7, NCW * 32);
        return;
    }

    project<0>(sm, gs + near(D_O + grp * 1024, side) + g * 128 + warp * 16 + t4 * 4, gs + off_p, warp, lane);
    if (warp == 0) TSL(9);
    const uint32_t gbar = bars + (BAR_GU + warp) * 8;
    const int rr = (lane >> 4) * 8 + (lane & 7), pl = ((lane >> 3) & 1) ^ P.zg;
    const uint32_t ab = sm + OFF_GU + warp * 8192 + pl * 4096 + rr * 64 + ((lane & 6) << 3);
    const uint32_t ax = sm + OFF_GX + (warp / 3 + pl) * 3072 + (warp * 64 + rr) * 16;
    uint32_t a[20][4] = {};
    auto load_gu = [&]() {
#pragma unroll
        for (int i = 0; i < 20; i++) ldsm4t(a[i], i % 5 < 4 ? (ab ^ ((i % 5) << 4)) + (i / 5) * 1024 : ax + (i / 5) * 256);
    };
    const uint32_t* const src_p = gs + (lane >> 3) * 256 + 16 * warp + (lane & 7) * 2;
    if (reducer) {
        bar_sync(6, 160);
        rx = badd2(rx, bmul2(rg[0], reduce16(src_p + near(D_P + cta * 1024, side), lane)));
        if (lane < 8) put1d(gs + off_x, rx);
        if (warp == 0) TSL(10);
    }
    bar_sync(7, NCW * 32);

    uint32_t h[8];
    const uint32_t* const src_x = gs + near(D_X1 + warp * 256, side) + t4 * 8 + (g & 1) * 4 + (g >> 1);
#pragma unroll
    for (int i = 0; i < 8; i++) h[i] = ld1(src_x + i * 32);
    const bool gpre = __all_sync(0xffffffffu, mbar_test(gbar, 0));
    if (gpre) load_gu();
    reget1<8>(src_x, 32, h);
    if (warp == 0) TSL(11);
    ln_partial(h, sm + OFF_ST + g * 80 + warp * 8, t4 == 0);
    bar_sync(3, 288);
    {
        uint32_t mean2;
        float inv;
        ln_combine(sm + OFF_ST + g * 80, mean2, inv);
#pragma unroll
        for (int i = 0; i < 8; i++) h[i] = modulate2(h[i], mean2, inv, sh[i], op[i]);
    }
    if (warp == 0) TSL(12);
    if (!gpre) {
        mbar_wait_lanes(gbar);
        load_gu();
    }
    if (warp == 8) TSL(17);
    {
        float acc[5][4] = {};
#pragma unroll
        for (int i = 0; i < 20; i++) mma(acc[i % 5], a[i][0], a[i][1], a[i][2], a[i][3], h[2 * (i / 5)], h[2 * (i / 5) + 1]);
#pragma unroll
        for (int m = 0; m < 5; m++) sts128f(sm + OFF_RED + m * 4608 + tid * 16, acc[m]);
    }
    bar_sync(3, 288);
    if (warp < 5) {
        float c[4] = {};
        sum_frags<9>(c, sm + OFF_RED + warp * 4608 + lane * 16, 512);
        const uint32_t w = movm(bmul2(silu2(pack2(c[0], c[1])), pack2(c[2], c[3])));
        if (act_writer) put1d(gs + off_a, w);
        if (warp == 1) TSL(13);
    }
    if (cta < 72) {
        float r = 0.f;
#pragma unroll
        for (int i = 0; i < 8; i++) {
            r = fmaf(blo(h[i]), blo(wr[i]), fmaf(bhi(h[i]), bhi(wr[i]), r));
            if (warp * 8 + i == cta) sts32(sm + OFF_HU + lane * 4, h[i]);
        }
        r = quad_sum(r);
        if (t4 == 0) sts32(sm + OFF_RT + g * 48 + warp * 4, __float_as_uint(r));
    }

    project<1>(sm, gs + near(D_ACT + (grp * 36 + 4 * warp) * 32, side) + lane, gs + off_p + 72 * 2048, warp, lane);
    if (warp == 0) TSL(14);
    if (reducer) {
        const uint4 r0 = lds128(sm + OFF_RT + rbat * 48), r1 = lds128(sm + OFF_RT + rbat * 48 + 16);
        float r = __uint_as_float(lds32(sm + OFF_RT + rbat * 48 + 32));
        r += ((__uint_as_float(r0.x) + __uint_as_float(r0.y)) + (__uint_as_float(r0.z) + __uint_as_float(r0.w))) +
             ((__uint_as_float(r1.x) + __uint_as_float(r1.y)) + (__uint_as_float(r1.z) + __uint_as_float(r1.w)));
        r = sigmoid_f(rbf(r));
        const uint32_t rh = lds32(sm + OFF_HU + (rbat * 4 + warp) * 4);
        const uint32_t y = badd2(rh, bmul2(reduce16(src_p + near(D_P + (72 + cta) * 1024, side), lane), pack2(r, r)));
        if (lane < 8) reinterpret_cast<uint32_t*>(P.out)[rbat * (DM / 2) + 4 * cta + warp] = badd2(rx, bmul2(rg[1], y));
        if (cta == 0 && tid == 0) g_epoch = epoch + 1;
        if (warp == 0) TSL(15);
    }
}

typedef CUresult (*EncodeFn)(CUtensorMap*, CUtensorMapDataType, cuuint32_t, void*, const cuuint64_t*, const cuuint64_t*,
                             const cuuint32_t*, const cuuint32_t*, CUtensorMapInterleave, CUtensorMapSwizzle,
                             CUtensorMapL2promotion, CUtensorMapFloatOOBfill);

#define PROMO_W CU_TENSOR_MAP_L2_PROMOTION_L2_128B
#define PROMO_KV CU_TENSOR_MAP_L2_PROMOTION_L2_256B
constexpr
int dbg_wfront = W_FRONT, dbg_wkv = W_KV, dbg_wwo = W_WO, dbg_wgu = W_GU, dbg_wwd = W_WD, dbg_promo_w = PROMO_W,
    dbg_promo_kv = PROMO_KV, dbg_mode = 0, dbg_slack = 4, dbg_gain = 4, dbg_wmin = 3, dbg_wmax = 8, dbg_tx = 40, dbg_two = 124, dbg_nping = 12, dbg_slack2 = 0;

void make_map(EncodeFn enc, CUtensorMap* m, void* p, int cols, int rows, int pitch, int bc, int br, int bp, int planes, size_t pstride,
              CUtensorMapSwizzle sw, int promo) {
    cuuint64_t dims[3] = {(cuuint64_t)cols, (cuuint64_t)rows, (cuuint64_t)planes};
    cuuint64_t strides[2] = {(cuuint64_t)pitch * 2, (cuuint64_t)pstride};
    cuuint32_t box[3] = {(cuuint32_t)bc, (cuuint32_t)br, (cuuint32_t)bp};
    cuuint32_t es[3] = {1, 1, 1};
    enc(m, CU_TENSOR_MAP_DATA_TYPE_BFLOAT16, 3, p, dims, strides, box, es, CU_TENSOR_MAP_INTERLEAVE_NONE, sw,
        (CUtensorMapL2promotion)promo, CU_TENSOR_MAP_FLOAT_OOB_FILL_NONE);
}

}

extern "C" void kernel_launch(void* const* d_in, const int* in_sizes, int n_in, void* d_out, int out_size) {
    static EncodeFn enc = nullptr;
    static uint32_t* scratch = nullptr;
    if (!enc) {
        void* fn = nullptr;
        cudaDriverEntryPointQueryResult st;
        cudaGetDriverEntryPoint("cuTensorMapEncodeTiled", &fn, cudaEnableDefault, &st);
        enc = (EncodeFn)fn;
        cudaGetSymbolAddress(&fn, g_scratch);
        scratch = (uint32_t*)(((uintptr_t)fn + 4 * G_PAGE - 1) & ~(uintptr_t)(4 * G_PAGE - 1));
        cudaFuncSetAttribute(fused_kernel, cudaFuncAttributeMaxDynamicSharedMemorySize, SMEM_BYTES);
    }
    Params P;
    const CUtensorMapSwizzle none = CU_TENSOR_MAP_SWIZZLE_NONE;
    make_map(enc, &P.m[M_K], d_in[1], 64, NB * HKV * SK, DH, 64, 32, 2, 2, 128, CU_TENSOR_MAP_SWIZZLE_128B, dbg_promo_kv);
    make_map(enc, &P.m[M_V], d_in[2], 64, NB * HKV * SK, DH, 64, 32, 2, 2, 128, CU_TENSOR_MAP_SWIZZLE_128B, dbg_promo_kv);
    make_map(enc, &P.m[M_WQ], d_in[3], HQ * DH, DM, HQ * DH, 32, 192, 1, 1, 16, CU_TENSOR_MAP_SWIZZLE_64B, dbg_promo_w);
    make_map(enc, &P.m[M_WM], d_in[11], 6 * DM, DM, 6 * DM, 32, 192, 1, 1, 16, CU_TENSOR_MAP_SWIZZLE_64B, dbg_promo_w);
    make_map(enc, &P.m[M_WA], d_in[11], DM, DM, 6 * DM, 16, 192, 2, 2, DM * 2, CU_TENSOR_MAP_SWIZZLE_32B, dbg_promo_w);
    char *wg = (char*)d_in[7], *wu = (char*)d_in[8], *wo = (char*)d_in[4], *wd = (char*)d_in[9];
    P.zg = wg > wu;
    P.zo = wo > wd;
    const size_t sg = P.zg ? wg - wu : wu - wg, so = P.zo ? wo - wd : wd - wo;
    make_map(enc, &P.m[M_GU], P.zg ? wu : wg, FF, DM, FF, 32, 64, 2, 2, sg, CU_TENSOR_MAP_SWIZZLE_64B, dbg_promo_w);
    make_map(enc, &P.m[M_GX], P.zg ? wu : wg, FF, DM, FF, 8, 192, 2, 2, sg, none, dbg_promo_w);
    make_map(enc, &P.m[M_OD], P.zo ? wd : wo, DM, FF, DM, 64, 32, 1, 2, so, CU_TENSOR_MAP_SWIZZLE_128B, dbg_promo_w);
    make_map(enc, &P.m[M_OX], P.zo ? wd : wo, DM, FF, DM, 8, 144, 1, 2, so, none, dbg_promo_w);
    P.x = (const __nv_bfloat16*)d_in[0];
    P.wr = (const __nv_bfloat16*)d_in[6];
    P.c = (const __nv_bfloat16*)d_in[10];
    P.out = (__nv_bfloat16*)d_out;
    P.scratch = scratch;
    P.wfront = dbg_wfront;
    P.wkv = dbg_wkv;
    P.wgu = dbg_wgu;
    P.wwd = dbg_wwd;
    P.mode = dbg_mode;
    P.wwo = dbg_wwo;
    P.slack = dbg_slack;
    P.gain = dbg_gain;
    P.wmin = dbg_wmin;
    P.wmax = dbg_wmax;
    P.tx = dbg_tx;
    P.two = dbg_two;
    P.nping = dbg_nping;
    P.slack2 = dbg_slack2;
    fused_kernel<<<NCTA, NTHREADS, SMEM_BYTES>>>(P);
}
```

```cpp
#include <cuda_runtime.h>
#include <cuda_bf16.h>
#include <cuda.h>
#include <stdint.h>

typedef unsigned long long u64;

#define W_FRONT 5
#define W_KV 5
#define W_WO 5
#define W_GU 4
#define W_WD 4

namespace {

constexpr int NB = 8, DM = 576, HQ = 32, HKV = 16, SK = 8192, WIN = 2048, DH = 128, FF = 4608;
constexpr int NCTA = 128;
constexpr int NCW = 10;
constexpr int NTHREADS = (NCW + 2) * 32;
constexpr int TILE_BYTES = 8192, NSLOT = 16, NT = 64;
constexpr int SPIN_LIMIT = 1 << 22;

constexpr int OFF_RING = 0;
constexpr int OFF_WM = 121856;
constexpr int OFF_WQ = OFF_WM + 36864;
constexpr int OFF_GU = 0;
constexpr int OFF_WD = 73728;
constexpr int OFF_OX = 131072;
constexpr int OFF_DX = OFF_OX + 4096;
constexpr int OFF_GX = OFF_DX + 4608;
constexpr int OFF_WO = OFF_WQ;
constexpr int OFF_P = OFF_WQ + 36864;
constexpr int P_PITCH = 528;
constexpr int OFF_RED = OFF_P + 16 * P_PITCH;
constexpr int OFF_ORED = OFF_RED + 5 * 4608 - 8704;
constexpr int OFF_ST = OFF_RED + 5 * 4608;
constexpr int OFF_SM = OFF_ST + 640;
constexpr int OFF_RT = OFF_SM + 128;
constexpr int OFF_HU = OFF_RT + 384;
constexpr int OFF_QS = OFF_HU + 128;
constexpr int OFF_WIN = OFF_QS + 512;
constexpr int OFF_BAR = OFF_WIN + 16;
constexpr int BAR_SYNC = 6, BAR_WMF = 8, BAR_X = 9, BAR_FULL = 14, BAR_WO = 30, BAR_GU = 34, BAR_WD = 43, BAR_EMPTY = 52, NBAR = 68;
constexpr int SMEM_BYTES = OFF_BAR + NBAR * 8;

constexpr int D_X1 = 0;
constexpr int D_O = 3072;
constexpr int D_ACT = D_O + 512 * 32;
constexpr int D_P = D_ACT + 576 * 32;
constexpr int D_PING = D_P + 2 * 72 * 1024;
constexpr int G_H = 2 * (D_PING + 1024);
constexpr int G_M = G_H + 72 * 32;
constexpr int G_Q = G_M + 288 * 32;
constexpr int G_CNT = G_Q + NB * HQ * 64;
constexpr int G_PAGE = 1 << 19;
static_assert(G_CNT < G_PAGE, "scratch exceeds a page");
__device__ unsigned g_epoch;
__device__ uint32_t g_scratch[3 * G_PAGE];
__device__ __forceinline__ int dual(int w) { return w + (w & ~1023); }
__device__ __forceinline__ int near(int w, int side) { return dual(w) + (((__popc(w & 0x16400) ^ side) & 1) << 10); }

#define TI(i)
#define TS(i)
#define TSL(i)

enum { M_K, M_V, M_GU, M_GX, M_OD, M_OX, M_WQ, M_WM, M_WA, NMAP };
struct Params {
    CUtensorMap m[NMAP];
    const __nv_bfloat16 *k, *v, *wm, *wq, *x, *c, *wr;
    __nv_bfloat16* out;
    uint32_t* scratch;
    int zg, zo;
    int wfront, wkv, wgu, wwd, mode, wwo, slack, gain, wmin, wmax, tx, two, nping, slack2, tclr, npf, ntp, gain2;
};

__device__ __forceinline__ void mbar_init(uint32_t bar, int cnt) {
    asm volatile("mbarrier.init.shared::cta.b64 [%0], %1;" ::"r"(bar), "r"(cnt));
}
__device__ __forceinline__ void mbar_expect(uint32_t bar, uint32_t bytes) {
    asm volatile("mbarrier.arrive.expect_tx.shared::cta.b64 _, [%0], %1;" ::"r"(bar), "r"(bytes) : "memory");
}
__device__ __forceinline__ void mbar_arrive(uint32_t bar) {
    asm volatile("mbarrier.arrive.shared::cta.b64 _, [%0];" ::"r"(bar) : "memory");
}
__device__ __forceinline__ void mbar_wait(uint32_t bar, uint32_t parity) {
    asm volatile("{\n.reg .pred p;\n.reg .u32 c;\n"
                 "mbarrier.try_wait.parity.shared::cta.b64 p, [%0], %1;\n@p bra DONE;\nmov.u32 c, %2;\n"
                 "AGAIN:\nmbarrier.try_wait.parity.shared::cta.b64 p, [%0], %1;\nsub.u32 c, c, 1;\n"
                 "setp.eq.or.u32 p, c, 0, p;\n@!p bra AGAIN;\nDONE:\n}"
                 ::"r"(bar), "r"(parity), "n"(SPIN_LIMIT) : "memory");
}
__device__ __forceinline__ bool mbar_test(uint32_t bar, uint32_t parity) {
    uint32_t ok;
    asm volatile("{\n.reg .pred p;\nmbarrier.test_wait.parity.shared::cta.b64 p, [%1], %2;\nselp.u32 %0, 1, 0, p;\n}"
                 : "=r"(ok) : "r"(bar), "r"(parity) : "memory");
    return ok;
}
__device__ __forceinline__ void mbar_wait_lanes(uint32_t bar) {
    mbar_wait(bar, 0);
    __syncwarp();
}
__device__ __forceinline__ void tma3d_hint(uint32_t dst, const CUtensorMap* m, int x, int y, int z, uint32_t bar, u64 pol) {
    asm volatile("cp.async.bulk.tensor.3d.shared::cluster.global.mbarrier::complete_tx::bytes.L2::cache_hint"
                 " [%0], [%1, {%2, %3, %4}], [%5], %6;"
                 ::"r"(dst), "l"(m), "r"(x), "r"(y), "r"(z), "r"(bar), "l"(pol) : "memory");
}
__device__ __forceinline__ void tma3d(uint32_t dst, const CUtensorMap* m, int x, int y, int z, uint32_t bar) {
    asm volatile("cp.async.bulk.tensor.3d.shared::cluster.global.mbarrier::complete_tx::bytes [%0], [%1, {%2, %3, %4}], [%5];"
                 ::"r"(dst), "l"(m), "r"(x), "r"(y), "r"(z), "r"(bar) : "memory");
}
__device__ __forceinline__ void bar_sync(int id, int n) { asm volatile("bar.sync %0, %1;" ::"r"(id), "r"(n) : "memory"); }
__device__ __forceinline__ void bar_arrive(int id, int n) { asm volatile("bar.arrive %0, %1;" ::"r"(id), "r"(n) : "memory"); }
__device__ __forceinline__ void ldsm4(uint32_t (&r)[4], uint32_t a) {
    asm volatile("ldmatrix.sync.aligned.m8n8.x4.shared.b16 {%0,%1,%2,%3}, [%4];"
                 : "=r"(r[0]), "=r"(r[1]), "=r"(r[2]), "=r"(r[3]) : "r"(a) : "memory");
}
__device__ __forceinline__ void ldsm4t(uint32_t (&r)[4], uint32_t a) {
    asm volatile("ldmatrix.sync.aligned.m8n8.x4.trans.shared.b16 {%0,%1,%2,%3}, [%4];"
                 : "=r"(r[0]), "=r"(r[1]), "=r"(r[2]), "=r"(r[3]) : "r"(a) : "memory");
}
__device__ __forceinline__ void mma(float (&c)[4], uint32_t a0, uint32_t a1, uint32_t a2, uint32_t a3, uint32_t b0, uint32_t b1) {
    asm volatile("mma.sync.aligned.m16n8k16.row.col.f32.bf16.bf16.f32 {%0,%1,%2,%3}, {%4,%5,%6,%7}, {%8,%9}, {%0,%1,%2,%3};"
                 : "+f"(c[0]), "+f"(c[1]), "+f"(c[2]), "+f"(c[3])
                 : "r"(a0), "r"(a1), "r"(a2), "r"(a3), "r"(b0), "r"(b1));
}
__device__ __forceinline__ uint32_t movm(uint32_t a) {
    uint32_t d;
    asm volatile("movmatrix.sync.aligned.m8n8.trans.b16 %0, %1;" : "=r"(d) : "r"(a));
    return d;
}
__device__ __forceinline__ uint32_t lds32(uint32_t a) { uint32_t v; asm volatile("ld.shared.b32 %0, [%1];" : "=r"(v) : "r"(a) : "memory"); return v; }
__device__ __forceinline__ float2 lds64f(uint32_t a) { float2 v; asm volatile("ld.shared.v2.f32 {%0,%1}, [%2];" : "=f"(v.x), "=f"(v.y) : "r"(a) : "memory"); return v; }
__device__ __forceinline__ uint4 lds128(uint32_t a) { uint4 v; asm volatile("ld.shared.v4.b32 {%0,%1,%2,%3}, [%4];" : "=r"(v.x), "=r"(v.y), "=r"(v.z), "=r"(v.w) : "r"(a) : "memory"); return v; }
__device__ __forceinline__ void sts32(uint32_t a, uint32_t v) { asm volatile("st.shared.b32 [%0], %1;" ::"r"(a), "r"(v) : "memory"); }
__device__ __forceinline__ void sts16(uint32_t a, uint16_t v) { asm volatile("st.shared.b16 [%0], %1;" ::"r"(a), "h"(v) : "memory"); }
__device__ __forceinline__ void sts64(uint32_t a, uint32_t x, uint32_t y) { asm volatile("st.shared.v2.b32 [%0], {%1,%2};" ::"r"(a), "r"(x), "r"(y) : "memory"); }
__device__ __forceinline__ void sts128(uint32_t a, uint32_t x, uint32_t y, uint32_t z, uint32_t w) {
    asm volatile("st.shared.v4.b32 [%0], {%1,%2,%3,%4};" ::"r"(a), "r"(x), "r"(y), "r"(z), "r"(w) : "memory");
}
__device__ __forceinline__ void sts128f(uint32_t a, const float (&c)[4]) {
    sts128(a, __float_as_uint(c[0]), __float_as_uint(c[1]), __float_as_uint(c[2]), __float_as_uint(c[3]));
}

__device__ __forceinline__ float sel4(const float (&c)[4], int t) { return (t & 2) ? ((t & 1) ? c[3] : c[2]) : ((t & 1) ? c[1] : c[0]); }

__device__ __forceinline__ uint32_t clock32(uint32_t dep) {
    uint32_t t;
    asm volatile("{\n.reg .pred p;\nsetp.eq.u32 p, %1, 0x9e3779b9;\n@p nanosleep.u32 1;\nmov.u32 %0, %clock;\n}" : "=r"(t) : "r"(dep) : "memory");
    return t;
}

__device__ __forceinline__ uint32_t nz(uint32_t v) { return v ? v : 0x80000000u; }
__device__ __forceinline__ void st1(uint32_t* p, uint32_t a) { asm volatile("st.relaxed.gpu.global.b32 [%0], %1;" ::"l"(p), "r"(a) : "memory"); }
__device__ __forceinline__ void st2(uint32_t* p, uint32_t a, uint32_t b) {
    asm volatile("st.relaxed.gpu.global.v2.b32 [%0], {%1,%2};" ::"l"(p), "r"(a), "r"(b) : "memory");
}
__device__ __forceinline__ void put1(uint32_t* p, uint32_t a) { st1(p, nz(a)); }
__device__ __forceinline__ void put2(uint32_t* p, uint32_t a, uint32_t b) { st2(p, nz(a), nz(b)); }
__device__ __forceinline__ void put1d(uint32_t* p, uint32_t a) { a = nz(a), st1(p, a), st1(p + 1024, a); }
__device__ __forceinline__ void put2d(uint32_t* p, uint32_t a, uint32_t b) { a = nz(a), b = nz(b), st2(p, a, b), st2(p + 1024, a, b); }
__device__ __forceinline__ void clear1(uint32_t* p) { st1(p, 0), st1(p + G_PAGE, 0); }
__device__ __forceinline__ void clear2(uint32_t* p) { st2(p, 0, 0), st2(p + G_PAGE, 0, 0); }
__device__ __forceinline__ void clear1d(uint32_t* p) { st1(p, 0), st1(p + 1024, 0); }
__device__ __forceinline__ void clear2d(uint32_t* p) { st2(p, 0, 0), st2(p + 1024, 0, 0); }
__device__ __forceinline__ void probe(const uint32_t* p, int slack) {
    uint32_t v;
    int it = 0;
    do {
        asm volatile("ld.relaxed.gpu.global.b32 %0, [%1];" : "=r"(v) : "l"(p) : "memory");
    } while (__popc(__ballot_sync(0xffffffffu, v == 0)) > slack && ++it < SPIN_LIMIT);
}
__device__ __forceinline__ uint32_t ld1(const uint32_t* p) {
    uint32_t v;
    asm volatile("ld.relaxed.gpu.global.b32 %0, [%1];" : "=r"(v) : "l"(p) : "memory");
    return v;
}
template <int N>
__device__ __forceinline__ void reget1(const uint32_t* p, int stride, uint32_t (&a)[N]) {
#pragma unroll 1
    for (int it = 0; it < SPIN_LIMIT; it++) {
        uint32_t lo = a[0];
#pragma unroll
        for (int i = 1; i < N; i++) lo = min(lo, a[i]);
        if (!__any_sync(0xffffffffu, lo == 0)) break;
#pragma unroll
        for (int i = 0; i < N; i++)
            asm volatile("{\n.reg .pred p;\nsetp.eq.u32 p, %0, 0;\n@p ld.relaxed.gpu.global.b32 %0, [%1];\n}"
                         : "+r"(a[i]) : "l"(p + i * stride) : "memory");
    }
}
template <int N>
__device__ __forceinline__ void get1(const uint32_t* p, int stride, uint32_t (&a)[N]) {
#pragma unroll
    for (int i = 0; i < N; i++) a[i] = 0;
    reget1<N>(p, stride, a);
}
template <int N>
__device__ __forceinline__ void get2(const uint32_t* p, int stride, uint32_t (&a)[N], uint32_t (&b)[N]) {
    uint32_t m[N], lo;
    int it = 0;
#pragma unroll
    for (int i = 0; i < N; i++) m[i] = a[i] = b[i] = 0;
    do {
#pragma unroll
        for (int i = 0; i < N; i++)
            asm volatile("{\n.reg .pred p;\nsetp.eq.u32 p, %2, 0;\n@p ld.relaxed.gpu.global.v2.b32 {%0,%1}, [%3];\n}"
                         : "+r"(a[i]), "+r"(b[i]) : "r"(m[i]), "l"(p + i * stride) : "memory");
        lo = 1;
#pragma unroll
        for (int i = 0; i < N; i++) m[i] = min(a[i], b[i]), lo = min(lo, m[i]);
    } while (__any_sync(0xffffffffu, lo == 0) && ++it < SPIN_LIMIT);
}
__device__ __forceinline__ void get4(const uint32_t* p, uint32_t (&a)[4]) {
    uint32_t lo = 0;
    int it = 0;
    a[0] = a[1] = a[2] = a[3] = 0;
    do {
        asm volatile("{\n.reg .pred p;\nsetp.eq.u32 p, %4, 0;\n@p ld.relaxed.gpu.global.v4.b32 {%0,%1,%2,%3}, [%5];\n}"
                     : "+r"(a[0]), "+r"(a[1]), "+r"(a[2]), "+r"(a[3]) : "r"(lo), "l"(p) : "memory");
        lo = min(min(a[0], a[1]), min(a[2], a[3]));
    } while (__any_sync(0xffffffffu, lo == 0) && ++it < SPIN_LIMIT);
}
__device__ __forceinline__ void cp16(uint32_t dst, const void* src) {
    asm volatile("cp.async.cg.shared.global [%0], [%1], 16;" ::"r"(dst), "l"(src) : "memory");
}

__device__ __forceinline__ uint32_t pack2(float lo, float hi) {
    uint32_t r;
    asm("cvt.rn.bf16x2.f32 %0, %1, %2;" : "=r"(r) : "f"(hi), "f"(lo));
    return r;
}
__device__ __forceinline__ float rbf(float x) { return __uint_as_float(pack2(0.f, x)); }
__device__ __forceinline__ float blo(uint32_t v) { return __uint_as_float(v << 16); }
__device__ __forceinline__ float bhi(uint32_t v) { return __uint_as_float(v & 0xffff0000u); }
__device__ __forceinline__ uint32_t badd2(uint32_t a, uint32_t b) { uint32_t r; asm("add.rn.bf16x2 %0, %1, %2;" : "=r"(r) : "r"(a), "r"(b)); return r; }
__device__ __forceinline__ uint32_t bsub2(uint32_t a, uint32_t b) { uint32_t r; asm("sub.rn.bf16x2 %0, %1, %2;" : "=r"(r) : "r"(a), "r"(b)); return r; }
__device__ __forceinline__ uint32_t bmul2(uint32_t a, uint32_t b) { uint32_t r; asm("mul.rn.bf16x2 %0, %1, %2;" : "=r"(r) : "r"(a), "r"(b)); return r; }
__device__ __forceinline__ float ex2(float x) { float r; asm("ex2.approx.ftz.f32 %0, %1;" : "=f"(r) : "f"(x)); return r; }
__device__ __forceinline__ float rcp(float x) { float r; asm("rcp.approx.ftz.f32 %0, %1;" : "=f"(r) : "f"(x)); return r; }
__device__ __forceinline__ float sqrt_f(float x) { float r; asm("sqrt.approx.ftz.f32 %0, %1;" : "=f"(r) : "f"(x)); return r; }
constexpr float LOG2E = 1.4426950408889634f;
constexpr uint32_t ONE2 = 0x3f803f80u;
__device__ __forceinline__ float sigmoid_f(float x) { return rcp(1.0f + ex2(-LOG2E * x)); }
__device__ __forceinline__ uint32_t silu2(uint32_t v) {
    const float a = blo(v), b = bhi(v);
    return pack2(a * sigmoid_f(a), b * sigmoid_f(b));
}
__device__ __forceinline__ float quad_sum(float v) {
    v += __shfl_xor_sync(0xffffffffu, v, 1);
    return v + __shfl_xor_sync(0xffffffffu, v, 2);
}
__device__ __forceinline__ void ln_partial(const uint32_t (&v)[8], uint32_t dst, bool writer) {
    float s0 = 0.f, s1 = 0.f;
#pragma unroll
    for (int i = 0; i < 8; i++) {
        s0 += blo(v[i]);
        s1 += bhi(v[i]);
    }
    const float mean = quad_sum(s0 + s1) * (1.0f / 64);
    s0 = s1 = 0.f;
#pragma unroll
    for (int i = 0; i < 8; i++) {
        const float a = blo(v[i]) - mean, b = bhi(v[i]) - mean;
        s0 = fmaf(a, a, s0);
        s1 = fmaf(b, b, s1);
    }
    s0 = quad_sum(s0 + s1);
    if (writer) sts64(dst, __float_as_uint(mean), __float_as_uint(s0));
}
__device__ __forceinline__ void ln_combine(uint32_t src, uint32_t& mean2, float& inv) {
    float m[10], q0 = 0.f, q1 = 0.f, s = 0.f;
#pragma unroll
    for (int i = 0; i < 5; i++) {
        const uint4 v = lds128(src + i * 16);
        m[2 * i] = __uint_as_float(v.x);
        m[2 * i + 1] = __uint_as_float(v.z);
        q0 += __uint_as_float(v.y);
        if (i < 4) q1 += __uint_as_float(v.w);
    }
    const float mean = (((m[0] + m[1]) + (m[2] + m[3])) + ((m[4] + m[5]) + (m[6] + m[7])) + m[8]) * (1.0f / 9);
#pragma unroll
    for (int i = 0; i < 9; i++) s = fmaf(m[i] - mean, m[i] - mean, s);
    const float var = fmaf(s, 64.f, q0 + q1) * (1.0f / DM);
    mean2 = pack2(mean, mean);
    inv = rcp(rbf(sqrt_f(rbf(rbf(var) + 1e-5f))));
}
__device__ __forceinline__ uint32_t modulate2(uint32_t x, uint32_t mean2, float inv, uint32_t shift, uint32_t onep) {
    const uint32_t d = bsub2(x, mean2);
    return badd2(bmul2(pack2(blo(d) * inv, bhi(d) * inv), onep), shift);
}
template <int N>
__device__ __forceinline__ void sum_frags(float (&c)[4], uint32_t addr, int stride) {
#pragma unroll
    for (int w = 0; w < N; w++) {
        const uint4 v = lds128(addr + w * stride);
        c[0] += __uint_as_float(v.x); c[1] += __uint_as_float(v.y);
        c[2] += __uint_as_float(v.z); c[3] += __uint_as_float(v.w);
    }
}

template <int ST>
__device__ __forceinline__ void project(uint32_t sm, const uint32_t* src, uint32_t* dst, int warp, int lane) {
    constexpr int NW = ST ? 9 : 8;
    const uint32_t red = sm + (ST ? OFF_WO : OFF_P) + lane * 8;
    if (warp < NW) {
        const uint32_t wbar = sm + OFF_BAR + ((ST ? BAR_WD : BAR_WO) + (warp >> 1)) * 8;
        const int r = warp * 32 + (lane >> 4) * 8 + (lane & 7);
        const uint32_t ab = sm + (ST ? OFF_WD : OFF_WO) + r * 128 + ((((lane >> 3) & 1) ^ (lane & 7)) << 4);
        const uint32_t ax = sm + (ST ? OFF_DX : OFF_OX) + r * 16;
        uint32_t a[10][4], b[4];
        auto load_w = [&]() {
#pragma unroll
            for (int i = 0; i < 10; i++) ldsm4t(a[i], i % 5 < 4 ? (ab ^ ((i % 5) << 5)) + (i / 5) * 2048 : ax + (i / 5) * 256);
        };
        const bool pre = __all_sync(0xffffffffu, mbar_test(wbar, 0));
        load_w();
        if (ST) get1<4>(src, 32, b);
        else get4(src, b);
        if (warp == 0) TSL(ST ? 24 : 21);
        if (!pre) {
            mbar_wait_lanes(wbar);
            load_w();
        }
        float acc[5][4] = {};
#pragma unroll
        for (int i = 0; i < 10; i++) mma(acc[i % 5], a[i][0], a[i][1], a[i][2], a[i][3], b[2 * (i / 5)], b[2 * (i / 5) + 1]);
#pragma unroll
        for (int u = 0; u < 9; u++)
            sts64(red + u * 2304 + warp * 256, __float_as_uint(acc[u >> 1][2 * (u & 1)]), __float_as_uint(acc[u >> 1][2 * (u & 1) + 1]));
    }
    bar_sync(3, 288);
    float s[2][2] = {};
#pragma unroll
    for (int w = 0; w < NW; w++) {
        const float2 v = lds64f(red + warp * 2304 + w * 256);
        s[w & 1][0] += v.x;
        s[w & 1][1] += v.y;
    }
    put2d(dst, __float_as_uint(s[0][0] + s[1][0]), __float_as_uint(s[0][1] + s[1][1]));
}

__device__ __forceinline__ uint32_t reduce16(const uint32_t* src, int lane) {
    uint32_t a[4], b[4];
    get2<4>(src, 64, a, b);
    float s0 = (__uint_as_float(a[0]) + __uint_as_float(a[1])) + (__uint_as_float(a[2]) + __uint_as_float(a[3]));
    float s1 = (__uint_as_float(b[0]) + __uint_as_float(b[1])) + (__uint_as_float(b[2]) + __uint_as_float(b[3]));
#pragma unroll
    for (int o = 8; o < 32; o <<= 1) {
        s0 += __shfl_xor_sync(0xffffffffu, s0, o);
        s1 += __shfl_xor_sync(0xffffffffu, s1, o);
    }
    const uint32_t y = pack2(s0, s1);
    return __byte_perm(y, __shfl_xor_sync(0xffffffffu, y, 4), (lane & 4) ? 0x3276 : 0x5410);
}

__global__ void __launch_bounds__(NTHREADS, 1) fused_kernel(const __grid_constant__ Params P) {
    extern __shared__ __align__(1024) char smem_raw[];
    const uint32_t sm = (uint32_t)__cvta_generic_to_shared(smem_raw);
    const int tid = threadIdx.x, lane = tid & 31;
    const int cta = blockIdx.x, grp = cta >> 3, sub = cta & 7;
    if (tid == NTHREADS - 32 && P.npf)
        asm volatile("cp.async.bulk.prefetch.L2.global [%0], %1;"
                     ::"l"(P.k + ((size_t)(sub * HKV + grp) * SK + (SK - WIN)) * DH), "r"(P.npf * TILE_BYTES) : "memory");
    if (tid == 288 && (P.mode & 512)) asm volatile("cp.async.bulk.prefetch.L2.global [%0], 31104;" ::"l"(P.wm + cta * 15552) : "memory");
    if (tid >= 256 && tid < 261 && (P.mode & 1024) && (cta * 9) / 2 + lane < (cta * 9 + 9) / 2)
        asm volatile("cp.async.bulk.prefetch.L2.global [%0], 2304;" ::"l"(P.wm + ((cta * 9) / 2 + lane) * (6 * DM)) : "memory");
    if (tid == 224 && (P.mode & 2048)) asm volatile("cp.async.bulk.prefetch.L2.global [%0], 36864;" ::"l"(P.wq + cta * 18432) : "memory");
    if (tid == 192 && (P.mode & 4096) && cta < 18) asm volatile("cp.async.bulk.prefetch.L2.global [%0], 1024;" ::"l"((cta < 9 ? P.c : P.x - 4608) + cta * 512) : "memory");
    const int warp = __shfl_sync(0xffffffffu, tid >> 5, 0);
    const uint32_t bars = sm + OFF_BAR;

    if (lane == 0 && warp <= NCW) {
        if (warp == NCW) TS(0);
#pragma unroll
        for (int i = 0; i < 6; i++) mbar_init(bars + (warp == NCW ? 0 : 64 + warp * 48) + i * 8, 1);
        if (warp == 9) mbar_init(bars + 48, 1), mbar_init(bars + 56, 1);
        asm volatile("fence.mbarrier_init.release.cluster;" ::: "memory");
    }

    if (warp >= NCW) {
        const int pw = warp - NCW, n0 = cta < 108 ? 0 : 3;
        if (pw == 0) {
            if (lane == 0) {
#pragma unroll
                for (int i = 0; i < 3; i++) {
                    mbar_expect(bars + (n0 + i) * 8, 12288);
                    tma3d(sm + OFF_WM + (n0 + i) * 12288, &P.m[cta < 36 ? M_WA : cta < 108 ? M_WM : M_WQ],
                          cta < 36 ? 16 * cta : 32 * cta, i * 192, 0, bars + (n0 + i) * 8);
                    TI(n0 + i);
                }
                TS(26);
                sts32(sm + OFF_WIN, 0);
            }
            __syncwarp();
            bar_arrive(1, (NCW + 1) * 32);
        } else if (lane <= M_WQ) {
            asm volatile("prefetch.tensormap [%0];" ::"l"(&P.m[M_WQ - lane]) : "memory");
        }
        __syncwarp();
        bar_sync(15, NTHREADS);
        if (lane == 0) {
            u64 pol;
            asm volatile("createpolicy.fractional.L2::evict_first.b64 %0, 1.0;" : "=l"(pol));
            const int row0 = (sub * HKV + grp) * SK + (SK - WIN);
            if (n0 == 0) {
#pragma unroll 1
                for (int n = 3 + pw; n < 6; n += 2) {
                    mbar_expect(bars + n * 8, 12288);
                    if (n >= P.wfront) mbar_wait(bars + (n - P.wfront) * 8, 0);
                    tma3d(sm + OFF_WM + n * 12288, &P.m[M_WQ], 32 * cta, (n - 3) * 192, 0, bars + n * 8);
                    TI(n);
                }
            }
#pragma unroll 1
            for (int t = pw ^ 1; t < NSLOT; t += 2) {
                const int m = t - P.wfront;
                if (t >= 14 && n0 == 0) mbar_wait(bars + BAR_WMF * 8, 0);
                mbar_expect(bars + (BAR_FULL + t) * 8, TILE_BYTES);
                if (m + 6 >= n0) mbar_wait(bars + (m + (m < 0 ? 6 : BAR_FULL)) * 8, 0);
                tma3d_hint(sm + OFF_RING + t * TILE_BYTES, &P.m[M_K], 0, row0 + t * 32, 0, bars + (BAR_FULL + t) * 8, pol);
                TI(6 + t);
            }
            TS(30);
            if (pw == 0) {
#pragma unroll 1
                for (int t = NSLOT; t < 2 * NT; t++) {
                    const int m = t - P.wkv - (int)lds32(sm + OFF_WIN);
                    const uint32_t fb = bars + (BAR_FULL + (t & 15)) * 8;
                    mbar_wait(fb + (BAR_EMPTY - BAR_FULL) * 8, (~t >> 4) & 1);
                    mbar_expect(fb, TILE_BYTES);
                    mbar_wait(bars + (BAR_FULL + (m & 15)) * 8, (m >> 4) & 1);
                    tma3d_hint(sm + OFF_RING + (t & 15) * TILE_BYTES, &P.m[t >> 6], 0, row0 + (t & (NT - 1)) * 32, 0, fb, pol);
                    TI(6 + t);
                    if (t == 104) mbar_arrive(bars + (BAR_SYNC + 1) * 8);
                }
                mbar_wait(bars + BAR_SYNC * 8, 0);
                auto window = [&](int b, int w) {
                    b -= max(w + (int)lds32(sm + OFF_WIN), 1);
                    mbar_wait(bars + b * 8, b < BAR_WO);
                };
#pragma unroll 1
                for (int i = 0; i < 4; i++) {
                    window(BAR_WO + i, P.wwo);
                    tma3d(sm + OFF_WO + i * 8192, &P.m[M_OD], 64 * sub, grp * 256 + i * 64, P.zo, bars + (BAR_WO + i) * 8);
                    TI(134 + i);
                }
                TS(28);
#pragma unroll 1
                for (int i = 0; i < 9; i++) {
                    mbar_wait(bars + (BAR_EMPTY + i) * 8, 1);
                    window(BAR_GU + i, P.wgu);
                    tma3d(sm + OFF_GU + i * 8192, &P.m[M_GU], grp * 288 + 32 * sub, i * 64, 0, bars + (BAR_GU + i) * 8);
                    TI(138 + i);
                }
                TS(29);
#pragma unroll 1
                for (int i = 0; i < 5; i++) {
                    const int r = min(i * 64, 224);
                    mbar_wait(bars + (BAR_EMPTY + 9 + i) * 8, 1);
                    window(BAR_WD + i, P.wwd);
                    tma3d(sm + OFF_WD + r * 128, &P.m[M_OD], 64 * sub, grp * 288 + r, P.zo ^ 1, bars + (BAR_WD + i) * 8);
                    TI(147 + i);
                }
            } else {
                mbar_wait(bars + (BAR_FULL + P.tx) * 8, 0);
#pragma unroll 1
                for (int i = 0; i < (sub < 4 ? 7 : 4); i++) {
                    const int r = (i & 1) * (i < 2 ? 112 : 144);
                    if (i >= 4 || i == 0) mbar_expect(bars + BAR_X * 8, i < 4 ? 9216 : 6144);
                    if (i < 4) tma3d(sm + OFF_OX + (i >> 1) * 4096 + r * 16, &P.m[M_OX], 512 + 8 * sub, grp * (i < 2 ? 256 : 288) + r, P.zo ^ (i >> 1), bars + BAR_X * 8);
                    else tma3d(sm + OFF_GX + (i - 4) * 6144, &P.m[M_GX], grp * 288 + 256 + 8 * sub, (i - 4) * 192, 0, bars + BAR_X * 8);
                    TI(152 + i);
                    if (i >= 3) mbar_wait(bars + BAR_X * 8, ~i & 1);
                }
#pragma unroll 1
                for (int i = 0; i < 18; i++) mbar_expect(bars + (BAR_WO + i) * 8, 8192);
                mbar_arrive(bars + BAR_SYNC * 8);
                uint32_t* const cnt = P.scratch + (ld1(&g_epoch) & 1) * G_PAGE + G_CNT;
#pragma unroll 1
                for (int j = 0; j < P.ntp; j++) {
                    mbar_wait(bars + (BAR_WO + P.two * j) * 8, 0);
                    const int d = (int)atomicAdd(cnt, 1u) - 128 * (26 + j) - 64;
                    sts32(sm + OFF_WIN, min(max((d * P.gain2 + 128) >> 8, P.wmin), P.wmax));
                }
            }
        }
        return;
    }

    __syncwarp();
    bar_arrive(15, NTHREADS);
    const int g = lane >> 2, t4 = lane & 3;
    uint32_t epoch;
    asm volatile("ld.relaxed.gpu.global.u32 %0, [%1];" : "=r"(epoch) : "l"(&g_epoch) : "memory");
    uint32_t* const g0 = P.scratch;
    uint32_t* const gs = g0 + (epoch & 1) * G_PAGE;

    if (warp < 9) {
        const int off_h = (cta < 36 ? G_H + 2 * cta * 32 : G_M + 4 * (cta - 36) * 32) + tid;
        const int off_q = G_Q + g * (HQ * 64) + cta * 16 + warp * 8 + t4 * 2;
        uint32_t bf[8] = {}, xp = 0, mean2 = 0;
        float inv = 0.f;
        if (cta < 108) {
            const uint32_t stage = sm + OFF_RED + warp * 2048;
#pragma unroll
            for (int i = 0; i < 2; i++) {
                const int row = (lane >> 3) + 4 * i, so = row * DM + warp * 64 + (lane & 7) * 8;
                const uint32_t d = stage + row * 128 + (((lane & 7) ^ row) << 4);
                cp16(d, P.c + so);
                if (cta < 36) cp16(d + 1024, P.x + so);
            }
            if (cta < 36) xp = __ldg(reinterpret_cast<const uint32_t*>(P.x) + g * (DM / 2) + 8 * cta + 4 * (warp & 1) + t4);
        }
        if (warp < 2) {
            clear2(g0 + off_q);
            if (cta < 108) clear1(g0 + off_h);
            if (cta >= 36 && cta < 108) clear1(g0 + off_h + 64);
        }
        if (cta < 108) {
            asm volatile("cp.async.wait_all;" ::: "memory");
            __syncwarp();
            const uint32_t fa = sm + OFF_RED + warp * 2048 + (lane & 7) * 128 + (((lane >> 3) ^ (lane & 7)) << 4);
            ldsm4(reinterpret_cast<uint32_t(&)[4]>(bf[0]), fa);
            ldsm4(reinterpret_cast<uint32_t(&)[4]>(bf[4]), fa ^ 64);
            if (cta < 36) {
                uint32_t xv[8];
                ldsm4(reinterpret_cast<uint32_t(&)[4]>(xv[0]), fa + 1024);
                ldsm4(reinterpret_cast<uint32_t(&)[4]>(xv[4]), (fa ^ 64) + 1024);
                ln_partial(xv, sm + OFF_ST + g * 80 + warp * 8, t4 == 0);
            }
#pragma unroll
            for (int i = 0; i < 8; i++) bf[i] = silu2(bf[i]);
        }
        if (warp == 0) TSL(18);
        bar_sync(1, (NCW + 1) * 32);
        if (cta < 36 && warp < 2) ln_combine(sm + OFF_ST + g * 80, mean2, inv);
        const int r = warp * 64 + (lane >> 4) * 8 + (lane & 7), hi8 = (lane >> 3) & 1, box = warp / 3;
#pragma unroll 1
        for (int pass = cta < 108 ? 0 : 1; pass < 2; pass++) {
            const bool pa = pass == 0 && cta < 36;
            const uint32_t ab = sm + OFF_WM + pass * 36864 +
                                (pa ? (box + hi8) * 6144 + r * 32 + ((lane & 4) << 2) : r * 64 + (((2 * hi8) ^ ((r >> 1) & 3)) << 4));
            const uint32_t as = pa ? 512 : 1024, red = sm + OFF_RED + pass * 9216;
            mbar_wait(bars + (pass * 3 + box) * 8, 0);
            if (warp == 8) TSL(pass ? 31 : 19);
            uint32_t a[4][2][4];
#pragma unroll
            for (int i = 0; i < 4; i++) {
                ldsm4t(a[i][0], ab + i * as);
                ldsm4t(a[i][1], (ab ^ 16) + i * as);
            }
            if (pass) {
                if (P.mode & 4) probe(gs + G_H + warp * 256, 0);
                get1<8>(gs + G_H + warp * 256 + lane, 32, bf);
                if (warp == 0) TSL(3);
            }
            float acc[2][4] = {};
#pragma unroll
            for (int i = 0; i < 4; i++)
#pragma unroll
                for (int m = 0; m < 2; m++) mma(acc[m], a[i][m][0], a[i][m][1], a[i][m][2], a[i][m][3], bf[2 * i], bf[2 * i + 1]);
            sts128f(red + tid * 16, acc[0]);
            sts128f(red + 4608 + tid * 16, acc[1]);
            bar_sync(3, 288);
            if (warp < 2) {
                float c[4] = {};
                sum_frags<9>(c, red + warp * 4608 + lane * 16, 512);
                uint32_t lo = movm(pack2(c[0], c[1])), hi = movm(pack2(c[2], c[3]));
                if (pass) {
                    put2(gs + off_q, lo, hi);
                    if (warp == 0) TSL(4);
                } else {
                    const uint32_t hi1 = badd2(hi, ONE2);
                    if (pa) lo = modulate2(xp, mean2, inv, lo, hi1);
                    if (cta >= 72 && cta < 90) lo = badd2(lo, ONE2), hi = hi1;
                    put1(gs + off_h, lo);
                    if (!pa) put1(gs + off_h + 64, hi);
                    if (warp == 0 && pa) TSL(2);
                }
            } else if (tid == 64 && pass == 0) {
                mbar_arrive(bars + BAR_WMF * 8);
            }
        }
    } else {
        bar_sync(1, (NCW + 1) * 32);
        mbar_wait(bars + 5 * 8, 0);
        uint32_t a[4];
        get4(gs + G_Q + (sub * HQ + 2 * grp) * 64 + lane * 4, a);
        sts128(sm + OFF_QS + lane * 16, a[0], a[1], a[2], a[3]);
        __syncwarp();
        TSL(5);
        bar_arrive(4, 288);
    }

    const uint32_t tile = sm + OFF_RING + warp * TILE_BYTES;
    const uint32_t fullb = bars + (BAR_FULL + warp) * 8;
    const uint32_t pw = sm + OFF_P + warp * (2 * P_PITCH);
    auto pace = [&](int t) {
        if ((tid & 127) == 96 && t >= 16) {
            const int d = (int)atomicAdd(gs + G_CNT, 1u) - 32 * (t - 19) - 64;
            sts32(sm + OFF_WIN, min(max((d * P.gain + 128) >> 8, P.wmin), P.wmax));
        }
    };
    if (cta == 0 && tid == 288) st1(g0 + (~epoch & 1) * G_PAGE + G_CNT, 0);
    if (warp < 8) {
        {
            uint32_t q0[8], q1[8];
            bar_sync(4, 288);
#pragma unroll
            for (int i = 0; i < 8; i++) {
                const float2 v = lds64f(sm + OFF_QS + (g & 1) * 256 + i * 32 + t4 * 8);
                q0[i] = __float_as_uint(v.x), q1[i] = __float_as_uint(v.y);
            }
            uint32_t sp = pw + (t4 & 1) * P_PITCH + ((t4 >> 1) * 8 + g) * 2;
#pragma unroll 1
            for (int it = 0; it < 8; it++, sp += 64) {
                const uint32_t ab = tile + (it & 1) * (8 * TILE_BYTES) + (lane & 15) * 128 + (((lane >> 4) ^ (lane & 7)) << 4);
                mbar_wait(fullb + (it & 1) * 64, (it >> 1) & 1);
                float acc[2][2][4] = {};
#pragma unroll
                for (int ks = 0; ks < 8; ks++)
#pragma unroll
                    for (int m = 0; m < 2; m++) {
                        uint32_t a[4];
                        ldsm4(a, (ab ^ ((ks & 3) << 5)) + (ks >> 2) * 4096 + m * 2048);
                        mma(acc[m][ks & 1], a[0], a[1], a[2], a[3], (ks & 1) ? q1[ks - 1] : q0[ks], (ks & 1) ? q1[ks] : q0[ks + 1]);
                    }
                __syncwarp();
                if (lane == 0) mbar_arrive(fullb + (it & 1) * 64 + (BAR_EMPTY - BAR_FULL) * 8);
#pragma unroll
                for (int m = 0; m < 2; m++) {
                    const float s = sel4(acc[m][0], t4) + sel4(acc[m][1], t4);
                    sts16(sp + m * 32, (uint16_t)pack2(rbf(s) * 0.08838834764831845f, 0.f));
                }
                pace(it * 8 + warp);
                __syncwarp();
            }
        }
        __syncwarp();
        if (warp == 7) TSL(6);
        const uint32_t pa = pw + (lane >> 4) * P_PITCH + (lane & 15) * 32;
        const uint32_t sa = sm + OFF_SM + (lane >> 4) * 64;
        const uint4 v0 = lds128(pa), v1 = lds128(pa + 16);
        const uint32_t sv[8] = {v0.x, v0.y, v0.z, v0.w, v1.x, v1.y, v1.z, v1.w};
        float e[16];
        float m = -INFINITY;
#pragma unroll
        for (int i = 0; i < 8; i++) {
            e[2 * i] = blo(sv[i]);
            e[2 * i + 1] = bhi(sv[i]);
            m = fmaxf(m, fmaxf(e[2 * i], e[2 * i + 1]));
        }
#pragma unroll
        for (int o = 8; o; o >>= 1) m = fmaxf(m, __shfl_xor_sync(0xffffffffu, m, o));
        float l = 0.f;
#pragma unroll
        for (int i = 0; i < 16; i++) {
            e[i] = ex2((e[i] - m) * LOG2E);
            l += e[i];
        }
#pragma unroll
        for (int o = 8; o; o >>= 1) l += __shfl_xor_sync(0xffffffffu, l, o);
        if ((lane & 15) == 0) sts64(sa + warp * 8, __float_as_uint(m), __float_as_uint(l));
        bar_sync(2, NCW * 32);
        const float2 v = lds64f(sa + (lane & 7) * 8);
        float M = v.x;
#pragma unroll
        for (int o = 4; o; o >>= 1) M = fmaxf(M, __shfl_xor_sync(0xffffffffu, M, o));
        float L = v.y * ex2((v.x - M) * LOG2E);
#pragma unroll
        for (int o = 4; o; o >>= 1) L += __shfl_xor_sync(0xffffffffu, L, o);
        const float sc = ex2((m - M) * LOG2E) * rcp(L);
        sts128(pa, pack2(e[0] * sc, e[1] * sc), pack2(e[2] * sc, e[3] * sc), pack2(e[4] * sc, e[5] * sc), pack2(e[6] * sc, e[7] * sc));
        sts128(pa + 16, pack2(e[8] * sc, e[9] * sc), pack2(e[10] * sc, e[11] * sc), pack2(e[12] * sc, e[13] * sc), pack2(e[14] * sc, e[15] * sc));
        __syncwarp();
    } else {
        if (tid == 256) {
            uint32_t* const ping = gs + dual(D_PING) + cta * 8;
            uint32_t best[2] = {~0u, ~0u}, v = 0;
#pragma unroll 1
            for (int r = 0; r < P.nping; r++) {
#pragma unroll
                for (int k = 0; k < 2; k++) {
                    const uint32_t t0 = clock32(v);
                    v = atomicExch(ping + k * 1024, t0);
                    best[k] = min(best[k], clock32(v) - t0);
                }
            }
            sts32(sm + OFF_WIN + 4, ((best[1] < best[0]) ^ __popc(D_PING & 0x16400) ^ (P.mode >> 4)) & 1);
        }
        __syncwarp();
        bar_sync(2, NCW * 32);
    }
    const int side = lds32(sm + OFF_WIN + 4);

    const bool reducer = cta < 72 && warp < 4;
    const bool act_writer = warp < 4 || (warp == 4 && sub < 4);
    const int rbat = 2 * t4 + (g & 1);
    const int off_o = dual(D_O + cta * 128) + (tid & 0x70) + (tid & 3) * 4 + ((tid >> 2) & 3);
    const int off_p = dual(D_P + (warp < 8 ? 8 * sub + warp : 64 + sub) * 1024) + grp * 64 + lane * 2;
    const int off_x = dual(D_X1 + cta * 32) + warp * 8 + lane;
    const int off_a = dual(D_ACT + (grp * 36 + (warp < 4 ? 4 * sub + warp : 32 + sub)) * 32) + lane;
    auto clear_slots = [&](uint32_t* page) {
        if (warp < 4) clear1d(page + off_o);
        clear2d(page + off_p);
        clear2d(page + off_p + 72 * 2048);
        if (act_writer) clear1d(page + off_a);
        if (reducer && lane < 8) clear1d(page + off_x);
    };
    uint32_t sh[8] = {}, op[8] = {}, wr[8] = {}, rx = 0, rg[2] = {};
    const uint32_t* const src_m = gs + G_M + (72 + warp * 8) * 32 + lane;
    const uint32_t* const src_g = gs + G_M + cta * 32 + rbat * 4 + warp;
    if (warp < 9) {
#pragma unroll
        for (int i = 0; i < 8; i++) {
            wr[i] = __ldg(reinterpret_cast<const uint32_t*>(P.wr) + warp * 32 + i * 4 + t4);
            sh[i] = ld1(src_m + i * 32);
            op[i] = ld1(src_m + (72 + i) * 32);
        }
        if (reducer) {
            rx = __ldg(reinterpret_cast<const uint32_t*>(P.x) + rbat * (DM / 2) + 4 * cta + warp);
            rg[0] = ld1(src_g), rg[1] = ld1(src_g + 216 * 32);
        }
        if (!(P.mode & 32)) clear_slots(g0 + (~epoch & 1) * G_PAGE);
        if (warp == 8) {
            if (P.tclr) mbar_wait(bars + (BAR_SYNC + 1) * 8, 0);
            clear_slots(gs);
        }
    }

    if (warp < 8) {
        float acc[8][4] = {};
        uint32_t pp = pw + (lane & 1) * P_PITCH + (lane >> 3) * 16;
#pragma unroll 1
        for (int it = 0; it < 8; it++, pp += 64) {
            const uint32_t ab = tile + (it & 1) * (8 * TILE_BYTES) + ((lane & 7) + (lane >> 4) * 8) * 128 + ((((lane >> 3) & 1) ^ (lane & 7)) << 4);
            uint32_t pb[4];
            ldsm4(pb, pp);
            if (it == P.tclr) clear_slots(gs);
            mbar_wait(fullb + (it & 1) * 64, (it >> 1) & 1);
#pragma unroll
            for (int ks = 0; ks < 2; ks++)
#pragma unroll
                for (int m = 0; m < 8; m++) {
                    uint32_t a[4];
                    ldsm4t(a, (ab ^ ((m & 3) << 5)) + (m >> 2) * 4096 + ks * 2048);
                    mma(acc[m], a[0], a[1], a[2], a[3], pb[2 * ks], pb[2 * ks + 1]);
                }
            __syncwarp();
            if (lane == 0) mbar_arrive(fullb + (it & 1) * 64 + (BAR_EMPTY - BAR_FULL) * 8);
            if (it < 7) pace(NT + it * 8 + warp);
            __syncwarp();
        }
        if (warp == 7) TSL(7);
        const uint32_t ra = sm + OFF_ORED + warp * 1088 + (t4 & 1) * 576 + ((t4 >> 1) * 8 + g) * 4;
#pragma unroll
        for (int m = 0; m < 8; m++) sts32(ra + m * 64, __float_as_uint(sel4(acc[m], t4)));
    }
    bar_sync(5, NCW * 32);
    if (warp < 4) {
        float s[2][2] = {};
#pragma unroll
        for (int w = 0; w < 8; w++) {
            const float2 v = lds64f(sm + OFF_ORED + w * 1088 + (tid >> 6) * 64 + tid * 8);
            s[w & 1][0] += v.x;
            s[w & 1][1] += v.y;
        }
        put1d(gs + off_o, pack2(s[0][0] + s[1][0], s[0][1] + s[1][1]));
        if (warp == 0) TSL(8);
    }
    if (warp == 9) {
        const uint32_t* pp = gs + near(D_P + (cta < 72 ? cta : cta - 72) * 1024, side) + (lane & 15) * 64;
        if (cta < 72) {
            probe(pp, P.slack);
            bar_arrive(6, 160);
        }
        probe(pp, P.slack2);
        TSL(27);
        bar_arrive(7, NCW * 32);
        return;
    }

    project<0>(sm, gs + near(D_O + grp * 1024, side) + g * 128 + warp * 16 + t4 * 4, gs + off_p, warp, lane);
    if (warp == 0) TSL(9);
    reget1<8>(src_m, 32, sh);
    reget1<8>(src_m + 72 * 32, 32, op);
    if (reducer) reget1<2>(src_g, 216 * 32, rg);
    if (P.mode & 64) clear_slots(g0 + (~epoch & 1) * G_PAGE);
    const uint32_t gbar = bars + (BAR_GU + warp) * 8;
    const int rr = (lane >> 4) * 8 + (lane & 7), pl = ((lane >> 3) & 1) ^ P.zg;
    const uint32_t ab = sm + OFF_GU + warp * 8192 + pl * 4096 + rr * 64 + ((lane & 6) << 3);
    const uint32_t ax = sm + OFF_GX + (warp / 3 + pl) * 3072 + (warp * 64 + rr) * 16;
    uint32_t a[20][4] = {};
    auto load_gu = [&]() {
#pragma unroll
        for (int i = 0; i < 20; i++) ldsm4t(a[i], i % 5 < 4 ? (ab ^ ((i % 5) << 4)) + (i / 5) * 1024 : ax + (i / 5) * 256);
    };
    const uint32_t* const src_p = gs + (lane >> 3) * 256 + 16 * warp + (lane & 7) * 2;
    if (reducer) {
        bar_sync(6, 160);
        rx = badd2(rx, bmul2(rg[0], reduce16(src_p + near(D_P + cta * 1024, side), lane)));
        if (lane < 8) put1d(gs + off_x, rx);
        if (warp == 0) TSL(10);
    }
    bar_sync(7, NCW * 32);

    uint32_t h[8];
    const uint32_t* const src_x = gs + near(D_X1 + warp * 256, side) + t4 * 8 + (g & 1) * 4 + (g >> 1);
#pragma unroll
    for (int i = 0; i < 8; i++) h[i] = ld1(src_x + i * 32);
    const bool gpre = __all_sync(0xffffffffu, mbar_test(gbar, 0));
    if (gpre) load_gu();
    reget1<8>(src_x, 32, h);
    if (warp == 0) TSL(11);
    ln_partial(h, sm + OFF_ST + g * 80 + warp * 8, t4 == 0);
    bar_sync(3, 288);
    {
        uint32_t mean2;
        float inv;
        ln_combine(sm + OFF_ST + g * 80, mean2, inv);
#pragma unroll
        for (int i = 0; i < 8; i++) h[i] = modulate2(h[i], mean2, inv, sh[i], op[i]);
    }
    if (warp == 0) TSL(12);
    if (!gpre) {
        mbar_wait_lanes(gbar);
        load_gu();
    }
    if (warp == 8) TSL(17);
    {
        float acc[5][4] = {};
#pragma unroll
        for (int i = 0; i < 20; i++) mma(acc[i % 5], a[i][0], a[i][1], a[i][2], a[i][3], h[2 * (i / 5)], h[2 * (i / 5) + 1]);
#pragma unroll
        for (int m = 0; m < 5; m++) sts128f(sm + OFF_RED + m * 4608 + tid * 16, acc[m]);
    }
    bar_sync(3, 288);
    if (warp < 5) {
        float c[4] = {};
        sum_frags<9>(c, sm + OFF_RED + warp * 4608 + lane * 16, 512);
        const uint32_t w = movm(bmul2(silu2(pack2(c[0], c[1])), pack2(c[2], c[3])));
        if (act_writer) put1d(gs + off_a, w);
        if (warp == 1) TSL(13);
    }
    if (cta < 72) {
        float r = 0.f;
#pragma unroll
        for (int i = 0; i < 8; i++) {
            r = fmaf(blo(h[i]), blo(wr[i]), fmaf(bhi(h[i]), bhi(wr[i]), r));
            if (warp * 8 + i == cta) sts32(sm + OFF_HU + lane * 4, h[i]);
        }
        r = quad_sum(r);
        if (t4 == 0) sts32(sm + OFF_RT + g * 48 + warp * 4, __float_as_uint(r));
    }

    project<1>(sm, gs + near(D_ACT + (grp * 36 + 4 * warp) * 32, side) + lane, gs + off_p + 72 * 2048, warp, lane);
    if (warp == 0) TSL(14);
    if (reducer) {
        const uint4 r0 = lds128(sm + OFF_RT + rbat * 48), r1 = lds128(sm + OFF_RT + rbat * 48 + 16);
        float r = __uint_as_float(lds32(sm + OFF_RT + rbat * 48 + 32));
        r += ((__uint_as_float(r0.x) + __uint_as_float(r0.y)) + (__uint_as_float(r0.z) + __uint_as_float(r0.w))) +
             ((__uint_as_float(r1.x) + __uint_as_float(r1.y)) + (__uint_as_float(r1.z) + __uint_as_float(r1.w)));
        r = sigmoid_f(rbf(r));
        const uint32_t rh = lds32(sm + OFF_HU + (rbat * 4 + warp) * 4);
        const uint32_t y = badd2(rh, bmul2(reduce16(src_p + near(D_P + (72 + cta) * 1024, side), lane), pack2(r, r)));
        if (lane < 8) reinterpret_cast<uint32_t*>(P.out)[rbat * (DM / 2) + 4 * cta + warp] = badd2(rx, bmul2(rg[1], y));
        if (cta == 0 && tid == 0) g_epoch = epoch + 1;
        if (warp == 0) TSL(15);
    }
    if (P.mode & 128) clear_slots(g0 + (~epoch & 1) * G_PAGE);
}

typedef CUresult (*EncodeFn)(CUtensorMap*, CUtensorMapDataType, cuuint32_t, void*, const cuuint64_t*, const cuuint64_t*,
                             const cuuint32_t*, const cuuint32_t*, CUtensorMapInterleave, CUtensorMapSwizzle,
                             CUtensorMapL2promotion, CUtensorMapFloatOOBfill);

#define PROMO_W CU_TENSOR_MAP_L2_PROMOTION_L2_128B
#define PROMO_KV CU_TENSOR_MAP_L2_PROMOTION_L2_256B
constexpr
int dbg_wfront = W_FRONT, dbg_wkv = W_KV, dbg_wwo = W_WO, dbg_wgu = W_GU, dbg_wwd = W_WD, dbg_promo_w = PROMO_W,
    dbg_promo_kv = PROMO_KV, dbg_mode = 1024, dbg_slack = 4, dbg_gain = 4, dbg_wmin = -2, dbg_wmax = 3, dbg_tx = 12, dbg_two = 3, dbg_nping = 12, dbg_slack2 = 0, dbg_tclr = 5, dbg_npf = 1, dbg_ntp = 5, dbg_gain2 = 4;

void make_map(EncodeFn enc, CUtensorMap* m, void* p, int cols, int rows, int pitch, int bc, int br, int bp, int planes, size_t pstride,
              CUtensorMapSwizzle sw, int promo) {
    cuuint64_t dims[3] = {(cuuint64_t)cols, (cuuint64_t)rows, (cuuint64_t)planes};
    cuuint64_t strides[2] = {(cuuint64_t)pitch * 2, (cuuint64_t)pstride};
    cuuint32_t box[3] = {(cuuint32_t)bc, (cuuint32_t)br, (cuuint32_t)bp};
    cuuint32_t es[3] = {1, 1, 1};
    enc(m, CU_TENSOR_MAP_DATA_TYPE_BFLOAT16, 3, p, dims, strides, box, es, CU_TENSOR_MAP_INTERLEAVE_NONE, sw,
        (CUtensorMapL2promotion)promo, CU_TENSOR_MAP_FLOAT_OOB_FILL_NONE);
}

}

extern "C" void kernel_launch(void* const* d_in, const int* in_sizes, int n_in, void* d_out, int out_size) {
    static EncodeFn enc = nullptr;
    static uint32_t* scratch = nullptr;
    if (!enc) {
        void* fn = nullptr;
        cudaDriverEntryPointQueryResult st;
        cudaGetDriverEntryPoint("cuTensorMapEncodeTiled", &fn, cudaEnableDefault, &st);
        enc = (EncodeFn)fn;
        cudaGetSymbolAddress(&fn, g_scratch);
        scratch = (uint32_t*)(((uintptr_t)fn + 4 * G_PAGE - 1) & ~(uintptr_t)(4 * G_PAGE - 1));
        cudaFuncSetAttribute(fused_kernel, cudaFuncAttributeMaxDynamicSharedMemorySize, SMEM_BYTES);
    }
    Params P;
    const CUtensorMapSwizzle none = CU_TENSOR_MAP_SWIZZLE_NONE;
    make_map(enc, &P.m[M_K], d_in[1], 64, NB * HKV * SK, DH, 64, 32, 2, 2, 128, CU_TENSOR_MAP_SWIZZLE_128B, dbg_promo_kv);
    make_map(enc, &P.m[M_V], d_in[2], 64, NB * HKV * SK, DH, 64, 32, 2, 2, 128, CU_TENSOR_MAP_SWIZZLE_128B, dbg_promo_kv);
    make_map(enc, &P.m[M_WQ], d_in[3], HQ * DH, DM, HQ * DH, 32, 192, 1, 1, 16, CU_TENSOR_MAP_SWIZZLE_64B, dbg_promo_w);
    make_map(enc, &P.m[M_WM], d_in[11], 6 * DM, DM, 6 * DM, 32, 192, 1, 1, 16, CU_TENSOR_MAP_SWIZZLE_64B, dbg_promo_w);
    make_map(enc, &P.m[M_WA], d_in[11], DM, DM, 6 * DM, 16, 192, 2, 2, DM * 2, CU_TENSOR_MAP_SWIZZLE_32B, dbg_promo_w);
    char *wg = (char*)d_in[7], *wu = (char*)d_in[8], *wo = (char*)d_in[4], *wd = (char*)d_in[9];
    P.zg = wg > wu;
    P.zo = wo > wd;
    const size_t sg = P.zg ? wg - wu : wu - wg, so = P.zo ? wo - wd : wd - wo;
    make_map(enc, &P.m[M_GU], P.zg ? wu : wg, FF, DM, FF, 32, 64, 2, 2, sg, CU_TENSOR_MAP_SWIZZLE_64B, dbg_promo_w);
    make_map(enc, &P.m[M_GX], P.zg ? wu : wg, FF, DM, FF, 8, 192, 2, 2, sg, none, dbg_promo_w);
    make_map(enc, &P.m[M_OD], P.zo ? wd : wo, DM, FF, DM, 64, 64, 1, 2, so, CU_TENSOR_MAP_SWIZZLE_128B, dbg_promo_w);
    make_map(enc, &P.m[M_OX], P.zo ? wd : wo, DM, FF, DM, 8, 144, 1, 2, so, none, dbg_promo_w);
    P.x = (const __nv_bfloat16*)d_in[0];
    P.wr = (const __nv_bfloat16*)d_in[6];
    P.c = (const __nv_bfloat16*)d_in[10];
    P.out = (__nv_bfloat16*)d_out;
    P.scratch = scratch;
    P.wfront = dbg_wfront;
    P.wkv = dbg_wkv;
    P.wgu = dbg_wgu;
    P.wwd = dbg_wwd;
    P.mode = dbg_mode;
    P.wwo = dbg_wwo;
    P.slack = dbg_slack;
    P.gain = dbg_gain;
    P.wmin = dbg_wmin;
    P.wmax = dbg_wmax;
    P.tx = dbg_tx;
    P.two = dbg_two;
    P.nping = dbg_nping;
    P.slack2 = dbg_slack2;
    P.tclr = dbg_tclr;
    P.npf = dbg_npf;
    P.ntp = dbg_ntp;
    P.gain2 = dbg_gain2;
    P.k = (const __nv_bfloat16*)d_in[1];
    P.v = (const __nv_bfloat16*)d_in[2];
    P.wm = (const __nv_bfloat16*)d_in[11];
    P.wq = (const __nv_bfloat16*)d_in[3];
    fused_kernel<<<NCTA, NTHREADS, SMEM_BYTES>>>(P);
}
```

```cpp
#include <cuda_runtime.h>
#include <cuda_bf16.h>
#include <cuda.h>
#include <stdint.h>

typedef unsigned long long u64;

#define W_KV 20
#define W_WO 20
#define W_GU 16
#define W_WD 16
#define W_MIN -8
#define W_MAX 12
#define GAIN_KV 3
#define GAIN_TAIL 4
#define NK0 1
#define T_STRIP 12
#define T_CLEAR 112
#define NPING0 3
#define NPING1 10
#define PROMO_W CU_TENSOR_MAP_L2_PROMOTION_L2_128B
#define PROMO_KV CU_TENSOR_MAP_L2_PROMOTION_L2_256B

namespace {

constexpr int NB = 8, DM = 576, HQ = 32, HKV = 16, SK = 8192, WIN = 2048, DH = 128, FF = 4608;
constexpr int NCTA = 128;
constexpr int NCW = 10;
constexpr int NTHREADS = (NCW + 2) * 32;
constexpr int TILE_BYTES = 8192, NSLOT = 16, NT = 64;
constexpr int SPIN_LIMIT = 1 << 22;

constexpr int OFF_RING = 0;
constexpr int OFF_WM = 121856;
constexpr int OFF_WQ = OFF_WM + 36864;
constexpr int OFF_GU = 0;
constexpr int OFF_WD = 73728;
constexpr int OFF_OX = 131072;
constexpr int OFF_DX = OFF_OX + 4096;
constexpr int OFF_GX = OFF_DX + 4608;
constexpr int OFF_WO = OFF_WQ;
constexpr int OFF_P = OFF_WQ + 36864;
constexpr int P_PITCH = 528;
constexpr int OFF_RED = OFF_P + 16 * P_PITCH;
constexpr int OFF_ORED = OFF_RED + 5 * 4608 - 8704;
constexpr int OFF_ST = OFF_RED + 5 * 4608;
constexpr int OFF_SM = OFF_ST + 640;
constexpr int OFF_RT = OFF_SM + 128;
constexpr int OFF_HU = OFF_RT + 384;
constexpr int OFF_QS = OFF_HU + 128;
constexpr int OFF_WIN = OFF_QS + 512;
constexpr int OFF_BAR = OFF_WIN + 16;
constexpr int BAR_FULL = 6, BAR_WO = 22, BAR_GU = 26, BAR_WD = 35, BAR_EMPTY = 40, BAR_SYNC = 56, BAR_WMF = 59, BAR_X = 60, NBAR = 70;
constexpr int SMEM_BYTES = OFF_BAR + NBAR * 8;

constexpr int D_X1 = 0;
constexpr int D_O = 3072;
constexpr int D_ACT = D_O + 512 * 32;
constexpr int D_H = D_ACT + 576 * 32;
constexpr int D_Q = D_H + 3072;
constexpr int G_M = 2 * (D_Q + NB * HQ * 64);
constexpr int G_CNT = G_M + 288 * 32;
constexpr int G_SET = 1 << 18;
__device__ __forceinline__ int d_part(int unit) { return (64 + unit + (unit & 64)) * 1024; }
constexpr int D_PING = 200 * 1024;
constexpr int G_EPOCH = 201 * 2048;
static_assert(G_CNT < 64 * 2048, "scratch layout");
__device__ uint32_t g_scratch[4 * G_SET];
__device__ __forceinline__ int dual(int w) { return w + (w & ~1023); }
__device__ __forceinline__ int near(int w, int side) { return dual(w) + (((__popc(w & 0x16400) ^ side) & 1) << 10); }

#define TI(i)
#define TS(i)
#define TSL(i)

enum { M_K, M_V, M_GU, M_GX, M_OD, M_OX, M_WQ, M_WM, M_WA, NMAP };
struct Params {
    CUtensorMap m[NMAP];
    const __nv_bfloat16 *x, *c, *wr;
    __nv_bfloat16* out;
    uint32_t* scratch;
    int zg, zo;
};

__device__ __forceinline__ void mbar_init(uint32_t bar, int cnt) {
    asm volatile("mbarrier.init.shared::cta.b64 [%0], %1;" ::"r"(bar), "r"(cnt));
}
__device__ __forceinline__ void mbar_expect(uint32_t bar, uint32_t bytes) {
    asm volatile("mbarrier.arrive.expect_tx.shared::cta.b64 _, [%0], %1;" ::"r"(bar), "r"(bytes) : "memory");
}
__device__ __forceinline__ void mbar_arrive(uint32_t bar) {
    asm volatile("mbarrier.arrive.shared::cta.b64 _, [%0];" ::"r"(bar) : "memory");
}
__device__ __forceinline__ void mbar_wait(uint32_t bar, uint32_t parity) {
    asm volatile("{\n.reg .pred p;\n.reg .u32 c;\n"
                 "mbarrier.try_wait.parity.shared::cta.b64 p, [%0], %1;\n@p bra DONE;\nmov.u32 c, %2;\n"
                 "AGAIN:\nmbarrier.try_wait.parity.shared::cta.b64 p, [%0], %1;\nsub.u32 c, c, 1;\n"
                 "setp.eq.or.u32 p, c, 0, p;\n@!p bra AGAIN;\nDONE:\n}"
                 ::"r"(bar), "r"(parity), "n"(SPIN_LIMIT) : "memory");
}
__device__ __forceinline__ bool mbar_test(uint32_t bar, uint32_t parity) {
    uint32_t ok;
    asm volatile("{\n.reg .pred p;\nmbarrier.test_wait.parity.shared::cta.b64 p, [%1], %2;\nselp.u32 %0, 1, 0, p;\n}"
                 : "=r"(ok) : "r"(bar), "r"(parity) : "memory");
    return ok;
}
__device__ __forceinline__ void mbar_wait_lanes(uint32_t bar) {
    mbar_wait(bar, 0);
    __syncwarp();
}
__device__ __forceinline__ void tma3d_hint(uint32_t dst, const CUtensorMap* m, int x, int y, int z, uint32_t bar, u64 pol) {
    asm volatile("cp.async.bulk.tensor.3d.shared::cluster.global.mbarrier::complete_tx::bytes.L2::cache_hint"
                 " [%0], [%1, {%2, %3, %4}], [%5], %6;"
                 ::"r"(dst), "l"(m), "r"(x), "r"(y), "r"(z), "r"(bar), "l"(pol) : "memory");
}
__device__ __forceinline__ void tma3d(uint32_t dst, const CUtensorMap* m, int x, int y, int z, uint32_t bar) {
    asm volatile("cp.async.bulk.tensor.3d.shared::cluster.global.mbarrier::complete_tx::bytes [%0], [%1, {%2, %3, %4}], [%5];"
                 ::"r"(dst), "l"(m), "r"(x), "r"(y), "r"(z), "r"(bar) : "memory");
}
__device__ __forceinline__ void bar_sync(int id, int n) { asm volatile("bar.sync %0, %1;" ::"r"(id), "r"(n) : "memory"); }
__device__ __forceinline__ void bar_arrive(int id, int n) { asm volatile("bar.arrive %0, %1;" ::"r"(id), "r"(n) : "memory"); }
__device__ __forceinline__ void ldsm4(uint32_t (&r)[4], uint32_t a) {
    asm volatile("ldmatrix.sync.aligned.m8n8.x4.shared.b16 {%0,%1,%2,%3}, [%4];"
                 : "=r"(r[0]), "=r"(r[1]), "=r"(r[2]), "=r"(r[3]) : "r"(a) : "memory");
}
__device__ __forceinline__ void ldsm4t(uint32_t (&r)[4], uint32_t a) {
    asm volatile("ldmatrix.sync.aligned.m8n8.x4.trans.shared.b16 {%0,%1,%2,%3}, [%4];"
                 : "=r"(r[0]), "=r"(r[1]), "=r"(r[2]), "=r"(r[3]) : "r"(a) : "memory");
}
__device__ __forceinline__ void mma(float (&c)[4], uint32_t a0, uint32_t a1, uint32_t a2, uint32_t a3, uint32_t b0, uint32_t b1) {
    asm volatile("mma.sync.aligned.m16n8k16.row.col.f32.bf16.bf16.f32 {%0,%1,%2,%3}, {%4,%5,%6,%7}, {%8,%9}, {%0,%1,%2,%3};"
                 : "+f"(c[0]), "+f"(c[1]), "+f"(c[2]), "+f"(c[3])
                 : "r"(a0), "r"(a1), "r"(a2), "r"(a3), "r"(b0), "r"(b1));
}
__device__ __forceinline__ uint32_t movm(uint32_t a) {
    uint32_t d;
    asm volatile("movmatrix.sync.aligned.m8n8.trans.b16 %0, %1;" : "=r"(d) : "r"(a));
    return d;
}
__device__ __forceinline__ uint32_t lds32(uint32_t a) { uint32_t v; asm volatile("ld.shared.b32 %0, [%1];" : "=r"(v) : "r"(a) : "memory"); return v; }
__device__ __forceinline__ float2 lds64f(uint32_t a) { float2 v; asm volatile("ld.shared.v2.f32 {%0,%1}, [%2];" : "=f"(v.x), "=f"(v.y) : "r"(a) : "memory"); return v; }
__device__ __forceinline__ uint4 lds128(uint32_t a) { uint4 v; asm volatile("ld.shared.v4.b32 {%0,%1,%2,%3}, [%4];" : "=r"(v.x), "=r"(v.y), "=r"(v.z), "=r"(v.w) : "r"(a) : "memory"); return v; }
__device__ __forceinline__ void sts32(uint32_t a, uint32_t v) { asm volatile("st.shared.b32 [%0], %1;" ::"r"(a), "r"(v) : "memory"); }
__device__ __forceinline__ void sts16(uint32_t a, uint16_t v) { asm volatile("st.shared.b16 [%0], %1;" ::"r"(a), "h"(v) : "memory"); }
__device__ __forceinline__ void sts64(uint32_t a, uint32_t x, uint32_t y) { asm volatile("st.shared.v2.b32 [%0], {%1,%2};" ::"r"(a), "r"(x), "r"(y) : "memory"); }
__device__ __forceinline__ void sts128(uint32_t a, uint32_t x, uint32_t y, uint32_t z, uint32_t w) {
    asm volatile("st.shared.v4.b32 [%0], {%1,%2,%3,%4};" ::"r"(a), "r"(x), "r"(y), "r"(z), "r"(w) : "memory");
}
__device__ __forceinline__ void sts128f(uint32_t a, const float (&c)[4]) {
    sts128(a, __float_as_uint(c[0]), __float_as_uint(c[1]), __float_as_uint(c[2]), __float_as_uint(c[3]));
}

__device__ __forceinline__ float sel4(const float (&c)[4], int t) { return (t & 2) ? ((t & 1) ? c[3] : c[2]) : ((t & 1) ? c[1] : c[0]); }

__device__ __forceinline__ uint32_t clock32(uint32_t dep) {
    uint32_t t;
    asm volatile("{\n.reg .pred p;\nsetp.eq.u32 p, %1, 0x9e3779b9;\n@p nanosleep.u32 1;\nmov.u32 %0, %clock;\n}" : "=r"(t) : "r"(dep) : "memory");
    return t;
}

__device__ __forceinline__ uint32_t nz(uint32_t v) { return v ? v : 0x80000000u; }
__device__ __forceinline__ void st1(uint32_t* p, uint32_t a) { asm volatile("st.relaxed.gpu.global.b32 [%0], %1;" ::"l"(p), "r"(a) : "memory"); }
__device__ __forceinline__ void st2(uint32_t* p, uint32_t a, uint32_t b) {
    asm volatile("st.relaxed.gpu.global.v2.b32 [%0], {%1,%2};" ::"l"(p), "r"(a), "r"(b) : "memory");
}
__device__ __forceinline__ void zero4(uint32_t* p) { asm volatile("st.relaxed.gpu.global.v4.b32 [%0], {%1,%1,%1,%1};" ::"l"(p), "r"(0) : "memory"); }
__device__ __forceinline__ void put1d(uint32_t* p, uint32_t a) { a = nz(a), st1(p, a), st1(p + 1024, a); }
__device__ __forceinline__ void put2d(uint32_t* p, uint32_t a, uint32_t b) { a = nz(a), b = nz(b), st2(p, a, b), st2(p + 1024, a, b); }
__device__ __forceinline__ uint32_t ld1(const uint32_t* p) {
    uint32_t v;
    asm volatile("ld.relaxed.gpu.global.b32 %0, [%1];" : "=r"(v) : "l"(p) : "memory");
    return v;
}
template <int N, int V>
__device__ __forceinline__ void fetch(const uint32_t* p, int stride, uint32_t (&a)[N * V]) {
#pragma unroll
    for (int i = 0; i < N; i++) {
        if (V == 1)
            asm volatile("{\n.reg .pred p;\nsetp.eq.u32 p, %0, 0;\n@p ld.relaxed.gpu.global.b32 %0, [%1];\n}"
                         : "+r"(a[i]) : "l"(p + i * stride) : "memory");
        if (V == 4)
            asm volatile("{\n.reg .pred p;\nsetp.eq.u32 p, %4, 0;\n@p ld.relaxed.gpu.global.v4.b32 {%0,%1,%2,%3}, [%5];\n}"
                         : "+r"(a[V * i]), "+r"(a[V * i + V / 4]), "+r"(a[V * i + V / 2]), "+r"(a[V * i + V - 1])
                         : "r"(min(min(a[V * i], a[V * i + V / 4]), min(a[V * i + V / 2], a[V * i + V - 1]))), "l"(p + i * stride) : "memory");
    }
}
template <int N>
__device__ __forceinline__ bool missing(const uint32_t (&a)[N]) {
    uint32_t lo = a[0];
#pragma unroll
    for (int i = 1; i < N; i++) lo = min(lo, a[i]);
    return __any_sync(0xffffffffu, lo == 0);
}
template <int N, int V>
__device__ __forceinline__ void get(const uint32_t* p, int stride, uint32_t (&a)[N * V]) {
    int it = 0;
    do fetch<N, V>(p, stride, a);
    while (missing(a) && ++it < SPIN_LIMIT);
}
__device__ __forceinline__ void cp16(uint32_t dst, const void* src) {
    asm volatile("cp.async.cg.shared.global [%0], [%1], 16;" ::"r"(dst), "l"(src) : "memory");
}

__device__ __forceinline__ uint32_t pack2(float lo, float hi) {
    uint32_t r;
    asm("cvt.rn.bf16x2.f32 %0, %1, %2;" : "=r"(r) : "f"(hi), "f"(lo));
    return r;
}
__device__ __forceinline__ float rbf(float x) { return __uint_as_float(pack2(0.f, x)); }
__device__ __forceinline__ float blo(uint32_t v) { return __uint_as_float(v << 16); }
__device__ __forceinline__ float bhi(uint32_t v) { return __uint_as_float(v & 0xffff0000u); }
__device__ __forceinline__ uint32_t badd2(uint32_t a, uint32_t b) { uint32_t r; asm("add.rn.bf16x2 %0, %1, %2;" : "=r"(r) : "r"(a), "r"(b)); return r; }
__device__ __forceinline__ uint32_t bsub2(uint32_t a, uint32_t b) { uint32_t r; asm("sub.rn.bf16x2 %0, %1, %2;" : "=r"(r) : "r"(a), "r"(b)); return r; }
__device__ __forceinline__ uint32_t bmul2(uint32_t a, uint32_t b) { uint32_t r; asm("mul.rn.bf16x2 %0, %1, %2;" : "=r"(r) : "r"(a), "r"(b)); return r; }
__device__ __forceinline__ float ex2(float x) { float r; asm("ex2.approx.ftz.f32 %0, %1;" : "=f"(r) : "f"(x)); return r; }
__device__ __forceinline__ float rcp(float x) { float r; asm("rcp.approx.ftz.f32 %0, %1;" : "=f"(r) : "f"(x)); return r; }
__device__ __forceinline__ float sqrt_f(float x) { float r; asm("sqrt.approx.ftz.f32 %0, %1;" : "=f"(r) : "f"(x)); return r; }
constexpr float LOG2E = 1.4426950408889634f;
constexpr uint32_t ONE2 = 0x3f803f80u;
__device__ __forceinline__ float sigmoid_f(float x) { return rcp(1.0f + ex2(-LOG2E * x)); }
__device__ __forceinline__ uint32_t silu2(uint32_t v) {
    const float a = blo(v), b = bhi(v);
    return pack2(a * sigmoid_f(a), b * sigmoid_f(b));
}
__device__ __forceinline__ float quad_sum(float v) {
    v += __shfl_xor_sync(0xffffffffu, v, 1);
    return v + __shfl_xor_sync(0xffffffffu, v, 2);
}
__device__ __forceinline__ void ln_partial(const uint32_t (&v)[8], uint32_t dst, bool writer) {
    float s0 = 0.f, s1 = 0.f;
#pragma unroll
    for (int i = 0; i < 8; i++) {
        s0 += blo(v[i]);
        s1 += bhi(v[i]);
    }
    const float mean = quad_sum(s0 + s1) * (1.0f / 64);
    s0 = s1 = 0.f;
#pragma unroll
    for (int i = 0; i < 8; i++) {
        const float a = blo(v[i]) - mean, b = bhi(v[i]) - mean;
        s0 = fmaf(a, a, s0);
        s1 = fmaf(b, b, s1);
    }
    s0 = quad_sum(s0 + s1);
    if (writer) sts64(dst, __float_as_uint(mean), __float_as_uint(s0));
}
__device__ __forceinline__ void ln_combine(uint32_t src, uint32_t& mean2, float& inv) {
    float m[10], q0 = 0.f, q1 = 0.f, s = 0.f;
#pragma unroll
    for (int i = 0; i < 5; i++) {
        const uint4 v = lds128(src + i * 16);
        m[2 * i] = __uint_as_float(v.x);
        m[2 * i + 1] = __uint_as_float(v.z);
        q0 += __uint_as_float(v.y);
        if (i < 4) q1 += __uint_as_float(v.w);
    }
    const float mean = (((m[0] + m[1]) + (m[2] + m[3])) + ((m[4] + m[5]) + (m[6] + m[7])) + m[8]) * (1.0f / 9);
#pragma unroll
    for (int i = 0; i < 9; i++) s = fmaf(m[i] - mean, m[i] - mean, s);
    const float var = fmaf(s, 64.f, q0 + q1) * (1.0f / DM);
    mean2 = pack2(mean, mean);
    inv = rcp(rbf(sqrt_f(rbf(rbf(var) + 1e-5f))));
}
__device__ __forceinline__ uint32_t modulate2(uint32_t x, uint32_t mean2, float inv, uint32_t shift, uint32_t onep) {
    const uint32_t d = bsub2(x, mean2);
    return badd2(bmul2(pack2(blo(d) * inv, bhi(d) * inv), onep), shift);
}
template <int N>
__device__ __forceinline__ void sum_frags(float (&c)[4], uint32_t addr, int stride) {
#pragma unroll
    for (int w = 0; w < N; w++) {
        const uint4 v = lds128(addr + w * stride);
        c[0] += __uint_as_float(v.x); c[1] += __uint_as_float(v.y);
        c[2] += __uint_as_float(v.z); c[3] += __uint_as_float(v.w);
    }
}

template <int ST>
__device__ __forceinline__ void project(uint32_t sm, const uint32_t* src, uint32_t* dst, int warp, int lane) {
    constexpr int NW = ST ? 9 : 8;
    const uint32_t red = sm + (ST ? OFF_WO : OFF_P) + lane * 8;
    if (warp < NW) {
        const uint32_t wbar = sm + OFF_BAR + ((ST ? BAR_WD : BAR_WO) + (warp >> 1)) * 8;
        const int r = warp * 32 + (lane >> 4) * 8 + (lane & 7);
        const uint32_t ab = sm + (ST ? OFF_WD : OFF_WO) + r * 128 + ((((lane >> 3) & 1) ^ (lane & 7)) << 4);
        const uint32_t ax = sm + (ST ? OFF_DX : OFF_OX) + r * 16;
        uint32_t a[10][4] = {}, b[4] = {};
        bool have_w = false;
        int it = 0;
        do {
            if (ST) fetch<4, 1>(src, 32, b);
            else fetch<1, 4>(src, 0, b);
            if (!have_w && __all_sync(0xffffffffu, mbar_test(wbar, 0))) {
                have_w = true;
#pragma unroll
                for (int i = 0; i < 10; i++) ldsm4t(a[i], i % 5 < 4 ? (ab ^ ((i % 5) << 5)) + (i / 5) * 2048 : ax + (i / 5) * 256);
            }
        } while ((missing(b) || !have_w) && ++it < SPIN_LIMIT);
        if (warp == 0) TSL(ST ? 24 : 21);
        float acc[5][4] = {};
#pragma unroll
        for (int i = 0; i < 10; i++) mma(acc[i % 5], a[i][0], a[i][1], a[i][2], a[i][3], b[2 * (i / 5)], b[2 * (i / 5) + 1]);
#pragma unroll
        for (int u = 0; u < 9; u++)
            sts64(red + u * 2304 + warp * 256, __float_as_uint(acc[u >> 1][2 * (u & 1)]), __float_as_uint(acc[u >> 1][2 * (u & 1) + 1]));
    }
    bar_sync(3, 288);
    float s[2][2] = {};
#pragma unroll
    for (int w = 0; w < NW; w++) {
        const float2 v = lds64f(red + warp * 2304 + w * 256);
        s[w & 1][0] += v.x;
        s[w & 1][1] += v.y;
    }
    const uint32_t p0 = (__float_as_uint(s[0][0] + s[1][0]) | 1) ^ ST, p1 = (__float_as_uint(s[0][1] + s[1][1]) | 1) ^ ST;
    st2(dst, p0, p1), st2(dst + 1024, p0, p1);
}

template <int ST>
__device__ __forceinline__ uint32_t reduce16(const uint32_t* src, int lane) {
    uint32_t a[8], bad[4] = {1, 1, 1, 1};
    int it = 0;
#pragma unroll
    for (int i = 0; i < 8; i++) a[i] = 0;
    do {
#pragma unroll
        for (int i = 0; i < 4; i++)
            asm volatile("{\n.reg .pred p;\nsetp.ne.u32 p, %2, 0;\n@p ld.relaxed.gpu.global.v2.b32 {%0,%1}, [%3];\n}"
                         : "+r"(a[2 * i]), "+r"(a[2 * i + 1]) : "r"(bad[i]), "l"(src + i * 64) : "memory");
#pragma unroll
        for (int i = 0; i < 4; i++) bad[i] = (ST ? a[2 * i] | a[2 * i + 1] : ~(a[2 * i] & a[2 * i + 1])) & 1;
    } while (__any_sync(0xffffffffu, bad[0] | bad[1] | bad[2] | bad[3]) && ++it < SPIN_LIMIT);
    float s0 = (__uint_as_float(a[0]) + __uint_as_float(a[2])) + (__uint_as_float(a[4]) + __uint_as_float(a[6]));
    float s1 = (__uint_as_float(a[1]) + __uint_as_float(a[3])) + (__uint_as_float(a[5]) + __uint_as_float(a[7]));
#pragma unroll
    for (int o = 8; o < 32; o <<= 1) {
        s0 += __shfl_xor_sync(0xffffffffu, s0, o);
        s1 += __shfl_xor_sync(0xffffffffu, s1, o);
    }
    const uint32_t y = pack2(s0, s1);
    return __byte_perm(y, __shfl_xor_sync(0xffffffffu, y, 4), (lane & 4) ? 0x3276 : 0x5410);
}

__global__ void __launch_bounds__(NTHREADS, 1) fused_kernel(const __grid_constant__ Params P) {
    extern __shared__ __align__(1024) char smem_raw[];
    const uint32_t sm = (uint32_t)__cvta_generic_to_shared(smem_raw);
    const int tid = threadIdx.x, lane = tid & 31;
    const int cta = blockIdx.x, grp = cta >> 3, sub = cta & 7;
    const uint32_t bars = sm + OFF_BAR;
    const int row0 = (sub * HKV + grp) * SK + (SK - WIN);
    u64 pol;
    asm volatile("createpolicy.fractional.L2::evict_first.b64 %0, 1.0;" : "=l"(pol));
    if (tid == NCW * 32) {
        TS(0);
        const int n0 = cta < 108 ? 0 : 3;
#pragma unroll
        for (int i = 0; i < 6; i++) mbar_init(bars + i * 8, 1);
        asm volatile("fence.mbarrier_init.release.cluster;" ::: "memory");
#pragma unroll
        for (int i = 0; i < 3; i++) {
            mbar_expect(bars + (n0 + i) * 8, 12288);
            tma3d(sm + OFF_WM + (n0 + i) * 12288, &P.m[cta < 36 ? M_WA : cta < 108 ? M_WM : M_WQ], cta < 36 ? 16 * cta : 32 * cta,
                  i * 192, 0, bars + (n0 + i) * 8);
            TI(n0 + i);
        }
        TS(26);
    }
    if (tid == NCW * 32 + 32) {
#pragma unroll
        for (int i = 0; i < 4; i++) mbar_init(bars + (BAR_FULL + i) * 8, 1);
        asm volatile("fence.mbarrier_init.release.cluster;" ::: "memory");
#pragma unroll
        for (int t = 0; t < NK0; t++) {
            mbar_expect(bars + (BAR_FULL + t) * 8, TILE_BYTES);
            tma3d_hint(sm + OFF_RING + t * TILE_BYTES, &P.m[M_K], 0, row0 + t * 32, 0, bars + (BAR_FULL + t) * 8, pol);
            TI(6 + t);
        }
    }
    if (tid < 288 && cta < 108) {
#pragma unroll
        for (int i = 0; i < 2; i++) {
            const int row = (lane >> 3) + 4 * i, so = row * DM + (tid >> 5) * 64 + (lane & 7) * 8;
            const uint32_t d = sm + OFF_RED + (tid >> 5) * 2048 + row * 128 + (((lane & 7) ^ row) << 4);
            cp16(d, P.c + so);
            if (cta < 36) cp16(d + 1024, P.x + so);
        }
    }
    uint32_t* const g0 = P.scratch;
    const uint32_t epoch = ld1(g0 + G_EPOCH);
    const int warp = __shfl_sync(0xffffffffu, tid >> 5, 0);
    auto pace = [&](int t, int gain) {
        const int d = (int)atomicAdd(g0 + (epoch & 1) * G_SET + G_CNT, 1u) - 32 * (t - 16) - 16;
        sts32(sm + OFF_WIN, min(max((d * gain + 32) >> 6, W_MIN), W_MAX));
    };

    if (warp >= NCW) {
        const int pw = warp - NCW;
        bar_arrive(1, (NCW + 1) * 32);
        if (pw && lane < M_WQ) asm volatile("prefetch.tensormap [%0];" ::"l"(&P.m[M_WQ - lane]) : "memory");
        if (tid == NCW * 32) sts32(sm + OFF_WIN, 0);
        __syncwarp();
        bar_sync(15, NTHREADS);
        if (lane == 0) {
            if (pw == 0 && cta < 108) {
#pragma unroll 1
                for (int n = 3; n < 6; n++) {
                    mbar_expect(bars + n * 8, 12288);
                    mbar_wait(bars + (n - 3) * 8, 0);
                    tma3d(sm + OFF_WM + n * 12288, &P.m[M_WQ], 32 * cta, (n - 3) * 192, 0, bars + n * 8);
                    TI(n);
                }
            }
#pragma unroll 1
            for (int t = (2 - pw) * NK0; t < 2 * NK0 + 3 * (1 - pw); t++) {
                mbar_expect(bars + (BAR_FULL + t) * 8, TILE_BYTES);
                mbar_wait(bars + (t + (pw ? BAR_FULL - NK0 : 3 - 2 * NK0)) * 8, 0);
                tma3d_hint(sm + OFF_RING + t * TILE_BYTES, &P.m[M_K], 0, row0 + t * 32, 0, bars + (BAR_FULL + t) * 8, pol);
                TI(6 + t);
            }
            if (pw == 0) {
#pragma unroll 1
                for (int t = 2 * NK0 + 3; t < 2 * NT; t++) {
                    if (t == 14 && cta < 108) mbar_wait(bars + BAR_WMF * 8, 0);
                    if (t == 15) TS(30);
                    const int m = t - ((W_KV + (int)lds32(sm + OFF_WIN) + ((0xd8 >> (2 * t & 6)) & 3)) >> 2);
                    const uint32_t fb = bars + (BAR_FULL + (t & 15)) * 8;
                    mbar_wait(fb + (BAR_EMPTY - BAR_FULL) * 8, (~t >> 4) & 1);
                    mbar_expect(fb, TILE_BYTES);
                    mbar_wait(bars + (BAR_FULL + (m & 15)) * 8, (m >> 4) & 1);
                    tma3d_hint(sm + OFF_RING + (t & 15) * TILE_BYTES, &P.m[t >> 6], 0, row0 + (t & (NT - 1)) * 32, 0, fb, pol);
                    TI(6 + t);
                    if (t == T_CLEAR) mbar_arrive(bars + (BAR_SYNC + 1) * 8);
                }
                mbar_arrive(bars + (BAR_SYNC + 2) * 8);
                mbar_wait(bars + BAR_SYNC * 8, 0);
                auto window = [&](int b, int w) {
                    b -= max((w + (int)lds32(sm + OFF_WIN) + ((0xd8 >> (2 * b & 6)) & 3)) >> 2, 1);
                    mbar_wait(bars + b * 8, b < BAR_WO);
                };
#pragma unroll 1
                for (int i = 0; i < 4; i++) {
                    window(BAR_WO + i, W_WO);
                    tma3d(sm + OFF_WO + i * 8192, &P.m[M_OD], 64 * sub, grp * 256 + i * 64, P.zo, bars + (BAR_WO + i) * 8);
                    TI(134 + i);
                }
                TS(28);
#pragma unroll 1
                for (int i = 0; i < 9; i++) {
                    mbar_wait(bars + (BAR_EMPTY + i) * 8, 1);
                    window(BAR_GU + i, W_GU);
                    tma3d(sm + OFF_GU + i * 8192, &P.m[M_GU], grp * 288 + 32 * sub, i * 64, 0, bars + (BAR_GU + i) * 8);
                    TI(138 + i);
                }
                TS(29);
#pragma unroll 1
                for (int i = 0; i < 5; i++) {
                    const int r = min(i * 64, 224);
                    mbar_wait(bars + (BAR_EMPTY + 9 + i) * 8, 1);
                    window(BAR_WD + i, W_WD);
                    tma3d(sm + OFF_WD + r * 128, &P.m[M_OD], 64 * sub, grp * 288 + r, P.zo ^ 1, bars + (BAR_WD + i) * 8);
                    TI(147 + i);
                }
            } else {
                mbar_wait(bars + (BAR_FULL + T_STRIP) * 8, 0);
                if (cta < 108) mbar_wait(bars + BAR_WMF * 8, 0);
#pragma unroll 1
                for (int i = 0; i < (sub < 4 ? 7 : 4); i++) {
                    const int r = (i & 1) * (i < 2 ? 112 : 144);
                    if (i >= 4 || i == 0) mbar_expect(bars + BAR_X * 8, i < 4 ? 9216 : 6144);
                    if (i < 4) tma3d(sm + OFF_OX + (i >> 1) * 4096 + r * 16, &P.m[M_OX], 512 + 8 * sub, grp * (i < 2 ? 256 : 288) + r, P.zo ^ (i >> 1), bars + BAR_X * 8);
                    else tma3d(sm + OFF_GX + (i - 4) * 6144, &P.m[M_GX], grp * 288 + 256 + 8 * sub, (i - 4) * 192, 0, bars + BAR_X * 8);
                    TI(152 + i);
                    if (i >= 3) mbar_wait(bars + BAR_X * 8, ~i & 1);
                }
#pragma unroll 1
                for (int i = 0; i < 18; i++) mbar_expect(bars + (BAR_WO + i) * 8, 8192);
                mbar_arrive(bars + BAR_SYNC * 8);
                mbar_wait(bars + (BAR_SYNC + 2) * 8, 0);
#pragma unroll 1
                for (int t = 124 + (cta & 3); t < 144; t += 4) {
                    mbar_wait(bars + (BAR_FULL - 112 + t) * 8, t < 128);
                    pace(t, GAIN_TAIL);
                }
            }
        }
        return;
    }

    if (lane == 0) {
#pragma unroll
        for (int i = 0; i < 6; i++) mbar_init(bars + (10 + warp * 6 + i) * 8, 1);
        asm volatile("fence.mbarrier_init.release.cluster;" ::: "memory");
    }
    __syncwarp();
    if (warp < 9) bar_arrive(15, NTHREADS);
    const int g = lane >> 2, t4 = lane & 3;
    uint32_t* const gs = g0 + (epoch & 1) * G_SET;

    if (warp < 9) {
        const int off_h = (cta < 36 ? dual(D_H + 2 * cta * 32) : G_M + 4 * (cta - 36) * 32) + tid;
        const int off_h2 = off_h + (cta < 36 ? 1024 : 64);
        const int off_q = dual(D_Q + g * (HQ * 64) + cta * 16) + warp * 8 + t4 * 2;
        uint32_t bf[8] = {}, xp = 0, mean2 = 0;
        float inv = 0.f;
        if (cta < 36) xp = __ldg(reinterpret_cast<const uint32_t*>(P.x) + g * (DM / 2) + 8 * cta + 4 * (warp & 1) + t4);
        if (warp < 2) {
#pragma unroll
            for (int pg = 0; pg < 2 * G_SET; pg += G_SET) {
                st2(g0 + pg + off_q, 0, 0), st2(g0 + pg + off_q + 1024, 0, 0);
                if (cta < 108) st1(g0 + pg + off_h, 0), st1(g0 + pg + off_h2, 0);
            }
        }
        if (cta < 108) {
            asm volatile("cp.async.wait_all;" ::: "memory");
            __syncwarp();
            const uint32_t fa = sm + OFF_RED + warp * 2048 + (lane & 7) * 128 + (((lane >> 3) ^ (lane & 7)) << 4);
            ldsm4(reinterpret_cast<uint32_t(&)[4]>(bf[0]), fa);
            ldsm4(reinterpret_cast<uint32_t(&)[4]>(bf[4]), fa ^ 64);
            if (cta < 36) {
                uint32_t xv[8];
                ldsm4(reinterpret_cast<uint32_t(&)[4]>(xv[0]), fa + 1024);
                ldsm4(reinterpret_cast<uint32_t(&)[4]>(xv[4]), (fa ^ 64) + 1024);
                ln_partial(xv, sm + OFF_ST + g * 80 + warp * 8, t4 == 0);
            }
#pragma unroll
            for (int i = 0; i < 8; i++) bf[i] = silu2(bf[i]);
        }
        if (warp == 0) TSL(18);
        bar_sync(1, (NCW + 1) * 32);
        if (cta < 36 && warp < 2) ln_combine(sm + OFF_ST + g * 80, mean2, inv);
        const int r = warp * 64 + (lane >> 4) * 8 + (lane & 7), hi8 = (lane >> 3) & 1, box = warp / 3;
#pragma unroll 1
        for (int pass = cta < 108 ? 0 : 1; pass < 2; pass++) {
            const bool pa = pass == 0 && cta < 36;
            const uint32_t ab = sm + OFF_WM + pass * 36864 +
                                (pa ? (box + hi8) * 6144 + r * 32 + ((lane & 4) << 2) : r * 64 + (((2 * hi8) ^ ((r >> 1) & 3)) << 4));
            const uint32_t as = pa ? 512 : 1024, red = sm + OFF_RED + pass * 9216;
            mbar_wait(bars + (pass * 3 + box) * 8, 0);
            if (warp == 8) TSL(pass ? 31 : 19);
            uint32_t a[4][2][4];
#pragma unroll
            for (int i = 0; i < 4; i++) {
                ldsm4t(a[i][0], ab + i * as);
                ldsm4t(a[i][1], (ab ^ 16) + i * as);
            }
            if (pass) {
                bar_sync(8, NCW * 32);
#pragma unroll
                for (int i = 0; i < 8; i++) bf[i] = 0;
                get<8, 1>(gs + near(D_H + warp * 256, lds32(sm + OFF_WIN + 4)) + lane, 32, bf);
                if (warp == 0) TSL(3);
            }
            float acc[2][4] = {};
#pragma unroll
            for (int i = 0; i < 4; i++)
#pragma unroll
                for (int m = 0; m < 2; m++) mma(acc[m], a[i][m][0], a[i][m][1], a[i][m][2], a[i][m][3], bf[2 * i], bf[2 * i + 1]);
            sts128f(red + tid * 16, acc[0]);
            sts128f(red + 4608 + tid * 16, acc[1]);
            bar_sync(3, 288);
            if (warp < 2) {
                float c[4] = {};
                sum_frags<9>(c, red + warp * 4608 + lane * 16, 512);
                uint32_t lo = movm(pack2(c[0], c[1])), hi = movm(pack2(c[2], c[3]));
                if (pass) {
                    put2d(gs + off_q, lo, hi);
                    if (warp == 0) TSL(4);
                } else {
                    const uint32_t hi1 = badd2(hi, ONE2);
                    if (pa) hi = lo = modulate2(xp, mean2, inv, lo, hi1);
                    if (cta >= 72 && cta < 90) lo = badd2(lo, ONE2), hi = hi1;
                    st1(gs + off_h, nz(lo));
                    st1(gs + off_h2, nz(hi));
                    if (warp == 0 && pa) TSL(2);
                }
            } else if (tid == 64 && pass == 0) {
                mbar_arrive(bars + BAR_WMF * 8);
            }
        }
    } else {
        uint32_t* const ping = g0 + dual(D_PING) + cta * 8;
        if (lane < 16) st1(ping + (lane >> 3) * 1024 + (lane & 7), 0);
        bar_sync(15, NTHREADS);
        uint32_t best[2] = {~0u, ~0u}, v = 0;
#pragma unroll 1
        for (int part = 0; part < 2; part++) {
            if (lane == 0) {
#pragma unroll 1
                for (int r = part ? NPING1 : NPING0; r > 0; r--) {
#pragma unroll
                    for (int k = 0; k < 2; k++) {
                        const uint32_t t0 = clock32(v);
                        v = atomicExch(ping + k * 1024, t0);
                        best[k] = min(best[k], clock32(v) - t0);
                    }
                }
                sts32(sm + OFF_WIN + 4 + 4 * part, ((best[1] < best[0]) ^ __popc(D_PING & 0x16400)) & 1);
            }
            __syncwarp();
            if (part) break;
            TSL(20);
            bar_arrive(8, NCW * 32);
            mbar_wait(bars + 5 * 8, 0);
            uint32_t a[4] = {};
            get<1, 4>(gs + near(D_Q + (sub * HQ + 2 * grp) * 64, lds32(sm + OFF_WIN + 4)) + lane * 4, 0, a);
            sts128(sm + OFF_QS + lane * 16, a[0], a[1], a[2], a[3]);
            __syncwarp();
            TSL(5);
            bar_arrive(4, 288);
        }
        if (cta == 0 && lane == 0) st1(g0 + (~epoch & 1) * G_SET + G_CNT, 0);
        mbar_wait(bars + (BAR_SYNC + 1) * 8, 0);
#pragma unroll 1
        for (int c = 0; c < 4; c++) {
            uint32_t* const pg = g0 + (c >> 1) * G_SET + (c & 1) * 1024;
            zero4(pg + dual(D_O + cta * 128) + lane * 4);
            zero4(pg + dual(D_ACT + (grp * 36 + 4 * sub) * 32) + lane * 4);
            if (lane < 8 ? sub < 4 : lane < 16 && cta < 72)
                zero4(pg + dual(lane < 8 ? D_ACT + (grp * 36 + 32 + sub) * 32 : D_X1 + cta * 32) + (lane & 7) * 4);
        }
#pragma unroll 1
        for (int u = 0; u < 9; u++) zero4(g0 + dual(d_part(u < 8 ? 8 * sub + u : 64 + sub)) + (lane >> 4) * 1024 + grp * 64 + (lane & 15) * 4);
        __syncwarp();
        bar_arrive(5, NCW * 32);
        return;
    }

    const uint32_t tile = sm + OFF_RING + warp * TILE_BYTES;
    const uint32_t fullb = bars + (BAR_FULL + warp) * 8;
    const uint32_t pw = sm + OFF_P + warp * (2 * P_PITCH);
    const bool pacer = (tid & 127) == (cta & 3) * 32;
    if (warp < 8) {
        {
            uint32_t q0[8], q1[8];
            bar_sync(4, 288);
#pragma unroll
            for (int i = 0; i < 8; i++) {
                const float2 v = lds64f(sm + OFF_QS + (g & 1) * 256 + i * 32 + t4 * 8);
                q0[i] = __float_as_uint(v.x), q1[i] = __float_as_uint(v.y);
            }
            uint32_t sp = pw + (t4 & 1) * P_PITCH + ((t4 >> 1) * 8 + g) * 2;
#pragma unroll 1
            for (int it = 0; it < 8; it++, sp += 64) {
                const uint32_t ab = tile + (it & 1) * (8 * TILE_BYTES) + (lane & 15) * 128 + (((lane >> 4) ^ (lane & 7)) << 4);
                mbar_wait(fullb + (it & 1) * 64, (it >> 1) & 1);
                float acc[2][2][4] = {};
#pragma unroll
                for (int ks = 0; ks < 8; ks++)
#pragma unroll
                    for (int m = 0; m < 2; m++) {
                        uint32_t a[4];
                        ldsm4(a, (ab ^ ((ks & 3) << 5)) + (ks >> 2) * 4096 + m * 2048);
                        mma(acc[m][ks & 1], a[0], a[1], a[2], a[3], (ks & 1) ? q1[ks - 1] : q0[ks], (ks & 1) ? q1[ks] : q0[ks + 1]);
                    }
                __syncwarp();
                if (lane == 0) mbar_arrive(fullb + (it & 1) * 64 + (BAR_EMPTY - BAR_FULL) * 8);
#pragma unroll
                for (int m = 0; m < 2; m++) {
                    const float s = sel4(acc[m][0], t4) + sel4(acc[m][1], t4);
                    sts16(sp + m * 32, (uint16_t)pack2(rbf(s) * 0.08838834764831845f, 0.f));
                }
                if (pacer && it >= 2) pace(it * 8 + warp, GAIN_KV);
                __syncwarp();
            }
        }
        __syncwarp();
        if (warp == 7) TSL(6);
        const uint32_t pa = pw + (lane >> 4) * P_PITCH + (lane & 15) * 32;
        const uint32_t sa = sm + OFF_SM + (lane >> 4) * 64;
        const uint4 v0 = lds128(pa), v1 = lds128(pa + 16);
        const uint32_t sv[8] = {v0.x, v0.y, v0.z, v0.w, v1.x, v1.y, v1.z, v1.w};
        float e[16];
        float m = -INFINITY;
#pragma unroll
        for (int i = 0; i < 8; i++) {
            e[2 * i] = blo(sv[i]);
            e[2 * i + 1] = bhi(sv[i]);
            m = fmaxf(m, fmaxf(e[2 * i], e[2 * i + 1]));
        }
#pragma unroll
        for (int o = 8; o; o >>= 1) m = fmaxf(m, __shfl_xor_sync(0xffffffffu, m, o));
        float l = 0.f;
#pragma unroll
        for (int i = 0; i < 16; i++) {
            e[i] = ex2((e[i] - m) * LOG2E);
            l += e[i];
        }
#pragma unroll
        for (int o = 8; o; o >>= 1) l += __shfl_xor_sync(0xffffffffu, l, o);
        if ((lane & 15) == 0) sts64(sa + warp * 8, __float_as_uint(m), __float_as_uint(l));
        bar_sync(2, 288);
        const float2 v = lds64f(sa + (lane & 7) * 8);
        float M = v.x;
#pragma unroll
        for (int o = 4; o; o >>= 1) M = fmaxf(M, __shfl_xor_sync(0xffffffffu, M, o));
        float L = v.y * ex2((v.x - M) * LOG2E);
#pragma unroll
        for (int o = 4; o; o >>= 1) L += __shfl_xor_sync(0xffffffffu, L, o);
        const float sc = ex2((m - M) * LOG2E) * rcp(L);
        sts128(pa, pack2(e[0] * sc, e[1] * sc), pack2(e[2] * sc, e[3] * sc), pack2(e[4] * sc, e[5] * sc), pack2(e[6] * sc, e[7] * sc));
        sts128(pa + 16, pack2(e[8] * sc, e[9] * sc), pack2(e[10] * sc, e[11] * sc), pack2(e[12] * sc, e[13] * sc), pack2(e[14] * sc, e[15] * sc));
        __syncwarp();
    } else {
        bar_sync(2, 288);
    }

    const bool reducer = cta < 72 && warp < 4;
    const int rbat = 2 * t4 + (g & 1);
    uint32_t sh[8] = {}, op[8] = {}, wr[8], rx = 0, rg[2] = {};
    const uint32_t* const src_m = gs + G_M + (72 + warp * 8) * 32 + lane;
    const uint32_t* const src_g = gs + G_M + cta * 32 + rbat * 4 + warp;
#pragma unroll
    for (int i = 0; i < 8; i++) {
        wr[i] = __ldg(reinterpret_cast<const uint32_t*>(P.wr) + warp * 32 + i * 4 + t4);
        sh[i] = ld1(src_m + i * 32);
        op[i] = ld1(src_m + (72 + i) * 32);
    }
    if (reducer) {
        rx = __ldg(reinterpret_cast<const uint32_t*>(P.x) + rbat * (DM / 2) + 4 * cta + warp);
        rg[0] = ld1(src_g), rg[1] = ld1(src_g + 216 * 32);
    }

    if (warp < 8) {
        float acc[8][4] = {};
        uint32_t pp = pw + (lane & 1) * P_PITCH + (lane >> 3) * 16;
#pragma unroll 1
        for (int it = 0; it < 8; it++, pp += 64) {
            const uint32_t ab = tile + (it & 1) * (8 * TILE_BYTES) + ((lane & 7) + (lane >> 4) * 8) * 128 + ((((lane >> 3) & 1) ^ (lane & 7)) << 4);
            uint32_t pb[4];
            ldsm4(pb, pp);
            mbar_wait(fullb + (it & 1) * 64, (it >> 1) & 1);
#pragma unroll
            for (int ks = 0; ks < 2; ks++)
#pragma unroll
                for (int m = 0; m < 8; m++) {
                    uint32_t a[4];
                    ldsm4t(a, (ab ^ ((m & 3) << 5)) + (m >> 2) * 4096 + ks * 2048);
                    mma(acc[m], a[0], a[1], a[2], a[3], pb[2 * ks], pb[2 * ks + 1]);
                }
            __syncwarp();
            if (lane == 0) mbar_arrive(fullb + (it & 1) * 64 + (BAR_EMPTY - BAR_FULL) * 8);
            if (pacer && it * 8 + warp < NT - 4) pace(NT + it * 8 + warp, GAIN_KV);
            __syncwarp();
        }
        if (warp == 7) TSL(7);
        const uint32_t ra = sm + OFF_ORED + warp * 1088 + (t4 & 1) * 576 + ((t4 >> 1) * 8 + g) * 4;
#pragma unroll
        for (int m = 0; m < 8; m++) sts32(ra + m * 64, __float_as_uint(sel4(acc[m], t4)));
    }
    bar_sync(5, NCW * 32);
    if (warp < 4) {
        float s[2][2] = {};
#pragma unroll
        for (int w = 0; w < 8; w++) {
            const float2 v = lds64f(sm + OFF_ORED + w * 1088 + (tid >> 6) * 64 + tid * 8);
            s[w & 1][0] += v.x;
            s[w & 1][1] += v.y;
        }
        put1d(gs + dual(D_O + cta * 128) + (tid & 0x70) + (tid & 3) * 4 + ((tid >> 2) & 3), pack2(s[0][0] + s[1][0], s[0][1] + s[1][1]));
        if (warp == 0) TSL(8);
    }

    const int side = lds32(sm + OFF_WIN + 8);
    uint32_t* const dst_p = g0 + dual(d_part(warp < 8 ? 8 * sub + warp : 64 + sub)) + grp * 64 + lane * 2;
    project<0>(sm, gs + near(D_O + grp * 1024, side) + g * 128 + warp * 16 + t4 * 4, dst_p, warp, lane);
    if (warp == 0) TSL(9);
    const uint32_t* const src_p = g0 + near(d_part(cta), side) + (lane >> 3) * 256 + 16 * warp + (lane & 7) * 2;
    if (reducer) {
        get<2, 1>(src_g, 216 * 32, rg);
        rx = badd2(rx, bmul2(rg[0], reduce16<0>(src_p, lane)));
        if (lane < 16) st1(gs + dual(D_X1 + cta * 32) + (lane >> 3) * 1024 + warp * 8 + (lane & 7), nz(rx));
        if (warp == 0) TSL(10);
    }

    get<8, 1>(src_m, 32, sh);
    get<8, 1>(src_m + 72 * 32, 32, op);
    const uint32_t gbar = bars + (BAR_GU + warp) * 8;
    const int rr = (lane >> 4) * 8 + (lane & 7), pl = ((lane >> 3) & 1) ^ P.zg;
    const uint32_t ab = sm + OFF_GU + warp * 8192 + pl * 4096 + rr * 64 + ((lane & 6) << 3);
    const uint32_t ax = sm + OFF_GX + (warp / 3 + pl) * 3072 + (warp * 64 + rr) * 16;
    uint32_t a[20][4] = {}, h[8] = {};
    auto load_gu = [&]() {
#pragma unroll
        for (int i = 0; i < 20; i++) ldsm4t(a[i], i % 5 < 4 ? (ab ^ ((i % 5) << 4)) + (i / 5) * 1024 : ax + (i / 5) * 256);
    };
    bool gpre = false;
    {
        const uint32_t* const src_x = gs + near(D_X1 + warp * 256, side) + t4 * 8 + (g & 1) * 4 + (g >> 1);
        int it = 0;
        do {
            fetch<8, 1>(src_x, 32, h);
            if (!gpre && __all_sync(0xffffffffu, mbar_test(gbar, 0))) gpre = true, load_gu();
        } while (missing(h) && ++it < SPIN_LIMIT);
    }
    if (warp == 0) TSL(11);
    ln_partial(h, sm + OFF_ST + g * 80 + warp * 8, t4 == 0);
    bar_sync(3, 288);
    {
        uint32_t mean2;
        float inv;
        ln_combine(sm + OFF_ST + g * 80, mean2, inv);
#pragma unroll
        for (int i = 0; i < 8; i++) h[i] = modulate2(h[i], mean2, inv, sh[i], op[i]);
    }
    if (warp == 0) TSL(12);
    if (!gpre) {
        mbar_wait(gbar, 0);
        load_gu();
    }
    if (warp == 8) TSL(17);
    {
        float acc[5][4] = {};
#pragma unroll
        for (int i = 0; i < 20; i++) mma(acc[i % 5], a[i][0], a[i][1], a[i][2], a[i][3], h[2 * (i / 5)], h[2 * (i / 5) + 1]);
#pragma unroll
        for (int m = 0; m < 5; m++) sts128f(sm + OFF_RED + m * 4608 + tid * 16, acc[m]);
    }
    bar_sync(3, 288);
    if (warp < 5) {
        float c[4] = {};
        sum_frags<9>(c, sm + OFF_RED + warp * 4608 + lane * 16, 512);
        const uint32_t w = movm(bmul2(silu2(pack2(c[0], c[1])), pack2(c[2], c[3])));
        if (warp < 4 || sub < 4) put1d(gs + dual(D_ACT + (grp * 36 + (warp < 4 ? 4 * sub + warp : 32 + sub)) * 32) + lane, w);
        if (warp == 1) TSL(13);
    }
    if (cta < 72) {
        float r = 0.f;
#pragma unroll
        for (int i = 0; i < 8; i++) {
            r = fmaf(blo(h[i]), blo(wr[i]), fmaf(bhi(h[i]), bhi(wr[i]), r));
            if (warp * 8 + i == cta) sts32(sm + OFF_HU + lane * 4, h[i]);
        }
        r = quad_sum(r);
        if (t4 == 0) sts32(sm + OFF_RT + g * 48 + warp * 4, __float_as_uint(r));
    }

    project<1>(sm, gs + near(D_ACT + (grp * 36 + 4 * warp) * 32, side) + lane, dst_p, warp, lane);
    if (warp == 0) TSL(14);
    if (reducer) {
        const uint4 r0 = lds128(sm + OFF_RT + rbat * 48), r1 = lds128(sm + OFF_RT + rbat * 48 + 16);
        float r = __uint_as_float(lds32(sm + OFF_RT + rbat * 48 + 32));
        r += ((__uint_as_float(r0.x) + __uint_as_float(r0.y)) + (__uint_as_float(r0.z) + __uint_as_float(r0.w))) +
             ((__uint_as_float(r1.x) + __uint_as_float(r1.y)) + (__uint_as_float(r1.z) + __uint_as_float(r1.w)));
        r = sigmoid_f(rbf(r));
        const uint32_t rh = lds32(sm + OFF_HU + (rbat * 4 + warp) * 4);
        const uint32_t y = badd2(rh, bmul2(reduce16<1>(src_p, lane), pack2(r, r)));
        if (lane < 8) reinterpret_cast<uint32_t*>(P.out)[rbat * (DM / 2) + 4 * cta + warp] = badd2(rx, bmul2(rg[1], y));
        if (cta == 0 && tid == 0) g0[G_EPOCH] = epoch + 1;
        if (warp == 0) TSL(15);
    }
}

typedef CUresult (*EncodeFn)(CUtensorMap*, CUtensorMapDataType, cuuint32_t, void*, const cuuint64_t*, const cuuint64_t*,
                             const cuuint32_t*, const cuuint32_t*, CUtensorMapInterleave, CUtensorMapSwizzle,
                             CUtensorMapL2promotion, CUtensorMapFloatOOBfill);

void make_map(EncodeFn enc, CUtensorMap* m, void* p, int cols, int rows, int pitch, int bc, int br, int bp, int planes, size_t pstride,
              CUtensorMapSwizzle sw, int promo) {
    cuuint64_t dims[3] = {(cuuint64_t)cols, (cuuint64_t)rows, (cuuint64_t)planes};
    cuuint64_t strides[2] = {(cuuint64_t)pitch * 2, (cuuint64_t)pstride};
    cuuint32_t box[3] = {(cuuint32_t)bc, (cuuint32_t)br, (cuuint32_t)bp};
    cuuint32_t es[3] = {1, 1, 1};
    enc(m, CU_TENSOR_MAP_DATA_TYPE_BFLOAT16, 3, p, dims, strides, box, es, CU_TENSOR_MAP_INTERLEAVE_NONE, sw,
        (CUtensorMapL2promotion)promo, CU_TENSOR_MAP_FLOAT_OOB_FILL_NONE);
}

}

extern "C" void kernel_launch(void* const* d_in, const int* in_sizes, int n_in, void* d_out, int out_size) {
    static EncodeFn enc = nullptr;
    static uint32_t* scratch = nullptr;
    if (!enc) {
        void* fn = nullptr;
        cudaDriverEntryPointQueryResult st;
        cudaGetDriverEntryPoint("cuTensorMapEncodeTiled", &fn, cudaEnableDefault, &st);
        enc = (EncodeFn)fn;
        cudaGetSymbolAddress(&fn, g_scratch);
        scratch = (uint32_t*)(((uintptr_t)fn + 8 * G_SET - 1) & ~(uintptr_t)(8 * G_SET - 1));
        cudaFuncSetAttribute(fused_kernel, cudaFuncAttributeMaxDynamicSharedMemorySize, SMEM_BYTES);
    }
    Params P;
    const CUtensorMapSwizzle none = CU_TENSOR_MAP_SWIZZLE_NONE;
    make_map(enc, &P.m[M_K], d_in[1], 64, NB * HKV * SK, DH, 64, 32, 2, 2, 128, CU_TENSOR_MAP_SWIZZLE_128B, PROMO_KV);
    make_map(enc, &P.m[M_V], d_in[2], 64, NB * HKV * SK, DH, 64, 32, 2, 2, 128, CU_TENSOR_MAP_SWIZZLE_128B, PROMO_KV);
    make_map(enc, &P.m[M_WQ], d_in[3], HQ * DH, DM, HQ * DH, 32, 192, 1, 1, 16, CU_TENSOR_MAP_SWIZZLE_64B, PROMO_W);
    make_map(enc, &P.m[M_WM], d_in[11], 6 * DM, DM, 6 * DM, 32, 192, 1, 1, 16, CU_TENSOR_MAP_SWIZZLE_64B, PROMO_W);
    make_map(enc, &P.m[M_WA], d_in[11], DM, DM, 6 * DM, 16, 192, 2, 2, DM * 2, CU_TENSOR_MAP_SWIZZLE_32B, PROMO_W);
    char *wg = (char*)d_in[7], *wu = (char*)d_in[8], *wo = (char*)d_in[4], *wd = (char*)d_in[9];
    P.zg = wg > wu;
    P.zo = wo > wd;
    const size_t sg = P.zg ? wg - wu : wu - wg, so = P.zo ? wo - wd : wd - wo;
    make_map(enc, &P.m[M_GU], P.zg ? wu : wg, FF, DM, FF, 32, 64, 2, 2, sg, CU_TENSOR_MAP_SWIZZLE_64B, PROMO_W);
    make_map(enc, &P.m[M_GX], P.zg ? wu : wg, FF, DM, FF, 8, 192, 2, 2, sg, none, PROMO_W);
    make_map(enc, &P.m[M_OD], P.zo ? wd : wo, DM, FF, DM, 64, 64, 1, 2, so, CU_TENSOR_MAP_SWIZZLE_128B, PROMO_W);
    make_map(enc, &P.m[M_OX], P.zo ? wd : wo, DM, FF, DM, 8, 144, 1, 2, so, none, PROMO_W);
    P.x = (const __nv_bfloat16*)d_in[0];
    P.wr = (const __nv_bfloat16*)d_in[6];
    P.c = (const __nv_bfloat16*)d_in[10];
    P.out = (__nv_bfloat16*)d_out;
    P.scratch = scratch;
    fused_kernel<<<NCTA, NTHREADS, SMEM_BYTES>>>(P);
}
```

```cpp
#include <cuda_runtime.h>
#include <cuda_bf16.h>
#include <cuda.h>
#include <stdint.h>

typedef unsigned long long u64;

#define W_KV 20
#define W_WO 20
#define W_GU 18
#define W_WD 14
#define W_MIN -8
#define W_MAX 8
#define GAIN_KV 2
#define GAIN_TAIL 3
#define NK0 1
#define T_STRIP 16
#define T_CLEAR 112
#define X_NS 7
#define B_CAP 8
#define NPING0 3
#define NPING1 10
#define PROMO_W CU_TENSOR_MAP_L2_PROMOTION_L2_128B
#define PROMO_GX 0
#define PROMO_OX 2
#define PROMO_GU 2
#define PROMO_KV CU_TENSOR_MAP_L2_PROMOTION_L2_256B

namespace {

constexpr int NB = 8, DM = 576, HQ = 32, HKV = 16, SK = 8192, WIN = 2048, DH = 128, FF = 4608;
constexpr int NCTA = 128;
constexpr int NCW = 10;
constexpr int NTHREADS = (NCW + 2) * 32;
constexpr int TILE_BYTES = 8192, NSLOT = 16, NT = 64;
constexpr int SPIN_LIMIT = 1 << 22;

constexpr int OFF_RING = 0;
constexpr int OFF_WM = 121856;
constexpr int OFF_WQ = OFF_WM + 36864;
constexpr int OFF_GU = 0;
constexpr int OFF_WD = 73728;
constexpr int OFF_OX = 131072;
constexpr int OFF_DX = OFF_OX + 4096;
constexpr int OFF_GX = OFF_DX + 4608;
constexpr int OFF_WO = OFF_WQ;
constexpr int OFF_P = OFF_WQ + 36864;
constexpr int P_PITCH = 528;
constexpr int OFF_RED = OFF_P + 16 * P_PITCH;
constexpr int OFF_ORED = OFF_RED + 5 * 4608 - 8704;
constexpr int OFF_ST = OFF_RED + 5 * 4608;
constexpr int OFF_SM = OFF_ST + 640;
constexpr int OFF_RT = OFF_SM + 128;
constexpr int OFF_HU = OFF_RT + 384;
constexpr int OFF_QS = OFF_HU + 128;
constexpr int OFF_WR = OFF_QS + 512;
constexpr int OFF_WIN = OFF_WR + 1152;
constexpr int OFF_BAR = OFF_WIN + 16;
constexpr int BAR_FULL = 6, BAR_WO = 22, BAR_GU = 26, BAR_WD = 35, BAR_EMPTY = 40, BAR_SYNC = 56, BAR_WMF = 59, BAR_X = 60, NBAR = 70;
constexpr int SMEM_BYTES = OFF_BAR + NBAR * 8;

constexpr int D_X1 = 0;
constexpr int D_O = 3072;
constexpr int D_ACT = D_O + 512 * 32;
constexpr int D_H = D_ACT + 576 * 32;
constexpr int D_Q = D_H + 3072;
constexpr int G_M = 2 * (D_Q + NB * HQ * 64);
constexpr int G_CNT = G_M + 288 * 32;
constexpr int G_SET = 1 << 18;
__device__ __forceinline__ int d_part(int unit) { return (64 + unit + (unit & 64)) * 1024; }
constexpr int D_PING = 200 * 1024;
constexpr int G_EPOCH = 201 * 2048;
static_assert(G_CNT < 64 * 2048, "scratch layout");
__device__ uint32_t g_scratch[4 * G_SET];
__device__ __forceinline__ int dual(int w) { return w + (w & ~1023); }
__device__ __forceinline__ int near(int w, int side) { return dual(w) + (((__popc(w & 0x16400) ^ side) & 1) << 10); }

#define TI(i)
#define TS(i)
#define TSL(i)

enum { M_K, M_V, M_GU, M_GX, M_OD, M_OX, M_WQ, M_WM, M_WA, NMAP };
struct Params {
    CUtensorMap m[NMAP];
    const __nv_bfloat16 *x, *c, *wr;
    __nv_bfloat16* out;
    uint32_t* scratch;
    int zg, zo;
};

__device__ __forceinline__ void mbar_init(uint32_t bar, int cnt) {
    asm volatile("mbarrier.init.shared::cta.b64 [%0], %1;" ::"r"(bar), "r"(cnt));
}
__device__ __forceinline__ void mbar_expect(uint32_t bar, uint32_t bytes) {
    asm volatile("mbarrier.arrive.expect_tx.shared::cta.b64 _, [%0], %1;" ::"r"(bar), "r"(bytes) : "memory");
}
__device__ __forceinline__ void mbar_arrive(uint32_t bar) {
    asm volatile("mbarrier.arrive.shared::cta.b64 _, [%0];" ::"r"(bar) : "memory");
}
__device__ __forceinline__ void mbar_wait(uint32_t bar, uint32_t parity) {
    asm volatile("{\n.reg .pred p;\n.reg .u32 c;\n"
                 "mbarrier.try_wait.parity.shared::cta.b64 p, [%0], %1;\n@p bra DONE;\nmov.u32 c, %2;\n"
                 "AGAIN:\nmbarrier.try_wait.parity.shared::cta.b64 p, [%0], %1;\nsub.u32 c, c, 1;\n"
                 "setp.eq.or.u32 p, c, 0, p;\n@!p bra AGAIN;\nDONE:\n}"
                 ::"r"(bar), "r"(parity), "n"(SPIN_LIMIT) : "memory");
}
__device__ __forceinline__ bool mbar_test(uint32_t bar, uint32_t parity) {
    uint32_t ok;
    asm volatile("{\n.reg .pred p;\nmbarrier.test_wait.parity.shared::cta.b64 p, [%1], %2;\nselp.u32 %0, 1, 0, p;\n}"
                 : "=r"(ok) : "r"(bar), "r"(parity) : "memory");
    return ok;
}
__device__ __forceinline__ void mbar_wait_lanes(uint32_t bar) {
    mbar_wait(bar, 0);
    __syncwarp();
}
__device__ __forceinline__ void tma3d_hint(uint32_t dst, const CUtensorMap* m, int x, int y, int z, uint32_t bar, u64 pol) {
    asm volatile("cp.async.bulk.tensor.3d.shared::cluster.global.mbarrier::complete_tx::bytes.L2::cache_hint"
                 " [%0], [%1, {%2, %3, %4}], [%5], %6;"
                 ::"r"(dst), "l"(m), "r"(x), "r"(y), "r"(z), "r"(bar), "l"(pol) : "memory");
}
__device__ __forceinline__ void tma3d(uint32_t dst, const CUtensorMap* m, int x, int y, int z, uint32_t bar) {
    asm volatile("cp.async.bulk.tensor.3d.shared::cluster.global.mbarrier::complete_tx::bytes [%0], [%1, {%2, %3, %4}], [%5];"
                 ::"r"(dst), "l"(m), "r"(x), "r"(y), "r"(z), "r"(bar) : "memory");
}
__device__ __forceinline__ void bar_sync(int id, int n) { asm volatile("bar.sync %0, %1;" ::"r"(id), "r"(n) : "memory"); }
__device__ __forceinline__ void bar_arrive(int id, int n) { asm volatile("bar.arrive %0, %1;" ::"r"(id), "r"(n) : "memory"); }
__device__ __forceinline__ void ldsm4(uint32_t (&r)[4], uint32_t a) {
    asm volatile("ldmatrix.sync.aligned.m8n8.x4.shared.b16 {%0,%1,%2,%3}, [%4];"
                 : "=r"(r[0]), "=r"(r[1]), "=r"(r[2]), "=r"(r[3]) : "r"(a) : "memory");
}
__device__ __forceinline__ void ldsm4t(uint32_t (&r)[4], uint32_t a) {
    asm volatile("ldmatrix.sync.aligned.m8n8.x4.trans.shared.b16 {%0,%1,%2,%3}, [%4];"
                 : "=r"(r[0]), "=r"(r[1]), "=r"(r[2]), "=r"(r[3]) : "r"(a) : "memory");
}
__device__ __forceinline__ void mma(float (&c)[4], uint32_t a0, uint32_t a1, uint32_t a2, uint32_t a3, uint32_t b0, uint32_t b1) {
    asm volatile("mma.sync.aligned.m16n8k16.row.col.f32.bf16.bf16.f32 {%0,%1,%2,%3}, {%4,%5,%6,%7}, {%8,%9}, {%0,%1,%2,%3};"
                 : "+f"(c[0]), "+f"(c[1]), "+f"(c[2]), "+f"(c[3])
                 : "r"(a0), "r"(a1), "r"(a2), "r"(a3), "r"(b0), "r"(b1));
}
__device__ __forceinline__ uint32_t movm(uint32_t a) {
    uint32_t d;
    asm volatile("movmatrix.sync.aligned.m8n8.trans.b16 %0, %1;" : "=r"(d) : "r"(a));
    return d;
}
__device__ __forceinline__ uint32_t lds32(uint32_t a) { uint32_t v; asm volatile("ld.shared.b32 %0, [%1];" : "=r"(v) : "r"(a) : "memory"); return v; }
__device__ __forceinline__ float2 lds64f(uint32_t a) { float2 v; asm volatile("ld.shared.v2.f32 {%0,%1}, [%2];" : "=f"(v.x), "=f"(v.y) : "r"(a) : "memory"); return v; }
__device__ __forceinline__ uint4 lds128(uint32_t a) { uint4 v; asm volatile("ld.shared.v4.b32 {%0,%1,%2,%3}, [%4];" : "=r"(v.x), "=r"(v.y), "=r"(v.z), "=r"(v.w) : "r"(a) : "memory"); return v; }
__device__ __forceinline__ void sts32(uint32_t a, uint32_t v) { asm volatile("st.shared.b32 [%0], %1;" ::"r"(a), "r"(v) : "memory"); }
__device__ __forceinline__ void sts16(uint32_t a, uint16_t v) { asm volatile("st.shared.b16 [%0], %1;" ::"r"(a), "h"(v) : "memory"); }
__device__ __forceinline__ void sts64(uint32_t a, uint32_t x, uint32_t y) { asm volatile("st.shared.v2.b32 [%0], {%1,%2};" ::"r"(a), "r"(x), "r"(y) : "memory"); }
__device__ __forceinline__ void sts128(uint32_t a, uint32_t x, uint32_t y, uint32_t z, uint32_t w) {
    asm volatile("st.shared.v4.b32 [%0], {%1,%2,%3,%4};" ::"r"(a), "r"(x), "r"(y), "r"(z), "r"(w) : "memory");
}
__device__ __forceinline__ void sts128f(uint32_t a, const float (&c)[4]) {
    sts128(a, __float_as_uint(c[0]), __float_as_uint(c[1]), __float_as_uint(c[2]), __float_as_uint(c[3]));
}

__device__ __forceinline__ float sel4(const float (&c)[4], int t) { return (t & 2) ? ((t & 1) ? c[3] : c[2]) : ((t & 1) ? c[1] : c[0]); }

__device__ __forceinline__ uint32_t pin(uint32_t v) { return __shfl_xor_sync(0xffffffffu, v, 0); }
template <typename T>
__device__ __forceinline__ T* at(T* base, uint32_t bytes) { return reinterpret_cast<T*>(reinterpret_cast<char*>(base) + bytes); }

__device__ __forceinline__ uint32_t clock32(uint32_t dep) {
    uint32_t t;
    asm volatile("{\n.reg .pred p;\nsetp.eq.u32 p, %1, 0x9e3779b9;\n@p nanosleep.u32 1;\nmov.u32 %0, %clock;\n}" : "=r"(t) : "r"(dep) : "memory");
    return t;
}

__device__ __forceinline__ uint32_t nz(uint32_t v) { return v ? v : 0x80000000u; }
__device__ __forceinline__ void st1(uint32_t* p, uint32_t a) { asm volatile("st.relaxed.gpu.global.b32 [%0], %1;" ::"l"(p), "r"(a) : "memory"); }
__device__ __forceinline__ void st2(uint32_t* p, uint32_t a, uint32_t b) {
    asm volatile("st.relaxed.gpu.global.v2.b32 [%0], {%1,%2};" ::"l"(p), "r"(a), "r"(b) : "memory");
}
__device__ __forceinline__ void zero4(uint32_t* p) { asm volatile("st.relaxed.gpu.global.v4.b32 [%0], {%1,%1,%1,%1};" ::"l"(p), "r"(0) : "memory"); }
__device__ __forceinline__ void put1d(uint32_t* p, uint32_t a) { a = nz(a), st1(p, a), st1(p + 1024, a); }
__device__ __forceinline__ void put2d(uint32_t* p, uint32_t a, uint32_t b) { a = nz(a), b = nz(b), st2(p, a, b), st2(p + 1024, a, b); }
__device__ __forceinline__ uint32_t ld1(const uint32_t* p) {
    uint32_t v;
    asm volatile("ld.relaxed.gpu.global.b32 %0, [%1];" : "=r"(v) : "l"(p) : "memory");
    return v;
}
template <int N, int V>
__device__ __forceinline__ void fetch(const uint32_t* p, int stride, uint32_t (&a)[N * V]) {
#pragma unroll
    for (int i = 0; i < N; i++) {
        if (V == 1)
            asm volatile("{\n.reg .pred p;\nsetp.eq.u32 p, %0, 0;\n@p ld.relaxed.gpu.global.b32 %0, [%1];\n}"
                         : "+r"(a[i]) : "l"(p + i * stride) : "memory");
        if (V == 4)
            asm volatile("{\n.reg .pred p;\nsetp.eq.u32 p, %4, 0;\n@p ld.relaxed.gpu.global.v4.b32 {%0,%1,%2,%3}, [%5];\n}"
                         : "+r"(a[V * i]), "+r"(a[V * i + V / 4]), "+r"(a[V * i + V / 2]), "+r"(a[V * i + V - 1])
                         : "r"(min(min(a[V * i], a[V * i + V / 4]), min(a[V * i + V / 2], a[V * i + V - 1]))), "l"(p + i * stride) : "memory");
    }
}
template <int N>
__device__ __forceinline__ bool missing(const uint32_t (&a)[N]) {
    uint32_t lo = a[0];
#pragma unroll
    for (int i = 1; i < N; i++) lo = min(lo, a[i]);
    return __any_sync(0xffffffffu, lo == 0);
}
template <int N, int V>
__device__ __forceinline__ void get(const uint32_t* p, int stride, uint32_t (&a)[N * V]) {
    int it = 0;
    do fetch<N, V>(p, stride, a);
    while (missing(a) & (++it < SPIN_LIMIT));
}
__device__ __forceinline__ void cp16(uint32_t dst, const void* src) {
    asm volatile("cp.async.cg.shared.global [%0], [%1], 16;" ::"r"(dst), "l"(src) : "memory");
}

__device__ __forceinline__ uint32_t pack2(float lo, float hi) {
    uint32_t r;
    asm("cvt.rn.bf16x2.f32 %0, %1, %2;" : "=r"(r) : "f"(hi), "f"(lo));
    return r;
}
__device__ __forceinline__ float rbf(float x) { return __uint_as_float(pack2(0.f, x)); }
__device__ __forceinline__ float blo(uint32_t v) { return __uint_as_float(v << 16); }
__device__ __forceinline__ float bhi(uint32_t v) { return __uint_as_float(v & 0xffff0000u); }
__device__ __forceinline__ uint32_t badd2(uint32_t a, uint32_t b) { uint32_t r; asm("add.rn.bf16x2 %0, %1, %2;" : "=r"(r) : "r"(a), "r"(b)); return r; }
__device__ __forceinline__ uint32_t bsub2(uint32_t a, uint32_t b) { uint32_t r; asm("sub.rn.bf16x2 %0, %1, %2;" : "=r"(r) : "r"(a), "r"(b)); return r; }
__device__ __forceinline__ uint32_t bmul2(uint32_t a, uint32_t b) { uint32_t r; asm("mul.rn.bf16x2 %0, %1, %2;" : "=r"(r) : "r"(a), "r"(b)); return r; }
__device__ __forceinline__ float ex2(float x) { float r; asm("ex2.approx.ftz.f32 %0, %1;" : "=f"(r) : "f"(x)); return r; }
__device__ __forceinline__ float rcp(float x) { float r; asm("rcp.approx.ftz.f32 %0, %1;" : "=f"(r) : "f"(x)); return r; }
__device__ __forceinline__ float sqrt_f(float x) { float r; asm("sqrt.approx.ftz.f32 %0, %1;" : "=f"(r) : "f"(x)); return r; }
constexpr float LOG2E = 1.4426950408889634f;
constexpr uint32_t ONE2 = 0x3f803f80u;
__device__ __forceinline__ float sigmoid_f(float x) { return rcp(1.0f + ex2(-LOG2E * x)); }
__device__ __forceinline__ uint32_t silu2(uint32_t v) {
    const float a = blo(v), b = bhi(v);
    return pack2(a * sigmoid_f(a), b * sigmoid_f(b));
}
__device__ __forceinline__ float quad_sum(float v) {
    v += __shfl_xor_sync(0xffffffffu, v, 1);
    return v + __shfl_xor_sync(0xffffffffu, v, 2);
}
__device__ __forceinline__ void ln_partial(const uint32_t (&v)[8], uint32_t dst, bool writer) {
    float s0 = 0.f, s1 = 0.f;
#pragma unroll
    for (int i = 0; i < 8; i++) {
        s0 += blo(v[i]);
        s1 += bhi(v[i]);
    }
    const float mean = quad_sum(s0 + s1) * (1.0f / 64);
    s0 = s1 = 0.f;
#pragma unroll
    for (int i = 0; i < 8; i++) {
        const float a = blo(v[i]) - mean, b = bhi(v[i]) - mean;
        s0 = fmaf(a, a, s0);
        s1 = fmaf(b, b, s1);
    }
    s0 = quad_sum(s0 + s1);
    if (writer) sts64(dst, __float_as_uint(mean), __float_as_uint(s0));
}
__device__ __forceinline__ void ln_combine(uint32_t src, uint32_t& mean2, float& inv) {
    float m[10], q0 = 0.f, q1 = 0.f, s = 0.f;
#pragma unroll
    for (int i = 0; i < 5; i++) {
        const uint4 v = lds128(src + i * 16);
        m[2 * i] = __uint_as_float(v.x);
        m[2 * i + 1] = __uint_as_float(v.z);
        q0 += __uint_as_float(v.y);
        if (i < 4) q1 += __uint_as_float(v.w);
    }
    const float mean = (((m[0] + m[1]) + (m[2] + m[3])) + ((m[4] + m[5]) + (m[6] + m[7])) + m[8]) * (1.0f / 9);
#pragma unroll
    for (int i = 0; i < 9; i++) s = fmaf(m[i] - mean, m[i] - mean, s);
    const float var = fmaf(s, 64.f, q0 + q1) * (1.0f / DM);
    mean2 = pack2(mean, mean);
    inv = rcp(rbf(sqrt_f(rbf(rbf(var) + 1e-5f))));
}
__device__ __forceinline__ uint32_t modulate2(uint32_t x, uint32_t mean2, float inv, uint32_t shift, uint32_t onep) {
    const uint32_t d = bsub2(x, mean2);
    return badd2(bmul2(pack2(blo(d) * inv, bhi(d) * inv), onep), shift);
}
template <int N>
__device__ __forceinline__ void sum_frags(float (&c)[4], uint32_t addr, int stride) {
#pragma unroll
    for (int w = 0; w < N; w++) {
        const uint4 v = lds128(addr + w * stride);
        c[0] += __uint_as_float(v.x); c[1] += __uint_as_float(v.y);
        c[2] += __uint_as_float(v.z); c[3] += __uint_as_float(v.w);
    }
}

template <int ST>
__device__ __forceinline__ void project(uint32_t sm, const uint32_t* src, uint32_t* dst, uint32_t rowoff, uint32_t reds, int warp, int lane) {
    constexpr int NW = ST ? 9 : 8;
    const uint32_t red = sm + (ST ? OFF_WO : OFF_P);
    if (warp < NW) {
        const uint32_t wbar = sm + OFF_BAR + ((ST ? BAR_WD : BAR_WO) + (warp >> 1)) * 8;
        const uint32_t ab = sm + (ST ? OFF_WD : OFF_WO) + rowoff;
        const uint32_t ax = sm + (ST ? OFF_DX : OFF_OX) + ((rowoff >> 7) << 4);
        uint32_t a[10][4] = {}, b[4] = {};
        bool have_w = false;
        int it = 0;
        do {
            if (!have_w && __all_sync(0xffffffffu, mbar_test(wbar, 0))) {
                have_w = true;
#pragma unroll
                for (int i = 0; i < 10; i++) ldsm4t(a[i], i % 5 < 4 ? (ab ^ ((i % 5) << 5)) + (i / 5) * 2048 : ax + (i / 5) * 256);
            }
            if (ST) fetch<4, 1>(src, 32, b);
            else fetch<1, 4>(src, 0, b);
        } while ((missing(b) | !have_w) & (++it < SPIN_LIMIT));
        if (warp == 0) TSL(ST ? 24 : 21);
        float acc[5][4] = {};
#pragma unroll
        for (int i = 0; i < 10; i++) mma(acc[i % 5], a[i][0], a[i][1], a[i][2], a[i][3], b[2 * (i / 5)], b[2 * (i / 5) + 1]);
#pragma unroll
        for (int u = 0; u < 9; u++)
            sts64(red + u * 2304 + (reds & 0xffff), __float_as_uint(acc[u >> 1][2 * (u & 1)]), __float_as_uint(acc[u >> 1][2 * (u & 1) + 1]));
    }
    bar_sync(3, 288);
    float s[2][2] = {};
#pragma unroll
    for (int w = 0; w < NW; w++) {
        const float2 v = lds64f(red + (reds >> 16) + w * 256);
        s[w & 1][0] += v.x;
        s[w & 1][1] += v.y;
    }
    const uint32_t p0 = (__float_as_uint(s[0][0] + s[1][0]) | 1) ^ ST, p1 = (__float_as_uint(s[0][1] + s[1][1]) | 1) ^ ST;
    st2(dst, p0, p1), st2(dst + 1024, p0, p1);
}

template <int ST>
__device__ __forceinline__ uint32_t reduce16(const uint32_t* src, int lane) {
    uint32_t a[8], bad[4] = {1, 1, 1, 1};
    int it = 0;
#pragma unroll
    for (int i = 0; i < 8; i++) a[i] = 0;
    do {
#pragma unroll
        for (int i = 0; i < 4; i++)
            asm volatile("{\n.reg .pred p;\nsetp.ne.u32 p, %2, 0;\n@p ld.relaxed.gpu.global.v2.b32 {%0,%1}, [%3];\n}"
                         : "+r"(a[2 * i]), "+r"(a[2 * i + 1]) : "r"(bad[i]), "l"(src + i * 64) : "memory");
#pragma unroll
        for (int i = 0; i < 4; i++) bad[i] = (ST ? a[2 * i] | a[2 * i + 1] : ~(a[2 * i] & a[2 * i + 1])) & 1;
    } while (__any_sync(0xffffffffu, (bad[0] | bad[1] | bad[2] | bad[3]) != 0) & (++it < SPIN_LIMIT));
    float s0 = (__uint_as_float(a[0]) + __uint_as_float(a[2])) + (__uint_as_float(a[4]) + __uint_as_float(a[6]));
    float s1 = (__uint_as_float(a[1]) + __uint_as_float(a[3])) + (__uint_as_float(a[5]) + __uint_as_float(a[7]));
#pragma unroll
    for (int o = 8; o < 32; o <<= 1) {
        s0 += __shfl_xor_sync(0xffffffffu, s0, o);
        s1 += __shfl_xor_sync(0xffffffffu, s1, o);
    }
    const uint32_t y = pack2(s0, s1);
    return __byte_perm(y, __shfl_xor_sync(0xffffffffu, y, 4), (lane & 4) ? 0x3276 : 0x5410);
}

__global__ void __launch_bounds__(NTHREADS, 1) fused_kernel(const __grid_constant__ Params P) {
    extern __shared__ __align__(1024) char smem_raw[];
    constexpr uint32_t sm = 1024;
    const int tid = threadIdx.x, lane = tid & 31;
    const int cta = blockIdx.x, grp = cta >> 3, sub = cta & 7;
    const uint32_t bars = sm + OFF_BAR;
    const int row0 = (sub * HKV + grp) * SK + (SK - WIN);
    u64 pol;
    asm volatile("createpolicy.fractional.L2::evict_first.b64 %0, 1.0;" : "=l"(pol));
    if (tid == NCW * 32) {
        TS(0);
        const int n0 = cta < 108 ? 0 : 3;
#pragma unroll
        for (int i = 0; i < 6; i++) mbar_init(bars + i * 8, 1);
        asm volatile("fence.mbarrier_init.release.cluster;" ::: "memory");
#pragma unroll
        for (int i = 0; i < 3; i++) {
            mbar_expect(bars + (n0 + i) * 8, 12288);
            tma3d(sm + OFF_WM + (n0 + i) * 12288, &P.m[cta < 36 ? M_WA : cta < 108 ? M_WM : M_WQ], cta < 36 ? 16 * cta : 32 * cta,
                  i * 192, 0, bars + (n0 + i) * 8);
            TI(n0 + i);
        }
        TS(26);
    }
    if (tid == NCW * 32 + 32) {
#pragma unroll
        for (int i = 0; i < 4; i++) mbar_init(bars + (BAR_FULL + i) * 8, 1);
        asm volatile("fence.mbarrier_init.release.cluster;" ::: "memory");
#pragma unroll
        for (int t = 0; t < NK0; t++) {
            mbar_expect(bars + (BAR_FULL + t) * 8, TILE_BYTES);
            tma3d_hint(sm + OFF_RING + t * TILE_BYTES, &P.m[M_K], 0, row0 + t * 32, 0, bars + (BAR_FULL + t) * 8, pol);
            TI(6 + t);
        }
    }
    if (tid < 288 && cta < 108) {
#pragma unroll
        for (int i = 0; i < 2; i++) {
            const int row = (lane >> 3) + 4 * i, so = row * DM + (tid >> 5) * 64 + (lane & 7) * 8;
            const uint32_t d = sm + OFF_RED + (tid >> 5) * 2048 + row * 128 + (((lane & 7) ^ row) << 4);
            cp16(d, P.c + so);
            if (cta < 36) cp16(d + 1024, P.x + so);
        }
    }
    uint32_t* const g0 = P.scratch;
    const uint32_t epoch = ld1(g0 + G_EPOCH);
    const int warp = __shfl_sync(0xffffffffu, tid >> 5, 0);
    auto pace = [&](int t, int gain) {
        const int d = (int)atomicAdd(g0 + (epoch & 1) * G_SET + G_CNT, 1u) - 32 * (t - 16) - 16;
        sts32(sm + OFF_WIN, min(max((d * gain + 32) >> 6, W_MIN), W_MAX));
    };

    if (warp >= NCW) {
        const int pw = warp - NCW;
        bar_arrive(1, (NCW + 1) * 32);
        if (pw && lane < M_WQ) asm volatile("prefetch.tensormap [%0];" ::"l"(&P.m[M_WQ - lane]) : "memory");
        if (tid == NCW * 32) sts32(sm + OFF_WIN, 0);
        __syncwarp();
        bar_sync(15, NTHREADS);
        if (lane == 0) {
            if (pw == 0 && cta < 108) {
#pragma unroll 1
                for (int n = 3; n < 6; n++) {
                    mbar_expect(bars + n * 8, 12288);
                    mbar_wait(bars + (n - 3) * 8, 0);
                    tma3d(sm + OFF_WM + n * 12288, &P.m[M_WQ], 32 * cta, (n - 3) * 192, 0, bars + n * 8);
                    TI(n);
                }
            }
#pragma unroll 1
            for (int t = (2 - pw) * NK0; t < 2 * NK0 + 3 * (1 - pw); t++) {
                mbar_expect(bars + (BAR_FULL + t) * 8, TILE_BYTES);
                mbar_wait(bars + (t + (pw ? BAR_FULL - NK0 : 3 - 2 * NK0)) * 8, 0);
                tma3d_hint(sm + OFF_RING + t * TILE_BYTES, &P.m[M_K], 0, row0 + t * 32, 0, bars + (BAR_FULL + t) * 8, pol);
                TI(6 + t);
            }
            if (pw == 0) {
#pragma unroll 1
                for (int t = 2 * NK0 + 3; t < 2 * NT; t++) {
                    if (t == 14 && cta < 108) mbar_wait(bars + BAR_WMF * 8, 0);
                    if (t == 15) TS(30);
                    const int m = t - ((W_KV + (int)lds32(sm + OFF_WIN) + ((0xd8 >> (2 * t & 6)) & 3)) >> 2);
                    const uint32_t fb = bars + (BAR_FULL + (t & 15)) * 8;
                    mbar_wait(fb + (BAR_EMPTY - BAR_FULL) * 8, (~t >> 4) & 1);
                    mbar_expect(fb, TILE_BYTES);
                    mbar_wait(bars + (BAR_FULL + (m & 15)) * 8, (m >> 4) & 1);
                    tma3d_hint(sm + OFF_RING + (t & 15) * TILE_BYTES, &P.m[t >> 6], 0, row0 + (t & (NT - 1)) * 32, 0, fb, pol);
                    TI(6 + t);
                    if (t == T_CLEAR || t == T_STRIP) mbar_arrive(bars + (t == T_CLEAR ? BAR_SYNC + 1 : BAR_X + 1) * 8);
                }
                mbar_arrive(bars + (BAR_SYNC + 2) * 8);
                mbar_wait(bars + BAR_SYNC * 8, 0);
                auto window = [&](int b, int w) {
                    b -= max((w + (int)lds32(sm + OFF_WIN) + ((0xd8 >> (2 * b & 6)) & 3)) >> 2, 1);
                    b = min(b, BAR_GU + B_CAP);
                    mbar_wait(bars + b * 8, b < BAR_WO);
                };
#pragma unroll 1
                for (int i = 0; i < 4; i++) {
                    window(BAR_WO + i, W_WO);
                    tma3d(sm + OFF_WO + i * 8192, &P.m[M_OD], 64 * sub, grp * 256 + i * 64, P.zo, bars + (BAR_WO + i) * 8);
                    TI(134 + i);
                }
                TS(28);
#pragma unroll 1
                for (int i = 0; i < 9; i++) {
                    mbar_wait(bars + (BAR_EMPTY + i) * 8, 1);
                    window(BAR_GU + i, W_GU);
                    tma3d(sm + OFF_GU + i * 8192, &P.m[M_GU], grp * 288 + 32 * sub, i * 64, 0, bars + (BAR_GU + i) * 8);
                    TI(138 + i);
                }
                TS(29);
#pragma unroll 1
                for (int i = 0; i < 5; i++) {
                    const int r = min(i * 64, 224);
                    mbar_wait(bars + (BAR_EMPTY + 9 + i) * 8, 1);
                    window(BAR_WD + i, W_WD);
                    tma3d(sm + OFF_WD + r * 128, &P.m[M_OD], 64 * sub, grp * 288 + r, P.zo ^ 1, bars + (BAR_WD + i) * 8);
                    TI(147 + i);
                }
            } else {
                mbar_wait(bars + (BAR_X + 1) * 8, 0);
#pragma unroll 1
                for (int i = 0; i < (sub < 4 ? X_NS : min(X_NS, 4)); i++) {
                    const int r = (i & 1) * (i < 2 ? 112 : 144);
                    if (i >= 4 || i == 0) mbar_expect(bars + BAR_X * 8, i < 4 ? 9216 : 6144);
                    if (i < 4) tma3d(sm + OFF_OX + (i >> 1) * 4096 + r * 16, &P.m[M_OX], 512 + 8 * sub, grp * (i < 2 ? 256 : 288) + r, P.zo ^ (i >> 1), bars + BAR_X * 8);
                    else tma3d(sm + OFF_GX + (i - 4) * 6144, &P.m[M_GX], grp * 288 + 256 + 8 * sub, (i - 4) * 192, 0, bars + BAR_X * 8);
                    TI(152 + i);
                    if (i >= 3) mbar_wait(bars + BAR_X * 8, ~i & 1);
                }
#pragma unroll 1
                for (int i = 0; i < 18; i++) mbar_expect(bars + (BAR_WO + i) * 8, 8192);
                mbar_arrive(bars + BAR_SYNC * 8);
                mbar_wait(bars + (BAR_SYNC + 2) * 8, 0);
#pragma unroll 1
                for (int t = 124 + (cta & 3); t < 144; t += 4) {
                    mbar_wait(bars + (BAR_FULL - 112 + t) * 8, t < 128);
                    pace(t, GAIN_TAIL);
                }
            }
        }
        return;
    }

    if (lane == 0) {
#pragma unroll
        for (int i = 0; i < 6; i++) mbar_init(bars + (10 + warp * 6 + i) * 8, 1);
        asm volatile("fence.mbarrier_init.release.cluster;" ::: "memory");
    }
    __syncwarp();
    if (warp < 9) bar_arrive(15, NTHREADS);
    const int g = lane >> 2, t4 = lane & 3;
    uint32_t* const gs = g0 + (epoch & 1) * G_SET;

    if (warp < 9) {
        const int off_h = (cta < 36 ? dual(D_H + 2 * cta * 32) : G_M + 4 * (cta - 36) * 32) + tid;
        const int off_h2 = off_h + (cta < 36 ? 1024 : 64);
        const int off_q = dual(D_Q + g * (HQ * 64) + cta * 16) + warp * 8 + t4 * 2;
        uint32_t bf[8] = {}, xp = 0, mean2 = 0;
        float inv = 0.f;
        if (cta < 36) xp = __ldg(reinterpret_cast<const uint32_t*>(P.x) + g * (DM / 2) + 8 * cta + 4 * (warp & 1) + t4);
        if (warp < 2) {
#pragma unroll
            for (int pg = 0; pg < 2 * G_SET; pg += G_SET) {
                st2(g0 + pg + off_q, 0, 0), st2(g0 + pg + off_q + 1024, 0, 0);
                if (cta < 108) st1(g0 + pg + off_h, 0), st1(g0 + pg + off_h2, 0);
            }
        }
        if (cta < 108) {
            asm volatile("cp.async.wait_all;" ::: "memory");
            __syncwarp();
            const uint32_t fa = sm + OFF_RED + warp * 2048 + (lane & 7) * 128 + (((lane >> 3) ^ (lane & 7)) << 4);
            ldsm4(reinterpret_cast<uint32_t(&)[4]>(bf[0]), fa);
            ldsm4(reinterpret_cast<uint32_t(&)[4]>(bf[4]), fa ^ 64);
            if (cta < 36) {
                uint32_t xv[8];
                ldsm4(reinterpret_cast<uint32_t(&)[4]>(xv[0]), fa + 1024);
                ldsm4(reinterpret_cast<uint32_t(&)[4]>(xv[4]), (fa ^ 64) + 1024);
                ln_partial(xv, sm + OFF_ST + g * 80 + warp * 8, t4 == 0);
            }
#pragma unroll
            for (int i = 0; i < 8; i++) bf[i] = silu2(bf[i]);
        }
        if (warp == 0) TSL(18);
        bar_sync(1, (NCW + 1) * 32);
        if (cta < 36 && warp < 2) ln_combine(sm + OFF_ST + g * 80, mean2, inv);
        const int r = warp * 64 + (lane >> 4) * 8 + (lane & 7), hi8 = (lane >> 3) & 1, box = warp / 3;
#pragma unroll 1
        for (int pass = cta < 108 ? 0 : 1; pass < 2; pass++) {
            const bool pa = pass == 0 && cta < 36;
            const uint32_t ab = sm + OFF_WM + pass * 36864 +
                                (pa ? (box + hi8) * 6144 + r * 32 + ((lane & 4) << 2) : r * 64 + (((2 * hi8) ^ ((r >> 1) & 3)) << 4));
            const uint32_t as = pa ? 512 : 1024, red = sm + OFF_RED + pass * 9216;
            mbar_wait(bars + (pass * 3 + box) * 8, 0);
            if (warp == 8) TSL(pass ? 31 : 19);
            uint32_t a[4][2][4];
#pragma unroll
            for (int i = 0; i < 4; i++) {
                ldsm4t(a[i][0], ab + i * as);
                ldsm4t(a[i][1], (ab ^ 16) + i * as);
            }
            if (pass) {
                bar_sync(8, NCW * 32);
#pragma unroll
                for (int i = 0; i < 8; i++) bf[i] = 0;
                get<8, 1>(gs + near(D_H + warp * 256, lds32(sm + OFF_WIN + 4)) + lane, 32, bf);
                if (warp == 0) TSL(3);
            }
            float acc[2][4] = {};
#pragma unroll
            for (int i = 0; i < 4; i++)
#pragma unroll
                for (int m = 0; m < 2; m++) mma(acc[m], a[i][m][0], a[i][m][1], a[i][m][2], a[i][m][3], bf[2 * i], bf[2 * i + 1]);
            sts128f(red + tid * 16, acc[0]);
            sts128f(red + 4608 + tid * 16, acc[1]);
            bar_sync(3, 288);
            if (warp < 2) {
                float c[4] = {};
                sum_frags<9>(c, red + warp * 4608 + lane * 16, 512);
                uint32_t lo = movm(pack2(c[0], c[1])), hi = movm(pack2(c[2], c[3]));
                if (pass) {
                    put2d(gs + off_q, lo, hi);
                    if (warp == 0) TSL(4);
                } else {
                    const uint32_t hi1 = badd2(hi, ONE2);
                    if (pa) hi = lo = modulate2(xp, mean2, inv, lo, hi1);
                    if (cta >= 72 && cta < 90) lo = badd2(lo, ONE2), hi = hi1;
                    st1(gs + off_h, nz(lo));
                    st1(gs + off_h2, nz(hi));
                    if (warp == 0 && pa) TSL(2);
                }
            } else if (tid == 64 && pass == 0) {
                mbar_arrive(bars + BAR_WMF * 8);
            }
        }
    } else {
        if ((uint32_t)__cvta_generic_to_shared(smem_raw) != sm) __trap();
        uint32_t* const ping = g0 + dual(D_PING) + cta * 8;
        if (lane < 16) st1(ping + (lane >> 3) * 1024 + (lane & 7), 0);
        bar_sync(15, NTHREADS);
        uint32_t best[2] = {~0u, ~0u}, v = 0;
#pragma unroll 1
        for (int part = 0; part < 2; part++) {
            if (lane == 0) {
#pragma unroll 1
                for (int r = part ? NPING1 : NPING0; r > 0; r--) {
#pragma unroll
                    for (int k = 0; k < 2; k++) {
                        const uint32_t t0 = clock32(v);
                        v = atomicExch(ping + k * 1024, t0);
                        best[k] = min(best[k], clock32(v) - t0);
                    }
                }
                sts32(sm + OFF_WIN + 4 + 4 * part, ((best[1] < best[0]) ^ __popc(D_PING & 0x16400)) & 1);
            }
            __syncwarp();
            if (part) break;
            TSL(20);
            bar_arrive(8, NCW * 32);
            mbar_wait(bars + 5 * 8, 0);
            uint32_t a[4] = {};
            get<1, 4>(gs + near(D_Q + (sub * HQ + 2 * grp) * 64, lds32(sm + OFF_WIN + 4)) + lane * 4, 0, a);
            sts128(sm + OFF_QS + lane * 16, a[0], a[1], a[2], a[3]);
            __syncwarp();
            TSL(5);
            bar_arrive(4, 288);
        }
#pragma unroll
        for (int i = lane; i < 72; i += 32) cp16(sm + OFF_WR + i * 16, P.wr + i * 8);
        asm volatile("cp.async.wait_all;" ::: "memory");
        __syncwarp();
        bar_arrive(2, NCW * 32);
        if (cta == 0 && lane == 0) st1(g0 + (~epoch & 1) * G_SET + G_CNT, 0);
        mbar_wait(bars + (BAR_SYNC + 1) * 8, 0);
#pragma unroll 1
        for (int c = 0; c < 4; c++) {
            uint32_t* const pg = g0 + (c >> 1) * G_SET + (c & 1) * 1024;
            zero4(pg + dual(D_O + cta * 128) + lane * 4);
            zero4(pg + dual(D_ACT + (grp * 36 + 4 * sub) * 32) + lane * 4);
            if (lane < 8 ? sub < 4 : lane < 16 && cta < 72)
                zero4(pg + dual(lane < 8 ? D_ACT + (grp * 36 + 32 + sub) * 32 : D_X1 + cta * 32) + (lane & 7) * 4);
        }
#pragma unroll 1
        for (int u = 0; u < 9; u++) zero4(g0 + dual(d_part(u < 8 ? 8 * sub + u : 64 + sub)) + (lane >> 4) * 1024 + grp * 64 + (lane & 15) * 4);
        __syncwarp();
        bar_arrive(5, NCW * 32);
        return;
    }

    const uint32_t tile = sm + OFF_RING + warp * TILE_BYTES;
    const uint32_t fullb = bars + (BAR_FULL + warp) * 8;
    const uint32_t pw = sm + OFF_P + warp * (2 * P_PITCH);
    const bool pacer = (tid & 127) == (cta & 3) * 32;
    if (warp < 8) {
        {
            uint32_t q0[8], q1[8];
            bar_sync(4, 288);
#pragma unroll
            for (int i = 0; i < 8; i++) {
                const float2 v = lds64f(sm + OFF_QS + (g & 1) * 256 + i * 32 + t4 * 8);
                q0[i] = __float_as_uint(v.x), q1[i] = __float_as_uint(v.y);
            }
            uint32_t sp = pw + (t4 & 1) * P_PITCH + ((t4 >> 1) * 8 + g) * 2;
#pragma unroll 1
            for (int it = 0; it < 8; it++, sp += 64) {
                const uint32_t ab = tile + (it & 1) * (8 * TILE_BYTES) + (lane & 15) * 128 + (((lane >> 4) ^ (lane & 7)) << 4);
                mbar_wait(fullb + (it & 1) * 64, (it >> 1) & 1);
                float acc[2][2][4] = {};
#pragma unroll
                for (int ks = 0; ks < 8; ks++)
#pragma unroll
                    for (int m = 0; m < 2; m++) {
                        uint32_t a[4];
                        ldsm4(a, (ab ^ ((ks & 3) << 5)) + (ks >> 2) * 4096 + m * 2048);
                        mma(acc[m][ks & 1], a[0], a[1], a[2], a[3], (ks & 1) ? q1[ks - 1] : q0[ks], (ks & 1) ? q1[ks] : q0[ks + 1]);
                    }
                __syncwarp();
                if (lane == 0) mbar_arrive(fullb + (it & 1) * 64 + (BAR_EMPTY - BAR_FULL) * 8);
#pragma unroll
                for (int m = 0; m < 2; m++) {
                    const float s = sel4(acc[m][0], t4) + sel4(acc[m][1], t4);
                    sts16(sp + m * 32, (uint16_t)pack2(rbf(s) * 0.08838834764831845f, 0.f));
                }
                if (pacer && it >= 2) pace(it * 8 + warp, GAIN_KV);
                __syncwarp();
            }
        }
        __syncwarp();
        if (warp == 7) TSL(6);
        const uint32_t pa = pw + (lane >> 4) * P_PITCH + (lane & 15) * 32;
        const uint32_t sa = sm + OFF_SM + (lane >> 4) * 64;
        const uint4 v0 = lds128(pa), v1 = lds128(pa + 16);
        const uint32_t sv[8] = {v0.x, v0.y, v0.z, v0.w, v1.x, v1.y, v1.z, v1.w};
        float e[16];
        float m = -INFINITY;
#pragma unroll
        for (int i = 0; i < 8; i++) {
            e[2 * i] = blo(sv[i]);
            e[2 * i + 1] = bhi(sv[i]);
            m = fmaxf(m, fmaxf(e[2 * i], e[2 * i + 1]));
        }
#pragma unroll
        for (int o = 8; o; o >>= 1) m = fmaxf(m, __shfl_xor_sync(0xffffffffu, m, o));
        float l = 0.f;
#pragma unroll
        for (int i = 0; i < 16; i++) {
            e[i] = ex2((e[i] - m) * LOG2E);
            l += e[i];
        }
#pragma unroll
        for (int o = 8; o; o >>= 1) l += __shfl_xor_sync(0xffffffffu, l, o);
        if ((lane & 15) == 0) sts64(sa + warp * 8, __float_as_uint(m), __float_as_uint(l));
        bar_sync(2, NCW * 32);
        const float2 v = lds64f(sa + (lane & 7) * 8);
        float M = v.x;
#pragma unroll
        for (int o = 4; o; o >>= 1) M = fmaxf(M, __shfl_xor_sync(0xffffffffu, M, o));
        float L = v.y * ex2((v.x - M) * LOG2E);
#pragma unroll
        for (int o = 4; o; o >>= 1) L += __shfl_xor_sync(0xffffffffu, L, o);
        const float sc = ex2((m - M) * LOG2E) * rcp(L);
        sts128(pa, pack2(e[0] * sc, e[1] * sc), pack2(e[2] * sc, e[3] * sc), pack2(e[4] * sc, e[5] * sc), pack2(e[6] * sc, e[7] * sc));
        sts128(pa + 16, pack2(e[8] * sc, e[9] * sc), pack2(e[10] * sc, e[11] * sc), pack2(e[12] * sc, e[13] * sc), pack2(e[14] * sc, e[15] * sc));
        __syncwarp();
    } else {
        bar_sync(2, NCW * 32);
    }

    const bool reducer = cta < 72 && warp < 4;
    const int rbat = 2 * t4 + (g & 1);
    uint32_t sh[8] = {}, op[8] = {}, rx = 0, rg[2] = {};
    {
        const uint32_t* const src_m = gs + G_M + (72 + warp * 8) * 32 + lane;
        fetch<8, 1>(src_m + 72 * 32, 32, op);
        if (reducer) {
            rx = __ldg(reinterpret_cast<const uint32_t*>(P.x) + rbat * (DM / 2) + 4 * cta + warp);
            get<2, 1>(gs + G_M + cta * 32 + rbat * 4 + warp, 216 * 32, rg);
        }
        get<8, 1>(src_m, 32, sh);
        get<8, 1>(src_m + 72 * 32, 32, op);
    }
    const int side = lds32(sm + OFF_WIN + 8), set = (epoch & 1) * G_SET, rr = (lane >> 4) * 8 + (lane & 7);
    const uint32_t dst_o = pin(4 * (set + dual(D_O + cta * 128) + (tid & 0x70) + (tid & 3) * 4 + ((tid >> 2) & 3)));
    const uint32_t src_o = pin(4 * (set + near(D_O + grp * 1024, side) + g * 128 + warp * 16 + t4 * 4));
    const uint32_t dst_p = pin(4 * (dual(d_part(warp < 8 ? 8 * sub + warp : 64 + sub)) + grp * 64 + lane * 2));
    const uint32_t src_p = pin(4 * (near(d_part(cta), side) + (lane >> 3) * 256 + 16 * warp + (lane & 7) * 2));
    const uint32_t dst_x = pin(4 * (set + dual(D_X1 + cta * 32) + (lane >> 3) * 1024 + warp * 8 + (lane & 7)));
    const uint32_t src_x = pin(4 * (set + near(D_X1 + warp * 256, side) + t4 * 8 + (g & 1) * 4 + (g >> 1)));
    const uint32_t dst_a = pin(4 * (set + dual(D_ACT + (grp * 36 + (warp < 4 ? 4 * sub + warp : 32 + sub)) * 32) + lane));
    const uint32_t src_a = pin(4 * (set + near(D_ACT + (grp * 36 + 4 * warp) * 32, side) + lane));
    const uint32_t dst_out = pin(4 * (rbat * (DM / 2) + 4 * cta + warp));
    const uint32_t rowoff = pin((warp * 32 + rr) * 128 + ((((lane >> 3) & 1) ^ (lane & 7)) << 4));
    const uint32_t reds = pin((tid * 8) | (warp * 2304 + lane * 8) << 16);
    const uint32_t ored = pin((warp * 1088 + (t4 & 1) * 576 + ((t4 >> 1) * 8 + g) * 4) | ((tid >> 6) * 64 + tid * 8) << 16);

    if (warp < 8) {
        float acc[8][4] = {};
        uint32_t pp = pw + (lane & 1) * P_PITCH + (lane >> 3) * 16;
#pragma unroll 1
        for (int it = 0; it < 8; it++, pp += 64) {
            const uint32_t ab = tile + (it & 1) * (8 * TILE_BYTES) + ((lane & 7) + (lane >> 4) * 8) * 128 + ((((lane >> 3) & 1) ^ (lane & 7)) << 4);
            uint32_t pb[4];
            ldsm4(pb, pp);
            mbar_wait(fullb + (it & 1) * 64, (it >> 1) & 1);
#pragma unroll
            for (int ks = 0; ks < 2; ks++)
#pragma unroll
                for (int m = 0; m < 8; m++) {
                    uint32_t a[4];
                    ldsm4t(a, (ab ^ ((m & 3) << 5)) + (m >> 2) * 4096 + ks * 2048);
                    mma(acc[m], a[0], a[1], a[2], a[3], pb[2 * ks], pb[2 * ks + 1]);
                }
            __syncwarp();
            if (lane == 0) mbar_arrive(fullb + (it & 1) * 64 + (BAR_EMPTY - BAR_FULL) * 8);
            if (pacer && it * 8 + warp < NT - 4) pace(NT + it * 8 + warp, GAIN_KV);
            __syncwarp();
        }
        if (warp == 7) TSL(7);
        const uint32_t ra = sm + OFF_ORED + (ored & 0xffff);
#pragma unroll
        for (int m = 0; m < 8; m++) sts32(ra + m * 64, __float_as_uint(sel4(acc[m], t4)));
    }
    bar_sync(5, NCW * 32);
    if (warp < 4) {
        float s[2][2] = {};
#pragma unroll
        for (int w = 0; w < 8; w++) {
            const float2 v = lds64f(sm + OFF_ORED + w * 1088 + (ored >> 16));
            s[w & 1][0] += v.x;
            s[w & 1][1] += v.y;
        }
        put1d(at(g0, dst_o), pack2(s[0][0] + s[1][0], s[0][1] + s[1][1]));
        if (warp == 0) TSL(8);
    }

    project<0>(sm, at(g0, src_o), at(g0, dst_p), rowoff, reds, warp, lane);
    if (warp == 0) TSL(9);
    if (reducer) {
        rx = badd2(rx, bmul2(rg[0], reduce16<0>(at(g0, src_p), lane)));
        if (lane < 16) st1(at(g0, dst_x), nz(rx));
        if (warp == 0) TSL(10);
    }

    const uint32_t gbar = bars + (BAR_GU + warp) * 8;
    const int pl = ((lane >> 3) & 1) ^ P.zg;
    const uint32_t ab = sm + OFF_GU + warp * 8192 + pl * 4096 + rr * 64 + ((lane & 6) << 3);
    const uint32_t ax = sm + OFF_GX + (warp / 3 + pl) * 3072 + (warp * 64 + rr) * 16;
    uint32_t a[20][4] = {}, h[8] = {};
    auto load_gu = [&]() {
#pragma unroll
        for (int i = 0; i < 20; i++) ldsm4t(a[i], i % 5 < 4 ? (ab ^ ((i % 5) << 4)) + (i / 5) * 1024 : ax + (i / 5) * 256);
    };
    bool gpre = false;
    {
        int it = 0;
        do {
            if (!gpre && __all_sync(0xffffffffu, mbar_test(gbar, 0))) gpre = true, load_gu();
            fetch<8, 1>(at(g0, src_x), 32, h);
        } while (missing(h) & (++it < SPIN_LIMIT));
    }
    if (warp == 0) TSL(11);
    ln_partial(h, sm + OFF_ST + g * 80 + warp * 8, t4 == 0);
    bar_sync(3, 288);
    {
        uint32_t mean2;
        float inv;
        ln_combine(sm + OFF_ST + g * 80, mean2, inv);
#pragma unroll
        for (int i = 0; i < 8; i++) h[i] = modulate2(h[i], mean2, inv, sh[i], op[i]);
    }
    if (warp == 0) TSL(12);
    if (!gpre) {
        mbar_wait(gbar, 0);
        load_gu();
    }
    if (warp == 8) TSL(17);
    {
        float acc[5][4] = {};
#pragma unroll
        for (int i = 0; i < 20; i++) mma(acc[i % 5], a[i][0], a[i][1], a[i][2], a[i][3], h[2 * (i / 5)], h[2 * (i / 5) + 1]);
#pragma unroll
        for (int m = 0; m < 5; m++) sts128f(sm + OFF_RED + m * 4608 + 2 * (reds & 0xffff), acc[m]);
    }
    bar_sync(3, 288);
    if (warp < 5) {
        float c[4] = {};
        sum_frags<9>(c, sm + OFF_RED + 2 * (reds >> 16), 512);
        const uint32_t w = movm(bmul2(silu2(pack2(c[0], c[1])), pack2(c[2], c[3])));
        if (warp < 4 || sub < 4) put1d(at(g0, dst_a), w);
        if (warp == 1) TSL(13);
    }
    if (cta < 72) {
        float r = 0.f;
#pragma unroll
        for (int i = 0; i < 8; i++) {
            const uint32_t wr = lds32(sm + OFF_WR + (warp * 32 + i * 4 + t4) * 4);
            r = fmaf(blo(h[i]), blo(wr), fmaf(bhi(h[i]), bhi(wr), r));
            if (warp * 8 + i == cta) sts32(sm + OFF_HU + lane * 4, h[i]);
        }
        r = quad_sum(r);
        if (t4 == 0) sts32(sm + OFF_RT + g * 48 + warp * 4, __float_as_uint(r));
    }

    project<1>(sm, at(g0, src_a), at(g0, dst_p), rowoff, reds, warp, lane);
    if (warp == 0) TSL(14);
    if (reducer) {
        const uint4 r0 = lds128(sm + OFF_RT + rbat * 48), r1 = lds128(sm + OFF_RT + rbat * 48 + 16);
        float r = __uint_as_float(lds32(sm + OFF_RT + rbat * 48 + 32));
        r += ((__uint_as_float(r0.x) + __uint_as_float(r0.y)) + (__uint_as_float(r0.z) + __uint_as_float(r0.w))) +
             ((__uint_as_float(r1.x) + __uint_as_float(r1.y)) + (__uint_as_float(r1.z) + __uint_as_float(r1.w)));
        r = sigmoid_f(rbf(r));
        const uint32_t rh = lds32(sm + OFF_HU + (rbat * 4 + warp) * 4);
        const uint32_t y = badd2(rh, bmul2(reduce16<1>(at(g0, src_p), lane), pack2(r, r)));
        if (lane < 8) *at(reinterpret_cast<uint32_t*>(P.out), dst_out) = badd2(rx, bmul2(rg[1], y));
        if (cta == 0 && tid == 0) g0[G_EPOCH] = epoch + 1;
        if (warp == 0) TSL(15);
    }
}

typedef CUresult (*EncodeFn)(CUtensorMap*, CUtensorMapDataType, cuuint32_t, void*, const cuuint64_t*, const cuuint64_t*,
                             const cuuint32_t*, const cuuint32_t*, CUtensorMapInterleave, CUtensorMapSwizzle,
                             CUtensorMapL2promotion, CUtensorMapFloatOOBfill);

void make_map(EncodeFn enc, CUtensorMap* m, void* p, int cols, int rows, int pitch, int bc, int br, int bp, int planes, size_t pstride,
              CUtensorMapSwizzle sw, int promo) {
    cuuint64_t dims[3] = {(cuuint64_t)cols, (cuuint64_t)rows, (cuuint64_t)planes};
    cuuint64_t strides[2] = {(cuuint64_t)pitch * 2, (cuuint64_t)pstride};
    cuuint32_t box[3] = {(cuuint32_t)bc, (cuuint32_t)br, (cuuint32_t)bp};
    cuuint32_t es[3] = {1, 1, 1};
    enc(m, CU_TENSOR_MAP_DATA_TYPE_BFLOAT16, 3, p, dims, strides, box, es, CU_TENSOR_MAP_INTERLEAVE_NONE, sw,
        (CUtensorMapL2promotion)promo, CU_TENSOR_MAP_FLOAT_OOB_FILL_NONE);
}

}

extern "C" void kernel_launch(void* const* d_in, const int* in_sizes, int n_in, void* d_out, int out_size) {
    static EncodeFn enc = nullptr;
    static uint32_t* scratch = nullptr;
    if (!enc) {
        void* fn = nullptr;
        cudaDriverEntryPointQueryResult st;
        cudaGetDriverEntryPoint("cuTensorMapEncodeTiled", &fn, cudaEnableDefault, &st);
        enc = (EncodeFn)fn;
        cudaGetSymbolAddress(&fn, g_scratch);
        scratch = (uint32_t*)(((uintptr_t)fn + 8 * G_SET - 1) & ~(uintptr_t)(8 * G_SET - 1));
        cudaFuncSetAttribute(fused_kernel, cudaFuncAttributeMaxDynamicSharedMemorySize, SMEM_BYTES);
    }
    Params P;
    const CUtensorMapSwizzle none = CU_TENSOR_MAP_SWIZZLE_NONE;
    make_map(enc, &P.m[M_K], d_in[1], 64, NB * HKV * SK, DH, 64, 32, 2, 2, 128, CU_TENSOR_MAP_SWIZZLE_128B, PROMO_KV);
    make_map(enc, &P.m[M_V], d_in[2], 64, NB * HKV * SK, DH, 64, 32, 2, 2, 128, CU_TENSOR_MAP_SWIZZLE_128B, PROMO_KV);
    make_map(enc, &P.m[M_WQ], d_in[3], HQ * DH, DM, HQ * DH, 32, 192, 1, 1, 16, CU_TENSOR_MAP_SWIZZLE_64B, PROMO_W);
    make_map(enc, &P.m[M_WM], d_in[11], 6 * DM, DM, 6 * DM, 32, 192, 1, 1, 16, CU_TENSOR_MAP_SWIZZLE_64B, PROMO_W);
    make_map(enc, &P.m[M_WA], d_in[11], DM, DM, 6 * DM, 16, 192, 2, 2, DM * 2, CU_TENSOR_MAP_SWIZZLE_32B, PROMO_W);
    char *wg = (char*)d_in[7], *wu = (char*)d_in[8], *wo = (char*)d_in[4], *wd = (char*)d_in[9];
    P.zg = wg > wu;
    P.zo = wo > wd;
    const size_t sg = P.zg ? wg - wu : wu - wg, so = P.zo ? wo - wd : wd - wo;
    make_map(enc, &P.m[M_GU], P.zg ? wu : wg, FF, DM, FF, 32, 64, 2, 2, sg, CU_TENSOR_MAP_SWIZZLE_64B, PROMO_GU);
    make_map(enc, &P.m[M_GX], P.zg ? wu : wg, FF, DM, FF, 8, 192, 2, 2, sg, none, PROMO_GX);
    make_map(enc, &P.m[M_OD], P.zo ? wd : wo, DM, FF, DM, 64, 64, 1, 2, so, CU_TENSOR_MAP_SWIZZLE_128B, PROMO_W);
    make_map(enc, &P.m[M_OX], P.zo ? wd : wo, DM, FF, DM, 8, 144, 1, 2, so, none, PROMO_OX);
    P.x = (const __nv_bfloat16*)d_in[0];
    P.wr = (const __nv_bfloat16*)d_in[6];
    P.c = (const __nv_bfloat16*)d_in[10];
    P.out = (__nv_bfloat16*)d_out;
    P.scratch = scratch;
    fused_kernel<<<NCTA, NTHREADS, SMEM_BYTES>>>(P);
}
```

```cpp
#include <cuda_runtime.h>
#include <cuda_bf16.h>
#include <cuda.h>
#include <stdint.h>

typedef unsigned long long u64;

#define W_KV 20
#define W_WO 20
#define W_GU 18
#define W_WD 14
#define W_MIN -8
#define W_MAX 8
#define GAIN_KV 2
#define GAIN_TAIL 3
#define NK0 2
#define T_STRIP 96
#define T_CLEAR 112
#define X_NS 7
#define B_CAP 8
#define NPING0 4
#define NPING1 16
#define PROMO_W CU_TENSOR_MAP_L2_PROMOTION_L2_128B
#define PROMO_GX 0
#define PROMO_OX 2
#define PROMO_GU 2
#define PROMO_KV CU_TENSOR_MAP_L2_PROMOTION_L2_256B

namespace {

constexpr int NB = 8, DM = 576, HQ = 32, HKV = 16, SK = 8192, WIN = 2048, DH = 128, FF = 4608;
constexpr int NCTA = 128;
constexpr int NCW = 10;
constexpr int NTHREADS = (NCW + 2) * 32;
constexpr int TILE_BYTES = 8192, NSLOT = 16, NT = 64;
constexpr int SPIN_LIMIT = 1 << 22;

constexpr int OFF_RING = 0;
constexpr int OFF_WM = 121856;
constexpr int OFF_WQ = OFF_WM + 36864;
constexpr int OFF_GU = 0;
constexpr int OFF_WD = 73728;
constexpr int OFF_OX = 131072;
constexpr int OFF_DX = OFF_OX + 4096;
constexpr int OFF_GX = OFF_DX + 4608;
constexpr int OFF_WO = OFF_WQ;
constexpr int OFF_P = OFF_WQ + 36864;
constexpr int P_PITCH = 528;
constexpr int OFF_RED = OFF_P + 16 * P_PITCH;
constexpr int OFF_ORED = OFF_RED + 5 * 4608 - 8704;
constexpr int OFF_ST = OFF_RED + 5 * 4608;
constexpr int OFF_SM = OFF_ST + 640;
constexpr int OFF_RT = OFF_SM + 128;
constexpr int OFF_HU = OFF_RT + 384;
constexpr int OFF_QS = OFF_HU + 128;
constexpr int OFF_WR = OFF_QS + 512;
constexpr int OFF_WIN = OFF_WR + 1152;
constexpr int OFF_BAR = OFF_WIN + 16;
constexpr int BAR_FULL = 6, BAR_WO = 22, BAR_GU = 26, BAR_WD = 35, BAR_EMPTY = 40, BAR_SYNC = 56, BAR_WMF = 59, BAR_X = 60, NBAR = 70;
constexpr int SMEM_BYTES = OFF_BAR + NBAR * 8;

constexpr int D_X1 = 0;
constexpr int D_O = 3072;
constexpr int D_ACT = D_O + 512 * 32;
constexpr int D_H = D_ACT + 576 * 32;
constexpr int D_Q = D_H + 3072;
constexpr int G_M = 2 * (D_Q + NB * HQ * 64);
constexpr int G_CNT = G_M + 288 * 32;
constexpr int G_SET = 1 << 18;
__device__ __forceinline__ int d_part(int unit) { return (64 + unit + (unit & 64)) * 1024; }
constexpr int D_PING = 200 * 1024;
constexpr int G_EPOCH = 201 * 2048;
static_assert(G_CNT < 64 * 2048, "scratch layout");
__device__ uint32_t g_scratch[4 * G_SET];
__device__ __forceinline__ int dual(int w) { return w + (w & ~1023); }
__device__ __forceinline__ int near(int w, int side) { return dual(w) + (((__popc(w & 0x16400) ^ side) & 1) << 10); }

#define TI(i)
#define TS(i)
#define TSL(i)

enum { M_K, M_V, M_GU, M_GX, M_OD, M_OX, M_WQ, M_WM, M_WA, NMAP };
struct Params {
    CUtensorMap m[NMAP];
    const __nv_bfloat16 *x, *c, *wr;
    __nv_bfloat16* out;
    uint32_t* scratch;
    int zg, zo;
};

__device__ __forceinline__ void mbar_init(uint32_t bar, int cnt) {
    asm volatile("mbarrier.init.shared::cta.b64 [%0], %1;" ::"r"(bar), "r"(cnt));
}
__device__ __forceinline__ void mbar_expect(uint32_t bar, uint32_t bytes) {
    asm volatile("mbarrier.arrive.expect_tx.shared::cta.b64 _, [%0], %1;" ::"r"(bar), "r"(bytes) : "memory");
}
__device__ __forceinline__ void mbar_arrive(uint32_t bar) {
    asm volatile("mbarrier.arrive.shared::cta.b64 _, [%0];" ::"r"(bar) : "memory");
}
__device__ __forceinline__ void mbar_wait(uint32_t bar, uint32_t parity) {
    asm volatile("{\n.reg .pred p;\n.reg .u32 c;\n"
                 "mbarrier.try_wait.parity.shared::cta.b64 p, [%0], %1;\n@p bra DONE;\nmov.u32 c, %2;\n"
                 "AGAIN:\nmbarrier.try_wait.parity.shared::cta.b64 p, [%0], %1;\nsub.u32 c, c, 1;\n"
                 "setp.eq.or.u32 p, c, 0, p;\n@!p bra AGAIN;\nDONE:\n}"
                 ::"r"(bar), "r"(parity), "n"(SPIN_LIMIT) : "memory");
}
__device__ __forceinline__ bool mbar_test(uint32_t bar, uint32_t parity) {
    uint32_t ok;
    asm volatile("{\n.reg .pred p;\nmbarrier.test_wait.parity.shared::cta.b64 p, [%1], %2;\nselp.u32 %0, 1, 0, p;\n}"
                 : "=r"(ok) : "r"(bar), "r"(parity) : "memory");
    return ok;
}
__device__ __forceinline__ void mbar_wait_lanes(uint32_t bar) {
    mbar_wait(bar, 0);
    __syncwarp();
}
__device__ __forceinline__ void tma3d_hint(uint32_t dst, const CUtensorMap* m, int x, int y, int z, uint32_t bar, u64 pol) {
    asm volatile("cp.async.bulk.tensor.3d.shared::cluster.global.mbarrier::complete_tx::bytes.L2::cache_hint"
                 " [%0], [%1, {%2, %3, %4}], [%5], %6;"
                 ::"r"(dst), "l"(m), "r"(x), "r"(y), "r"(z), "r"(bar), "l"(pol) : "memory");
}
__device__ __forceinline__ void tma3d(uint32_t dst, const CUtensorMap* m, int x, int y, int z, uint32_t bar) {
    asm volatile("cp.async.bulk.tensor.3d.shared::cluster.global.mbarrier::complete_tx::bytes [%0], [%1, {%2, %3, %4}], [%5];"
                 ::"r"(dst), "l"(m), "r"(x), "r"(y), "r"(z), "r"(bar) : "memory");
}
__device__ __forceinline__ void bar_sync(int id, int n) { asm volatile("bar.sync %0, %1;" ::"r"(id), "r"(n) : "memory"); }
__device__ __forceinline__ void bar_arrive(int id, int n) { asm volatile("bar.arrive %0, %1;" ::"r"(id), "r"(n) : "memory"); }
__device__ __forceinline__ void ldsm4(uint32_t (&r)[4], uint32_t a) {
    asm volatile("ldmatrix.sync.aligned.m8n8.x4.shared.b16 {%0,%1,%2,%3}, [%4];"
                 : "=r"(r[0]), "=r"(r[1]), "=r"(r[2]), "=r"(r[3]) : "r"(a) : "memory");
}
__device__ __forceinline__ void ldsm4t(uint32_t (&r)[4], uint32_t a) {
    asm volatile("ldmatrix.sync.aligned.m8n8.x4.trans.shared.b16 {%0,%1,%2,%3}, [%4];"
                 : "=r"(r[0]), "=r"(r[1]), "=r"(r[2]), "=r"(r[3]) : "r"(a) : "memory");
}
__device__ __forceinline__ void mma(float (&c)[4], uint32_t a0, uint32_t a1, uint32_t a2, uint32_t a3, uint32_t b0, uint32_t b1) {
    asm volatile("mma.sync.aligned.m16n8k16.row.col.f32.bf16.bf16.f32 {%0,%1,%2,%3}, {%4,%5,%6,%7}, {%8,%9}, {%0,%1,%2,%3};"
                 : "+f"(c[0]), "+f"(c[1]), "+f"(c[2]), "+f"(c[3])
                 : "r"(a0), "r"(a1), "r"(a2), "r"(a3), "r"(b0), "r"(b1));
}
__device__ __forceinline__ uint32_t movm(uint32_t a) {
    uint32_t d;
    asm volatile("movmatrix.sync.aligned.m8n8.trans.b16 %0, %1;" : "=r"(d) : "r"(a));
    return d;
}
__device__ __forceinline__ uint32_t lds32(uint32_t a) { uint32_t v; asm volatile("ld.shared.b32 %0, [%1];" : "=r"(v) : "r"(a) : "memory"); return v; }
__device__ __forceinline__ float2 lds64f(uint32_t a) { float2 v; asm volatile("ld.shared.v2.f32 {%0,%1}, [%2];" : "=f"(v.x), "=f"(v.y) : "r"(a) : "memory"); return v; }
__device__ __forceinline__ uint4 lds128(uint32_t a) { uint4 v; asm volatile("ld.shared.v4.b32 {%0,%1,%2,%3}, [%4];" : "=r"(v.x), "=r"(v.y), "=r"(v.z), "=r"(v.w) : "r"(a) : "memory"); return v; }
__device__ __forceinline__ void sts32(uint32_t a, uint32_t v) { asm volatile("st.shared.b32 [%0], %1;" ::"r"(a), "r"(v) : "memory"); }
__device__ __forceinline__ void sts16(uint32_t a, uint16_t v) { asm volatile("st.shared.b16 [%0], %1;" ::"r"(a), "h"(v) : "memory"); }
__device__ __forceinline__ void sts64(uint32_t a, uint32_t x, uint32_t y) { asm volatile("st.shared.v2.b32 [%0], {%1,%2};" ::"r"(a), "r"(x), "r"(y) : "memory"); }
__device__ __forceinline__ void sts128(uint32_t a, uint32_t x, uint32_t y, uint32_t z, uint32_t w) {
    asm volatile("st.shared.v4.b32 [%0], {%1,%2,%3,%4};" ::"r"(a), "r"(x), "r"(y), "r"(z), "r"(w) : "memory");
}
__device__ __forceinline__ void sts128f(uint32_t a, const float (&c)[4]) {
    sts128(a, __float_as_uint(c[0]), __float_as_uint(c[1]), __float_as_uint(c[2]), __float_as_uint(c[3]));
}

__device__ __forceinline__ float sel4(const float (&c)[4], int t) { return (t & 2) ? ((t & 1) ? c[3] : c[2]) : ((t & 1) ? c[1] : c[0]); }

__device__ __forceinline__ uint32_t pin(uint32_t v) { return __shfl_xor_sync(0xffffffffu, v, 0); }
template <typename T>
__device__ __forceinline__ T* at(T* base, uint32_t bytes) { return reinterpret_cast<T*>(reinterpret_cast<char*>(base) + bytes); }

__device__ __forceinline__ uint32_t clock32(uint32_t dep) {
    uint32_t t;
    asm volatile("{\n.reg .pred p;\nsetp.eq.u32 p, %1, 0x9e3779b9;\n@p nanosleep.u32 1;\nmov.u32 %0, %clock;\n}" : "=r"(t) : "r"(dep) : "memory");
    return t;
}

__device__ __forceinline__ uint32_t nz(uint32_t v) { return v ? v : 0x80000000u; }
__device__ __forceinline__ void st1(uint32_t* p, uint32_t a) { asm volatile("st.relaxed.gpu.global.b32 [%0], %1;" ::"l"(p), "r"(a) : "memory"); }
__device__ __forceinline__ void st2(uint32_t* p, uint32_t a, uint32_t b) {
    asm volatile("st.relaxed.gpu.global.v2.b32 [%0], {%1,%2};" ::"l"(p), "r"(a), "r"(b) : "memory");
}
__device__ __forceinline__ void zero4(uint32_t* p) { asm volatile("st.relaxed.gpu.global.v4.b32 [%0], {%1,%1,%1,%1};" ::"l"(p), "r"(0) : "memory"); }
__device__ __forceinline__ void put1d(uint32_t* p, uint32_t a) { a = nz(a), st1(p, a), st1(p + 1024, a); }
__device__ __forceinline__ void put2d(uint32_t* p, uint32_t a, uint32_t b) { a = nz(a), b = nz(b), st2(p, a, b), st2(p + 1024, a, b); }
__device__ __forceinline__ uint32_t ld1(const uint32_t* p) {
    uint32_t v;
    asm volatile("ld.relaxed.gpu.global.b32 %0, [%1];" : "=r"(v) : "l"(p) : "memory");
    return v;
}
template <int N, int V>
__device__ __forceinline__ void fetch(const uint32_t* p, int stride, uint32_t (&a)[N * V]) {
#pragma unroll
    for (int i = 0; i < N; i++) {
        if (V == 1)
            asm volatile("{\n.reg .pred p;\nsetp.eq.u32 p, %0, 0;\n@p ld.relaxed.gpu.global.b32 %0, [%1];\n}"
                         : "+r"(a[i]) : "l"(p + i * stride) : "memory");
        if (V == 4)
            asm volatile("{\n.reg .pred p;\nsetp.eq.u32 p, %4, 0;\n@p ld.relaxed.gpu.global.v4.b32 {%0,%1,%2,%3}, [%5];\n}"
                         : "+r"(a[V * i]), "+r"(a[V * i + V / 4]), "+r"(a[V * i + V / 2]), "+r"(a[V * i + V - 1])
                         : "r"(min(min(a[V * i], a[V * i + V / 4]), min(a[V * i + V / 2], a[V * i + V - 1]))), "l"(p + i * stride) : "memory");
    }
}
template <int N>
__device__ __forceinline__ bool missing(const uint32_t (&a)[N]) {
    uint32_t lo = a[0];
#pragma unroll
    for (int i = 1; i < N; i++) lo = min(lo, a[i]);
    return __any_sync(0xffffffffu, lo == 0);
}
template <int N, int V>
__device__ __forceinline__ void get(const uint32_t* p, int stride, uint32_t (&a)[N * V]) {
    int it = 0;
    do fetch<N, V>(p, stride, a);
    while (missing(a) & (++it < SPIN_LIMIT));
}
__device__ __forceinline__ void cp16(uint32_t dst, const void* src) {
    asm volatile("cp.async.cg.shared.global [%0], [%1], 16;" ::"r"(dst), "l"(src) : "memory");
}

__device__ __forceinline__ uint32_t pack2(float lo, float hi) {
    uint32_t r;
    asm("cvt.rn.bf16x2.f32 %0, %1, %2;" : "=r"(r) : "f"(hi), "f"(lo));
    return r;
}
__device__ __forceinline__ float rbf(float x) { return __uint_as_float(pack2(0.f, x)); }
__device__ __forceinline__ float blo(uint32_t v) { return __uint_as_float(v << 16); }
__device__ __forceinline__ float bhi(uint32_t v) { return __uint_as_float(v & 0xffff0000u); }
__device__ __forceinline__ uint32_t badd2(uint32_t a, uint32_t b) { uint32_t r; asm("add.rn.bf16x2 %0, %1, %2;" : "=r"(r) : "r"(a), "r"(b)); return r; }
__device__ __forceinline__ uint32_t bsub2(uint32_t a, uint32_t b) { uint32_t r; asm("sub.rn.bf16x2 %0, %1, %2;" : "=r"(r) : "r"(a), "r"(b)); return r; }
__device__ __forceinline__ uint32_t bmul2(uint32_t a, uint32_t b) { uint32_t r; asm("mul.rn.bf16x2 %0, %1, %2;" : "=r"(r) : "r"(a), "r"(b)); return r; }
__device__ __forceinline__ float ex2(float x) { float r; asm("ex2.approx.ftz.f32 %0, %1;" : "=f"(r) : "f"(x)); return r; }
__device__ __forceinline__ float rcp(float x) { float r; asm("rcp.approx.ftz.f32 %0, %1;" : "=f"(r) : "f"(x)); return r; }
__device__ __forceinline__ float sqrt_f(float x) { float r; asm("sqrt.approx.ftz.f32 %0, %1;" : "=f"(r) : "f"(x)); return r; }
constexpr float LOG2E = 1.4426950408889634f;
constexpr uint32_t ONE2 = 0x3f803f80u;
__device__ __forceinline__ float sigmoid_f(float x) { return rcp(1.0f + ex2(-LOG2E * x)); }
__device__ __forceinline__ uint32_t silu2(uint32_t v) {
    const float a = blo(v), b = bhi(v);
    return pack2(a * sigmoid_f(a), b * sigmoid_f(b));
}
__device__ __forceinline__ float quad_sum(float v) {
    v += __shfl_xor_sync(0xffffffffu, v, 1);
    return v + __shfl_xor_sync(0xffffffffu, v, 2);
}
__device__ __forceinline__ void ln_partial(const uint32_t (&v)[8], uint32_t dst, bool writer) {
    float s0 = 0.f, s1 = 0.f;
#pragma unroll
    for (int i = 0; i < 8; i++) {
        s0 += blo(v[i]);
        s1 += bhi(v[i]);
    }
    const float mean = quad_sum(s0 + s1) * (1.0f / 64);
    s0 = s1 = 0.f;
#pragma unroll
    for (int i = 0; i < 8; i++) {
        const float a = blo(v[i]) - mean, b = bhi(v[i]) - mean;
        s0 = fmaf(a, a, s0);
        s1 = fmaf(b, b, s1);
    }
    s0 = quad_sum(s0 + s1);
    if (writer) sts64(dst, __float_as_uint(mean), __float_as_uint(s0));
}
__device__ __forceinline__ void ln_combine(uint32_t src, uint32_t& mean2, float& inv) {
    float m[10], q0 = 0.f, q1 = 0.f, s = 0.f;
#pragma unroll
    for (int i = 0; i < 5; i++) {
        const uint4 v = lds128(src + i * 16);
        m[2 * i] = __uint_as_float(v.x);
        m[2 * i + 1] = __uint_as_float(v.z);
        q0 += __uint_as_float(v.y);
        if (i < 4) q1 += __uint_as_float(v.w);
    }
    const float mean = (((m[0] + m[1]) + (m[2] + m[3])) + ((m[4] + m[5]) + (m[6] + m[7])) + m[8]) * (1.0f / 9);
#pragma unroll
    for (int i = 0; i < 9; i++) s = fmaf(m[i] - mean, m[i] - mean, s);
    const float var = fmaf(s, 64.f, q0 + q1) * (1.0f / DM);
    mean2 = pack2(mean, mean);
    inv = rcp(rbf(sqrt_f(rbf(rbf(var) + 1e-5f))));
}
__device__ __forceinline__ uint32_t modulate2(uint32_t x, uint32_t mean2, float inv, uint32_t shift, uint32_t onep) {
    const uint32_t d = bsub2(x, mean2);
    return badd2(bmul2(pack2(blo(d) * inv, bhi(d) * inv), onep), shift);
}
template <int N>
__device__ __forceinline__ void sum_frags(float (&c)[4], uint32_t addr, int stride) {
#pragma unroll
    for (int w = 0; w < N; w++) {
        const uint4 v = lds128(addr + w * stride);
        c[0] += __uint_as_float(v.x); c[1] += __uint_as_float(v.y);
        c[2] += __uint_as_float(v.z); c[3] += __uint_as_float(v.w);
    }
}

template <int ST>
__device__ __forceinline__ void project(uint32_t sm, const uint32_t* src, uint32_t* dst, uint32_t rowoff, uint32_t reds, int warp, int lane) {
    constexpr int NW = ST ? 9 : 8;
    const uint32_t red = sm + (ST ? OFF_WO : OFF_P);
    if (warp < NW) {
        const uint32_t wbar = sm + OFF_BAR + ((ST ? BAR_WD : BAR_WO) + (warp >> 1)) * 8;
        const uint32_t ab = sm + (ST ? OFF_WD : OFF_WO) + rowoff;
        const uint32_t ax = sm + (ST ? OFF_DX : OFF_OX) + ((rowoff >> 7) << 4);
        uint32_t a[10][4] = {}, b[4] = {};
        bool have_w = false;
        int it = 0;
        do {
            if (!have_w && __all_sync(0xffffffffu, mbar_test(wbar, 0))) {
                have_w = true;
#pragma unroll
                for (int i = 0; i < 10; i++) ldsm4t(a[i], i % 5 < 4 ? (ab ^ ((i % 5) << 5)) + (i / 5) * 2048 : ax + (i / 5) * 256);
            }
            if (ST) fetch<4, 1>(src, 32, b);
            else fetch<1, 4>(src, 0, b);
        } while ((missing(b) | !have_w) & (++it < SPIN_LIMIT));
        if (warp == 0) TSL(ST ? 24 : 21);
        float acc[5][4] = {};
#pragma unroll
        for (int i = 0; i < 10; i++) mma(acc[i % 5], a[i][0], a[i][1], a[i][2], a[i][3], b[2 * (i / 5)], b[2 * (i / 5) + 1]);
#pragma unroll
        for (int u = 0; u < 9; u++)
            sts64(red + u * 2304 + (reds & 0xffff), __float_as_uint(acc[u >> 1][2 * (u & 1)]), __float_as_uint(acc[u >> 1][2 * (u & 1) + 1]));
    }
    bar_sync(3, 288);
    float s[2][2] = {};
#pragma unroll
    for (int w = 0; w < NW; w++) {
        const float2 v = lds64f(red + (reds >> 16) + w * 256);
        s[w & 1][0] += v.x;
        s[w & 1][1] += v.y;
    }
    const uint32_t p0 = (__float_as_uint(s[0][0] + s[1][0]) | 1) ^ ST, p1 = (__float_as_uint(s[0][1] + s[1][1]) | 1) ^ ST;
    st2(dst, p0, p1), st2(dst + 1024, p0, p1);
}

template <int ST>
__device__ __forceinline__ uint32_t reduce16(const uint32_t* src, int lane) {
    uint32_t a[8], bad[4] = {1, 1, 1, 1};
    int it = 0;
#pragma unroll
    for (int i = 0; i < 8; i++) a[i] = 0;
    do {
#pragma unroll
        for (int i = 0; i < 4; i++)
            asm volatile("{\n.reg .pred p;\nsetp.ne.u32 p, %2, 0;\n@p ld.relaxed.gpu.global.v2.b32 {%0,%1}, [%3];\n}"
                         : "+r"(a[2 * i]), "+r"(a[2 * i + 1]) : "r"(bad[i]), "l"(src + i * 64) : "memory");
#pragma unroll
        for (int i = 0; i < 4; i++) bad[i] = (ST ? a[2 * i] | a[2 * i + 1] : ~(a[2 * i] & a[2 * i + 1])) & 1;
    } while (__any_sync(0xffffffffu, (bad[0] | bad[1] | bad[2] | bad[3]) != 0) & (++it < SPIN_LIMIT));
    float s0 = (__uint_as_float(a[0]) + __uint_as_float(a[2])) + (__uint_as_float(a[4]) + __uint_as_float(a[6]));
    float s1 = (__uint_as_float(a[1]) + __uint_as_float(a[3])) + (__uint_as_float(a[5]) + __uint_as_float(a[7]));
#pragma unroll
    for (int o = 8; o < 32; o <<= 1) {
        s0 += __shfl_xor_sync(0xffffffffu, s0, o);
        s1 += __shfl_xor_sync(0xffffffffu, s1, o);
    }
    const uint32_t y = pack2(s0, s1);
    return __byte_perm(y, __shfl_xor_sync(0xffffffffu, y, 4), (lane & 4) ? 0x3276 : 0x5410);
}

__global__ void __launch_bounds__(NTHREADS, 1) fused_kernel(const __grid_constant__ Params P) {
    extern __shared__ __align__(1024) char smem_raw[];
    constexpr uint32_t sm = 1024;
    const int tid = threadIdx.x, lane = tid & 31;
    const int cta = blockIdx.x, grp = cta >> 3, sub = cta & 7;
    const uint32_t bars = sm + OFF_BAR;
    const int row0 = (sub * HKV + grp) * SK + (SK - WIN);
    u64 pol;
    asm volatile("createpolicy.fractional.L2::evict_first.b64 %0, 1.0;" : "=l"(pol));
    if (tid == NCW * 32) {
        TS(0);
        const int n0 = cta < 108 ? 0 : 3;
#pragma unroll
        for (int i = 0; i < 6; i++) mbar_init(bars + i * 8, 1);
        asm volatile("fence.mbarrier_init.release.cluster;" ::: "memory");
#pragma unroll
        for (int i = 0; i < 3; i++) {
            mbar_expect(bars + (n0 + i) * 8, 12288);
            tma3d(sm + OFF_WM + (n0 + i) * 12288, &P.m[cta < 36 ? M_WA : cta < 108 ? M_WM : M_WQ], cta < 36 ? 16 * cta : 32 * cta,
                  i * 192, 0, bars + (n0 + i) * 8);
            TI(n0 + i);
        }
        TS(26);
    }
    if (tid == NCW * 32 + 32) {
#pragma unroll
        for (int i = 0; i < 4; i++) mbar_init(bars + (BAR_FULL + i) * 8, 1);
        asm volatile("fence.mbarrier_init.release.cluster;" ::: "memory");
#pragma unroll
        for (int t = 0; t < NK0; t++) {
            mbar_expect(bars + (BAR_FULL + t) * 8, TILE_BYTES);
            tma3d_hint(sm + OFF_RING + t * TILE_BYTES, &P.m[M_K], 0, row0 + t * 32, 0, bars + (BAR_FULL + t) * 8, pol);
            TI(6 + t);
        }
    }
    if (tid < 288 && cta < 108) {
#pragma unroll
        for (int i = 0; i < 2; i++) {
            const int row = (lane >> 3) + 4 * i, so = row * DM + (tid >> 5) * 64 + (lane & 7) * 8;
            const uint32_t d = sm + OFF_RED + (tid >> 5) * 2048 + row * 128 + (((lane & 7) ^ row) << 4);
            cp16(d, P.c + so);
            if (cta < 36) cp16(d + 1024, P.x + so);
        }
    }
    uint32_t* const g0 = P.scratch;
    const uint32_t epoch = ld1(g0 + G_EPOCH);
    const int warp = __shfl_sync(0xffffffffu, tid >> 5, 0);
    auto pace = [&](int t, int gain) {
        const int d = (int)atomicAdd(g0 + (epoch & 1) * G_SET + G_CNT, 1u) - 32 * (t - 16) - 16;
        sts32(sm + OFF_WIN, min(max((d * gain + 32) >> 6, W_MIN), W_MAX));
    };

    if (warp >= NCW) {
        const int pw = warp - NCW;
        bar_arrive(1, (NCW + 1) * 32);
        if (pw && lane < M_WQ) asm volatile("prefetch.tensormap [%0];" ::"l"(&P.m[M_WQ - lane]) : "memory");
        if (tid == NCW * 32) sts32(sm + OFF_WIN, 0);
        __syncwarp();
        bar_sync(15, NTHREADS);
        if (lane == 0) {
            if (pw == 0 && cta < 108) {
#pragma unroll 1
                for (int n = 3; n < 6; n++) {
                    mbar_expect(bars + n * 8, 12288);
                    mbar_wait(bars + (n - 3) * 8, 0);
                    tma3d(sm + OFF_WM + n * 12288, &P.m[M_WQ], 32 * cta, (n - 3) * 192, 0, bars + n * 8);
                    TI(n);
                }
            }
#pragma unroll 1
            for (int t = (2 - pw) * NK0; t < 2 * NK0 + 3 * (1 - pw); t++) {
                mbar_expect(bars + (BAR_FULL + t) * 8, TILE_BYTES);
                mbar_wait(bars + (t + (pw ? BAR_FULL - NK0 : 3 - 2 * NK0)) * 8, 0);
                tma3d_hint(sm + OFF_RING + t * TILE_BYTES, &P.m[M_K], 0, row0 + t * 32, 0, bars + (BAR_FULL + t) * 8, pol);
                TI(6 + t);
            }
            if (pw == 0) {
#pragma unroll 1
                for (int t = 2 * NK0 + 3; t < 2 * NT; t++) {
                    if (t == 14 && cta < 108) mbar_wait(bars + BAR_WMF * 8, 0);
                    if (t == 15) TS(30);
                    const int m = t - ((W_KV + (int)lds32(sm + OFF_WIN) + ((0xd8 >> (2 * t & 6)) & 3)) >> 2);
                    const uint32_t fb = bars + (BAR_FULL + (t & 15)) * 8;
                    mbar_wait(fb + (BAR_EMPTY - BAR_FULL) * 8, (~t >> 4) & 1);
                    mbar_expect(fb, TILE_BYTES);
                    mbar_wait(bars + (BAR_FULL + (m & 15)) * 8, (m >> 4) & 1);
                    tma3d_hint(sm + OFF_RING + (t & 15) * TILE_BYTES, &P.m[t >> 6], 0, row0 + (t & (NT - 1)) * 32, 0, fb, pol);
                    TI(6 + t);
                    if (t == T_CLEAR || t == T_STRIP) mbar_arrive(bars + (t == T_CLEAR ? BAR_SYNC + 1 : BAR_X + 1) * 8);
                }
                mbar_arrive(bars + (BAR_SYNC + 2) * 8);
                mbar_wait(bars + BAR_SYNC * 8, 0);
                auto window = [&](int b, int w) {
                    b -= max((w + (int)lds32(sm + OFF_WIN) + ((0xd8 >> (2 * b & 6)) & 3)) >> 2, 1);
                    b = min(b, BAR_GU + B_CAP);
                    mbar_wait(bars + b * 8, b < BAR_WO);
                };
#pragma unroll 1
                for (int i = 0; i < 4; i++) {
                    window(BAR_WO + i, W_WO);
                    tma3d(sm + OFF_WO + i * 8192, &P.m[M_OD], 64 * sub, grp * 256 + i * 64, P.zo, bars + (BAR_WO + i) * 8);
                    TI(134 + i);
                }
                TS(28);
#pragma unroll 1
                for (int i = 0; i < 9; i++) {
                    mbar_wait(bars + (BAR_EMPTY + i) * 8, 1);
                    window(BAR_GU + i, W_GU);
                    tma3d(sm + OFF_GU + i * 8192, &P.m[M_GU], grp * 288 + 32 * sub, i * 64, 0, bars + (BAR_GU + i) * 8);
                    TI(138 + i);
                }
                TS(29);
#pragma unroll 1
                for (int i = 0; i < 5; i++) {
                    const int r = min(i * 64, 224);
                    mbar_wait(bars + (BAR_EMPTY + 9 + i) * 8, 1);
                    window(BAR_WD + i, W_WD);
                    tma3d(sm + OFF_WD + r * 128, &P.m[M_OD], 64 * sub, grp * 288 + r, P.zo ^ 1, bars + (BAR_WD + i) * 8);
                    TI(147 + i);
                }
            } else {
                mbar_wait(bars + (BAR_X + 1) * 8, 0);
#pragma unroll 1
                for (int i = 0; i < (sub < 4 ? X_NS : min(X_NS, 4)); i++) {
                    const int r = (i & 1) * (i < 2 ? 112 : 144);
                    if (i >= 4 || i == 0) mbar_expect(bars + BAR_X * 8, i < 4 ? 9216 : 6144);
                    if (i < 4) tma3d(sm + OFF_OX + (i >> 1) * 4096 + r * 16, &P.m[M_OX], 512 + 8 * sub, grp * (i < 2 ? 256 : 288) + r, P.zo ^ (i >> 1), bars + BAR_X * 8);
                    else tma3d(sm + OFF_GX + (i - 4) * 6144, &P.m[M_GX], grp * 288 + 256 + 8 * sub, (i - 4) * 192, 0, bars + BAR_X * 8);
                    TI(152 + i);
                    if (i >= 3) mbar_wait(bars + BAR_X * 8, ~i & 1);
                }
#pragma unroll 1
                for (int i = 0; i < 18; i++) mbar_expect(bars + (BAR_WO + i) * 8, 8192);
                mbar_arrive(bars + BAR_SYNC * 8);
                mbar_wait(bars + (BAR_SYNC + 2) * 8, 0);
#pragma unroll 1
                for (int t = 124 + (cta & 3); t < 144; t += 4) {
                    mbar_wait(bars + (BAR_FULL - 112 + t) * 8, t < 128);
                    pace(t, GAIN_TAIL);
                }
            }
        }
        return;
    }

    if (lane == 0) {
#pragma unroll
        for (int i = 0; i < 6; i++) mbar_init(bars + (10 + warp * 6 + i) * 8, 1);
        asm volatile("fence.mbarrier_init.release.cluster;" ::: "memory");
    }
    __syncwarp();
    if (warp < 9) bar_arrive(15, NTHREADS);
    const int g = lane >> 2, t4 = lane & 3;
    uint32_t* const gs = g0 + (epoch & 1) * G_SET;

    if (warp < 9) {
        const int off_h = (cta < 36 ? dual(D_H + 2 * cta * 32) : G_M + 4 * (cta - 36) * 32) + tid;
        const int off_h2 = off_h + (cta < 36 ? 1024 : 64);
        const int off_q = dual(D_Q + g * (HQ * 64) + cta * 16) + warp * 8 + t4 * 2;
        uint32_t bf[8] = {}, xp = 0, mean2 = 0;
        float inv = 0.f;
        if (cta < 36) xp = __ldg(reinterpret_cast<const uint32_t*>(P.x) + g * (DM / 2) + 8 * cta + 4 * (warp & 1) + t4);
        if (warp < 2) {
            st2(gs + off_q, 0, 0), st2(gs + off_q + 1024, 0, 0);
            if (cta < 36) st1(gs + off_h, 0), st1(gs + off_h2, 0);
        }
        if (cta < 108) {
            asm volatile("cp.async.wait_all;" ::: "memory");
            __syncwarp();
            const uint32_t fa = sm + OFF_RED + warp * 2048 + (lane & 7) * 128 + (((lane >> 3) ^ (lane & 7)) << 4);
            ldsm4(reinterpret_cast<uint32_t(&)[4]>(bf[0]), fa);
            ldsm4(reinterpret_cast<uint32_t(&)[4]>(bf[4]), fa ^ 64);
            if (cta < 36) {
                uint32_t xv[8];
                ldsm4(reinterpret_cast<uint32_t(&)[4]>(xv[0]), fa + 1024);
                ldsm4(reinterpret_cast<uint32_t(&)[4]>(xv[4]), (fa ^ 64) + 1024);
                ln_partial(xv, sm + OFF_ST + g * 80 + warp * 8, t4 == 0);
            }
#pragma unroll
            for (int i = 0; i < 8; i++) bf[i] = silu2(bf[i]);
        }
        if (warp == 0) TSL(18);
        bar_sync(1, (NCW + 1) * 32);
        if (cta < 36 && warp < 2) ln_combine(sm + OFF_ST + g * 80, mean2, inv);
        const int r = warp * 64 + (lane >> 4) * 8 + (lane & 7), hi8 = (lane >> 3) & 1, box = warp / 3;
#pragma unroll 1
        for (int pass = cta < 108 ? 0 : 1; pass < 2; pass++) {
            const bool pa = pass == 0 && cta < 36;
            const uint32_t ab = sm + OFF_WM + pass * 36864 +
                                (pa ? (box + hi8) * 6144 + r * 32 + ((lane & 4) << 2) : r * 64 + (((2 * hi8) ^ ((r >> 1) & 3)) << 4));
            const uint32_t as = pa ? 512 : 1024, red = sm + OFF_RED + pass * 9216;
            mbar_wait(bars + (pass * 3 + box) * 8, 0);
            if (warp == 8) TSL(pass ? 31 : 19);
            uint32_t a[4][2][4];
#pragma unroll
            for (int i = 0; i < 4; i++) {
                ldsm4t(a[i][0], ab + i * as);
                ldsm4t(a[i][1], (ab ^ 16) + i * as);
            }
            if (pass) {
                bar_sync(8, NCW * 32);
#pragma unroll
                for (int i = 0; i < 8; i++) bf[i] = 0;
                get<8, 1>(gs + near(D_H + warp * 256, lds32(sm + OFF_WIN + 4)) + lane, 32, bf);
                if (warp == 0) TSL(3);
            }
            float acc[2][4] = {};
#pragma unroll
            for (int i = 0; i < 4; i++)
#pragma unroll
                for (int m = 0; m < 2; m++) mma(acc[m], a[i][m][0], a[i][m][1], a[i][m][2], a[i][m][3], bf[2 * i], bf[2 * i + 1]);
            sts128f(red + tid * 16, acc[0]);
            sts128f(red + 4608 + tid * 16, acc[1]);
            bar_sync(3, 288);
            if (warp < 2) {
                float c[4] = {};
                sum_frags<9>(c, red + warp * 4608 + lane * 16, 512);
                uint32_t lo = movm(pack2(c[0], c[1])), hi = movm(pack2(c[2], c[3]));
                if (pass) {
                    put2d(gs + off_q, lo, hi);
                    if (warp == 0) TSL(4);
                } else {
                    const uint32_t hi1 = badd2(hi, ONE2);
                    if (pa) hi = lo = modulate2(xp, mean2, inv, lo, hi1);
                    if (cta >= 72 && cta < 90) lo = badd2(lo, ONE2), hi = hi1;
                    st1(gs + off_h, nz(lo));
                    st1(gs + off_h2, nz(hi));
                    if (warp == 0 && pa) TSL(2);
                }
            } else if (tid == 64 && pass == 0) {
                mbar_arrive(bars + BAR_WMF * 8);
            }
        }
    } else {
        if ((uint32_t)__cvta_generic_to_shared(smem_raw) != sm) __trap();
        uint32_t* const ping = g0 + dual(D_PING) + cta * 8;
        if (lane < 16) st1(ping + (lane >> 3) * 1024 + (lane & 7), 0);
        bar_sync(15, NTHREADS);
        uint32_t best[2] = {~0u, ~0u}, v = 0;
#pragma unroll 1
        for (int part = 0; part < 2; part++) {
            if (lane == 0) {
#pragma unroll 1
                for (int r = part ? NPING1 : NPING0; r > 0; r--) {
#pragma unroll
                    for (int k = 0; k < 2; k++) {
                        const uint32_t t0 = clock32(v);
                        v = atomicExch(ping + k * 1024, t0);
                        best[k] = min(best[k], clock32(v) - t0);
                    }
                }
                sts32(sm + OFF_WIN + 4 + 4 * part, ((best[1] < best[0]) ^ __popc(D_PING & 0x16400)) & 1);
            }
            __syncwarp();
            if (part) break;
            TSL(20);
            bar_arrive(8, NCW * 32);
            mbar_wait(bars + 5 * 8, 0);
            uint32_t a[4] = {};
            get<1, 4>(gs + near(D_Q + (sub * HQ + 2 * grp) * 64, lds32(sm + OFF_WIN + 4)) + lane * 4, 0, a);
            sts128(sm + OFF_QS + lane * 16, a[0], a[1], a[2], a[3]);
            __syncwarp();
            TSL(5);
            bar_arrive(4, 288);
        }
#pragma unroll
        for (int i = lane; i < 72; i += 32) cp16(sm + OFF_WR + i * 16, P.wr + i * 8);
        asm volatile("cp.async.wait_all;" ::: "memory");
        __syncwarp();
        bar_arrive(2, NCW * 32);
        if (cta == 0 && lane == 0) st1(g0 + (~epoch & 1) * G_SET + G_CNT, 0);
        mbar_wait(bars + (BAR_SYNC + 1) * 8, 0);
#pragma unroll 1
        for (int c = 0; c < 4; c++) {
            uint32_t* const pg = g0 + (c >> 1) * G_SET + (c & 1) * 1024;
            zero4(pg + dual(D_O + cta * 128) + lane * 4);
            zero4(pg + dual(D_ACT + (grp * 36 + 4 * sub) * 32) + lane * 4);
            if (lane < 8 ? sub < 4 : lane < 16 && cta < 72)
                zero4(pg + dual(lane < 8 ? D_ACT + (grp * 36 + 32 + sub) * 32 : D_X1 + cta * 32) + (lane & 7) * 4);
        }
#pragma unroll 1
        for (int u = 0; u < 9; u++) zero4(g0 + dual(d_part(u < 8 ? 8 * sub + u : 64 + sub)) + (lane >> 4) * 1024 + grp * 64 + (lane & 15) * 4);
        __syncwarp();
        bar_arrive(5, NCW * 32);
        {
            uint32_t* const nx = g0 + (~epoch & 1) * G_SET;
            uint32_t* const q = nx + dual(D_Q + g * (HQ * 64) + cta * 16) + t4 * 4;
            zero4(q), zero4(q + 1024);
            if (cta < 108) zero4(nx + (cta < 36 ? dual(D_H + 2 * cta * 32) + (lane >> 4) * (1024 - 64) : G_M + 4 * (cta - 36) * 32) + lane * 4);
        }
        return;
    }

    const uint32_t tile = sm + OFF_RING + warp * TILE_BYTES;
    const uint32_t fullb = bars + (BAR_FULL + warp) * 8;
    const uint32_t pw = sm + OFF_P + warp * (2 * P_PITCH);
    const bool pacer = (tid & 127) == (cta & 3) * 32;
    if (warp < 8) {
        {
            uint32_t q0[8], q1[8];
            bar_sync(4, 288);
#pragma unroll
            for (int i = 0; i < 8; i++) {
                const float2 v = lds64f(sm + OFF_QS + (g & 1) * 256 + i * 32 + t4 * 8);
                q0[i] = __float_as_uint(v.x), q1[i] = __float_as_uint(v.y);
            }
            uint32_t sp = pw + (t4 & 1) * P_PITCH + ((t4 >> 1) * 8 + g) * 2;
#pragma unroll 1
            for (int it = 0; it < 8; it++, sp += 64) {
                const uint32_t ab = tile + (it & 1) * (8 * TILE_BYTES) + (lane & 15) * 128 + (((lane >> 4) ^ (lane & 7)) << 4);
                mbar_wait(fullb + (it & 1) * 64, (it >> 1) & 1);
                float acc[2][2][4] = {};
#pragma unroll
                for (int ks = 0; ks < 8; ks++)
#pragma unroll
                    for (int m = 0; m < 2; m++) {
                        uint32_t a[4];
                        ldsm4(a, (ab ^ ((ks & 3) << 5)) + (ks >> 2) * 4096 + m * 2048);
                        mma(acc[m][ks & 1], a[0], a[1], a[2], a[3], (ks & 1) ? q1[ks - 1] : q0[ks], (ks & 1) ? q1[ks] : q0[ks + 1]);
                    }
                __syncwarp();
                if (lane == 0) mbar_arrive(fullb + (it & 1) * 64 + (BAR_EMPTY - BAR_FULL) * 8);
#pragma unroll
                for (int m = 0; m < 2; m++) {
                    const float s = sel4(acc[m][0], t4) + sel4(acc[m][1], t4);
                    sts16(sp + m * 32, (uint16_t)pack2(rbf(s) * 0.08838834764831845f, 0.f));
                }
                if (pacer && it >= 2) pace(it * 8 + warp, GAIN_KV);
                __syncwarp();
            }
        }
        __syncwarp();
        if (warp == 7) TSL(6);
        const uint32_t pa = pw + (lane >> 4) * P_PITCH + (lane & 15) * 32;
        const uint32_t sa = sm + OFF_SM + (lane >> 4) * 64;
        const uint4 v0 = lds128(pa), v1 = lds128(pa + 16);
        const uint32_t sv[8] = {v0.x, v0.y, v0.z, v0.w, v1.x, v1.y, v1.z, v1.w};
        float e[16];
        float m = -INFINITY;
#pragma unroll
        for (int i = 0; i < 8; i++) {
            e[2 * i] = blo(sv[i]);
            e[2 * i + 1] = bhi(sv[i]);
            m = fmaxf(m, fmaxf(e[2 * i], e[2 * i + 1]));
        }
#pragma unroll
        for (int o = 8; o; o >>= 1) m = fmaxf(m, __shfl_xor_sync(0xffffffffu, m, o));
        float l = 0.f;
#pragma unroll
        for (int i = 0; i < 16; i++) {
            e[i] = ex2((e[i] - m) * LOG2E);
            l += e[i];
        }
#pragma unroll
        for (int o = 8; o; o >>= 1) l += __shfl_xor_sync(0xffffffffu, l, o);
        if ((lane & 15) == 0) sts64(sa + warp * 8, __float_as_uint(m), __float_as_uint(l));
        bar_sync(2, NCW * 32);
        const float2 v = lds64f(sa + (lane & 7) * 8);
        float M = v.x;
#pragma unroll
        for (int o = 4; o; o >>= 1) M = fmaxf(M, __shfl_xor_sync(0xffffffffu, M, o));
        float L = v.y * ex2((v.x - M) * LOG2E);
#pragma unroll
        for (int o = 4; o; o >>= 1) L += __shfl_xor_sync(0xffffffffu, L, o);
        const float sc = ex2((m - M) * LOG2E) * rcp(L);
        sts128(pa, pack2(e[0] * sc, e[1] * sc), pack2(e[2] * sc, e[3] * sc), pack2(e[4] * sc, e[5] * sc), pack2(e[6] * sc, e[7] * sc));
        sts128(pa + 16, pack2(e[8] * sc, e[9] * sc), pack2(e[10] * sc, e[11] * sc), pack2(e[12] * sc, e[13] * sc), pack2(e[14] * sc, e[15] * sc));
        __syncwarp();
    } else {
        bar_sync(2, NCW * 32);
    }

    const bool reducer = cta < 72 && warp < 4;
    const int rbat = 2 * t4 + (g & 1);
    uint32_t sh[8] = {}, op[8] = {}, rx = 0, rg[2] = {};
    {
        const uint32_t* const src_m = gs + G_M + (72 + warp * 8) * 32 + lane;
        fetch<8, 1>(src_m + 72 * 32, 32, op);
        if (reducer) {
            rx = __ldg(reinterpret_cast<const uint32_t*>(P.x) + rbat * (DM / 2) + 4 * cta + warp);
            get<2, 1>(gs + G_M + cta * 32 + rbat * 4 + warp, 216 * 32, rg);
        }
        get<8, 1>(src_m, 32, sh);
        get<8, 1>(src_m + 72 * 32, 32, op);
    }
    const int side = lds32(sm + OFF_WIN + 8), set = (epoch & 1) * G_SET, rr = (lane >> 4) * 8 + (lane & 7);
    const uint32_t dst_o = pin(4 * (set + dual(D_O + cta * 128) + (tid & 0x70) + (tid & 3) * 4 + ((tid >> 2) & 3)));
    const uint32_t src_o = pin(4 * (set + near(D_O + grp * 1024, side) + g * 128 + warp * 16 + t4 * 4));
    const uint32_t dst_p = pin(4 * (dual(d_part(warp < 8 ? 8 * sub + warp : 64 + sub)) + grp * 64 + lane * 2));
    const uint32_t src_p = pin(4 * (near(d_part(cta), side) + (lane >> 3) * 256 + 16 * warp + (lane & 7) * 2));
    const uint32_t dst_x = pin(4 * (set + dual(D_X1 + cta * 32) + (lane >> 3) * 1024 + warp * 8 + (lane & 7)));
    const uint32_t src_x = pin(4 * (set + near(D_X1 + warp * 256, side) + t4 * 8 + (g & 1) * 4 + (g >> 1)));
    const uint32_t dst_a = pin(4 * (set + dual(D_ACT + (grp * 36 + (warp < 4 ? 4 * sub + warp : 32 + sub)) * 32) + lane));
    const uint32_t src_a = pin(4 * (set + near(D_ACT + (grp * 36 + 4 * warp) * 32, side) + lane));
    const uint32_t dst_out = pin(4 * (rbat * (DM / 2) + 4 * cta + warp));
    const uint32_t rowoff = pin((warp * 32 + rr) * 128 + ((((lane >> 3) & 1) ^ (lane & 7)) << 4));
    const uint32_t reds = pin((tid * 8) | (warp * 2304 + lane * 8) << 16);
    const uint32_t ored = pin((warp * 1088 + (t4 & 1) * 576 + ((t4 >> 1) * 8 + g) * 4) | ((tid >> 6) * 64 + tid * 8) << 16);

    if (warp < 8) {
        float acc[8][4] = {};
        uint32_t pp = pw + (lane & 1) * P_PITCH + (lane >> 3) * 16;
#pragma unroll 1
        for (int it = 0; it < 8; it++, pp += 64) {
            const uint32_t ab = tile + (it & 1) * (8 * TILE_BYTES) + ((lane & 7) + (lane >> 4) * 8) * 128 + ((((lane >> 3) & 1) ^ (lane & 7)) << 4);
            uint32_t pb[4];
            ldsm4(pb, pp);
            mbar_wait(fullb + (it & 1) * 64, (it >> 1) & 1);
#pragma unroll
            for (int ks = 0; ks < 2; ks++)
#pragma unroll
                for (int m = 0; m < 8; m++) {
                    uint32_t a[4];
                    ldsm4t(a, (ab ^ ((m & 3) << 5)) + (m >> 2) * 4096 + ks * 2048);
                    mma(acc[m], a[0], a[1], a[2], a[3], pb[2 * ks], pb[2 * ks + 1]);
                }
            __syncwarp();
            if (lane == 0) mbar_arrive(fullb + (it & 1) * 64 + (BAR_EMPTY - BAR_FULL) * 8);
            if (pacer && it * 8 + warp < NT - 4) pace(NT + it * 8 + warp, GAIN_KV);
            __syncwarp();
        }
        if (warp == 7) TSL(7);
        const uint32_t ra = sm + OFF_ORED + (ored & 0xffff);
#pragma unroll
        for (int m = 0; m < 8; m++) sts32(ra + m * 64, __float_as_uint(sel4(acc[m], t4)));
    }
    bar_sync(5, NCW * 32);
    if (warp < 4) {
        float s[2][2] = {};
#pragma unroll
        for (int w = 0; w < 8; w++) {
            const float2 v = lds64f(sm + OFF_ORED + w * 1088 + (ored >> 16));
            s[w & 1][0] += v.x;
            s[w & 1][1] += v.y;
        }
        put1d(at(g0, dst_o), pack2(s[0][0] + s[1][0], s[0][1] + s[1][1]));
        if (warp == 0) TSL(8);
    }

    project<0>(sm, at(g0, src_o), at(g0, dst_p), rowoff, reds, warp, lane);
    if (warp == 0) TSL(9);
    if (reducer) {
        rx = badd2(rx, bmul2(rg[0], reduce16<0>(at(g0, src_p), lane)));
        if (lane < 16) st1(at(g0, dst_x), nz(rx));
        if (warp == 0) TSL(10);
    }

    const uint32_t gbar = bars + (BAR_GU + warp) * 8;
    const int pl = ((lane >> 3) & 1) ^ P.zg;
    const uint32_t ab = sm + OFF_GU + warp * 8192 + pl * 4096 + rr * 64 + ((lane & 6) << 3);
    const uint32_t ax = sm + OFF_GX + (warp / 3 + pl) * 3072 + (warp * 64 + rr) * 16;
    uint32_t a[20][4] = {}, h[8] = {};
    auto load_gu = [&]() {
#pragma unroll
        for (int i = 0; i < 20; i++) ldsm4t(a[i], i % 5 < 4 ? (ab ^ ((i % 5) << 4)) + (i / 5) * 1024 : ax + (i / 5) * 256);
    };
    bool gpre = false;
    {
        int it = 0;
        do {
            if (!gpre && __all_sync(0xffffffffu, mbar_test(gbar, 0))) gpre = true, load_gu();
            fetch<8, 1>(at(g0, src_x), 32, h);
        } while (missing(h) & (++it < SPIN_LIMIT));
    }
    if (warp == 0) TSL(11);
    ln_partial(h, sm + OFF_ST + g * 80 + warp * 8, t4 == 0);
    bar_sync(3, 288);
    {
        uint32_t mean2;
        float inv;
        ln_combine(sm + OFF_ST + g * 80, mean2, inv);
#pragma unroll
        for (int i = 0; i < 8; i++) h[i] = modulate2(h[i], mean2, inv, sh[i], op[i]);
    }
    if (warp == 0) TSL(12);
    if (!gpre) {
        mbar_wait(gbar, 0);
        load_gu();
    }
    if (warp == 8) TSL(17);
    {
        float acc[5][4] = {};
#pragma unroll
        for (int i = 0; i < 20; i++) mma(acc[i % 5], a[i][0], a[i][1], a[i][2], a[i][3], h[2 * (i / 5)], h[2 * (i / 5) + 1]);
#pragma unroll
        for (int m = 0; m < 5; m++) sts128f(sm + OFF_RED + m * 4608 + 2 * (reds & 0xffff), acc[m]);
    }
    bar_sync(3, 288);
    if (warp < 5) {
        float c[4] = {};
        sum_frags<9>(c, sm + OFF_RED + 2 * (reds >> 16), 512);
        const uint32_t w = movm(bmul2(silu2(pack2(c[0], c[1])), pack2(c[2], c[3])));
        if (warp < 4 || sub < 4) put1d(at(g0, dst_a), w);
        if (warp == 1) TSL(13);
    }
    if (cta < 72) {
        float r = 0.f;
#pragma unroll
        for (int i = 0; i < 8; i++) {
            const uint32_t wr = lds32(sm + OFF_WR + (warp * 32 + i * 4 + t4) * 4);
            r = fmaf(blo(h[i]), blo(wr), fmaf(bhi(h[i]), bhi(wr), r));
            if (warp * 8 + i == cta) sts32(sm + OFF_HU + lane * 4, h[i]);
        }
        r = quad_sum(r);
        if (t4 == 0) sts32(sm + OFF_RT + g * 48 + warp * 4, __float_as_uint(r));
    }

    project<1>(sm, at(g0, src_a), at(g0, dst_p), rowoff, reds, warp, lane);
    if (warp == 0) TSL(14);
    if (reducer) {
        const uint4 r0 = lds128(sm + OFF_RT + rbat * 48), r1 = lds128(sm + OFF_RT + rbat * 48 + 16);
        float r = __uint_as_float(lds32(sm + OFF_RT + rbat * 48 + 32));
        r += ((__uint_as_float(r0.x) + __uint_as_float(r0.y)) + (__uint_as_float(r0.z) + __uint_as_float(r0.w))) +
             ((__uint_as_float(r1.x) + __uint_as_float(r1.y)) + (__uint_as_float(r1.z) + __uint_as_float(r1.w)));
        r = sigmoid_f(rbf(r));
        const uint32_t rh = lds32(sm + OFF_HU + (rbat * 4 + warp) * 4);
        const uint32_t y = badd2(rh, bmul2(reduce16<1>(at(g0, src_p), lane), pack2(r, r)));
        if (lane < 8) *at(reinterpret_cast<uint32_t*>(P.out), dst_out) = badd2(rx, bmul2(rg[1], y));
        if (cta == 0 && tid == 0) g0[G_EPOCH] = epoch + 1;
        if (warp == 0) TSL(15);
    }
}

typedef CUresult (*EncodeFn)(CUtensorMap*, CUtensorMapDataType, cuuint32_t, void*, const cuuint64_t*, const cuuint64_t*,
                             const cuuint32_t*, const cuuint32_t*, CUtensorMapInterleave, CUtensorMapSwizzle,
                             CUtensorMapL2promotion, CUtensorMapFloatOOBfill);

void make_map(EncodeFn enc, CUtensorMap* m, void* p, int cols, int rows, int pitch, int bc, int br, int bp, int planes, size_t pstride,
              CUtensorMapSwizzle sw, int promo) {
    cuuint64_t dims[3] = {(cuuint64_t)cols, (cuuint64_t)rows, (cuuint64_t)planes};
    cuuint64_t strides[2] = {(cuuint64_t)pitch * 2, (cuuint64_t)pstride};
    cuuint32_t box[3] = {(cuuint32_t)bc, (cuuint32_t)br, (cuuint32_t)bp};
    cuuint32_t es[3] = {1, 1, 1};
    enc(m, CU_TENSOR_MAP_DATA_TYPE_BFLOAT16, 3, p, dims, strides, box, es, CU_TENSOR_MAP_INTERLEAVE_NONE, sw,
        (CUtensorMapL2promotion)promo, CU_TENSOR_MAP_FLOAT_OOB_FILL_NONE);
}

}

extern "C" void kernel_launch(void* const* d_in, const int* in_sizes, int n_in, void* d_out, int out_size) {
    static EncodeFn enc = nullptr;
    static uint32_t* scratch = nullptr;
    if (!enc) {
        void* fn = nullptr;
        cudaDriverEntryPointQueryResult st;
        cudaGetDriverEntryPoint("cuTensorMapEncodeTiled", &fn, cudaEnableDefault, &st);
        enc = (EncodeFn)fn;
        cudaGetSymbolAddress(&fn, g_scratch);
        scratch = (uint32_t*)(((uintptr_t)fn + 8 * G_SET - 1) & ~(uintptr_t)(8 * G_SET - 1));
        cudaFuncSetAttribute(fused_kernel, cudaFuncAttributeMaxDynamicSharedMemorySize, SMEM_BYTES);
    }
    Params P;
    const CUtensorMapSwizzle none = CU_TENSOR_MAP_SWIZZLE_NONE;
    make_map(enc, &P.m[M_K], d_in[1], 64, NB * HKV * SK, DH, 64, 32, 2, 2, 128, CU_TENSOR_MAP_SWIZZLE_128B, PROMO_KV);
    make_map(enc, &P.m[M_V], d_in[2], 64, NB * HKV * SK, DH, 64, 32, 2, 2, 128, CU_TENSOR_MAP_SWIZZLE_128B, PROMO_KV);
    make_map(enc, &P.m[M_WQ], d_in[3], HQ * DH, DM, HQ * DH, 32, 192, 1, 1, 16, CU_TENSOR_MAP_SWIZZLE_64B, PROMO_W);
    make_map(enc, &P.m[M_WM], d_in[11], 6 * DM, DM, 6 * DM, 32, 192, 1, 1, 16, CU_TENSOR_MAP_SWIZZLE_64B, PROMO_W);
    make_map(enc, &P.m[M_WA], d_in[11], DM, DM, 6 * DM, 16, 192, 2, 2, DM * 2, CU_TENSOR_MAP_SWIZZLE_32B, PROMO_W);
    char *wg = (char*)d_in[7], *wu = (char*)d_in[8], *wo = (char*)d_in[4], *wd = (char*)d_in[9];
    P.zg = wg > wu;
    P.zo = wo > wd;
    const size_t sg = P.zg ? wg - wu : wu - wg, so = P.zo ? wo - wd : wd - wo;
    make_map(enc, &P.m[M_GU], P.zg ? wu : wg, FF, DM, FF, 32, 64, 2, 2, sg, CU_TENSOR_MAP_SWIZZLE_64B, PROMO_GU);
    make_map(enc, &P.m[M_GX], P.zg ? wu : wg, FF, DM, FF, 8, 192, 2, 2, sg, none, PROMO_GX);
    make_map(enc, &P.m[M_OD], P.zo ? wd : wo, DM, FF, DM, 64, 64, 1, 2, so, CU_TENSOR_MAP_SWIZZLE_128B, PROMO_W);
    make_map(enc, &P.m[M_OX], P.zo ? wd : wo, DM, FF, DM, 8, 144, 1, 2, so, none, PROMO_OX);
    P.x = (const __nv_bfloat16*)d_in[0];
    P.wr = (const __nv_bfloat16*)d_in[6];
    P.c = (const __nv_bfloat16*)d_in[10];
    P.out = (__nv_bfloat16*)d_out;
    P.scratch = scratch;
    fused_kernel<<<NCTA, NTHREADS, SMEM_BYTES>>>(P);
}
```

```cpp
#include <cuda_runtime.h>
#include <cuda_bf16.h>
#include <cuda.h>
#include <stdint.h>

typedef unsigned long long u64;

#define W_KV 20
#define W_WO 19
#define W_GU 19
#define W_GU2 W_GU
#define W_WD 13
#define W_MIN -8
#define W_MAX 8
#define GAIN_KV 2
#define GAIN_TAIL 3
#define NK0 2
#define T_CLEAR 116
#define B_CAP 8
#define NPING0 4
#define NPING1 16
#define PROMO_W CU_TENSOR_MAP_L2_PROMOTION_L2_128B
#define PROMO_GX 2
#define PROMO_OX 2
#define PROMO_GU 2
#define PROMO_KV CU_TENSOR_MAP_L2_PROMOTION_L2_256B

namespace {

constexpr int NB = 8, DM = 576, HQ = 32, HKV = 16, SK = 8192, WIN = 2048, DH = 128, FF = 4608;
constexpr int NCTA = 128;
constexpr int NCW = 10;
constexpr int NTHREADS = (NCW + 2) * 32;
constexpr int TILE_BYTES = 8192, NSLOT = 16, NT = 64;
constexpr int SPIN_LIMIT = 1 << 22;

constexpr int OFF_RING = 0;
constexpr int OFF_WM = 121856;
constexpr int OFF_WQ = OFF_WM + 36864;
constexpr int OFF_GU = 0;
constexpr int OFF_WD = 73728;
constexpr int OFF_OX = 131072;
constexpr int OFF_DX = OFF_OX + 4096;
constexpr int OFF_GX = OFF_DX + 4608;
constexpr int OFF_WO = OFF_WQ;
constexpr int OFF_P = OFF_WQ + 36864;
constexpr int P_PITCH = 528;
constexpr int OFF_RED = OFF_P + 16 * P_PITCH;
constexpr int OFF_ORED = OFF_RED + 5 * 4608 - 8704;
constexpr int OFF_ST = OFF_RED + 5 * 4608;
constexpr int OFF_SM = OFF_ST + 640;
constexpr int OFF_RT = OFF_SM + 128;
constexpr int OFF_HU = OFF_RT + 384;
constexpr int OFF_QS = OFF_HU + 128;
constexpr int OFF_WR = OFF_QS + 512;
constexpr int OFF_WIN = OFF_WR + 1152;
constexpr int OFF_BAR = OFF_WIN + 16;
constexpr int BAR_FULL = 6, BAR_WO = 22, BAR_GU = 26, BAR_WD = 35, BAR_EMPTY = 40, BAR_SYNC = 56, BAR_WMF = 59, NBAR = 70;
constexpr int SMEM_BYTES = OFF_BAR + NBAR * 8;

constexpr int D_X1 = 0;
constexpr int D_O = 3072;
constexpr int D_ACT = D_O + 512 * 32;
constexpr int D_H = D_ACT + 576 * 32;
constexpr int D_Q = D_H + 3072;
constexpr int G_M = 2 * (D_Q + NB * HQ * 64);
constexpr int G_CNT = G_M + 288 * 32;
constexpr int G_SET = 1 << 18;
__device__ __forceinline__ int d_part(int unit) { return (64 + unit + (unit & 64)) * 1024; }
constexpr int D_PING = 200 * 1024;
constexpr int G_EPOCH = 201 * 2048;
static_assert(G_CNT < 64 * 2048, "scratch layout");
__device__ uint32_t g_scratch[4 * G_SET];
__device__ __forceinline__ int dual(int w) { return w + (w & ~1023); }
__device__ __forceinline__ int near(int w, int side) { return dual(w) + (((__popc(w & 0x16400) ^ side) & 1) << 10); }

#define TI(i)
#define TS(i)
#define TSL(i)

enum { M_K, M_V, M_GU, M_GX, M_OD, M_OX, M_WQ, M_WM, M_WA, NMAP };
struct Params {
    CUtensorMap m[NMAP];
    const __nv_bfloat16 *x, *c, *wr;
    __nv_bfloat16* out;
    uint32_t* scratch;
    int zg, zo;
};

__device__ __forceinline__ void mbar_init(uint32_t bar, int cnt) {
    asm volatile("mbarrier.init.shared::cta.b64 [%0], %1;" ::"r"(bar), "r"(cnt));
}
__device__ __forceinline__ void mbar_expect(uint32_t bar, uint32_t bytes) {
    asm volatile("mbarrier.arrive.expect_tx.shared::cta.b64 _, [%0], %1;" ::"r"(bar), "r"(bytes) : "memory");
}
__device__ __forceinline__ void mbar_arrive(uint32_t bar) {
    asm volatile("mbarrier.arrive.shared::cta.b64 _, [%0];" ::"r"(bar) : "memory");
}
__device__ __forceinline__ void mbar_wait(uint32_t bar, uint32_t parity) {
    asm volatile("{\n.reg .pred p;\n.reg .u32 c;\n"
                 "mbarrier.try_wait.parity.shared::cta.b64 p, [%0], %1;\n@p bra DONE;\nmov.u32 c, %2;\n"
                 "AGAIN:\nmbarrier.try_wait.parity.shared::cta.b64 p, [%0], %1;\nsub.u32 c, c, 1;\n"
                 "setp.eq.or.u32 p, c, 0, p;\n@!p bra AGAIN;\nDONE:\n}"
                 ::"r"(bar), "r"(parity), "n"(SPIN_LIMIT) : "memory");
}
__device__ __forceinline__ bool mbar_test(uint32_t bar, uint32_t parity) {
    uint32_t ok;
    asm volatile("{\n.reg .pred p;\nmbarrier.test_wait.parity.shared::cta.b64 p, [%1], %2;\nselp.u32 %0, 1, 0, p;\n}"
                 : "=r"(ok) : "r"(bar), "r"(parity) : "memory");
    return ok;
}
__device__ __forceinline__ void mbar_wait_lanes(uint32_t bar) {
    mbar_wait(bar, 0);
    __syncwarp();
}
__device__ __forceinline__ void tma3d_hint(uint32_t dst, const CUtensorMap* m, int x, int y, int z, uint32_t bar, u64 pol) {
    asm volatile("cp.async.bulk.tensor.3d.shared::cluster.global.mbarrier::complete_tx::bytes.L2::cache_hint"
                 " [%0], [%1, {%2, %3, %4}], [%5], %6;"
                 ::"r"(dst), "l"(m), "r"(x), "r"(y), "r"(z), "r"(bar), "l"(pol) : "memory");
}
__device__ __forceinline__ void tma3d(uint32_t dst, const CUtensorMap* m, int x, int y, int z, uint32_t bar) {
    asm volatile("cp.async.bulk.tensor.3d.shared::cluster.global.mbarrier::complete_tx::bytes [%0], [%1, {%2, %3, %4}], [%5];"
                 ::"r"(dst), "l"(m), "r"(x), "r"(y), "r"(z), "r"(bar) : "memory");
}
__device__ __forceinline__ void bar_sync(int id, int n) { asm volatile("bar.sync %0, %1;" ::"r"(id), "r"(n) : "memory"); }
__device__ __forceinline__ void bar_arrive(int id, int n) { asm volatile("bar.arrive %0, %1;" ::"r"(id), "r"(n) : "memory"); }
__device__ __forceinline__ void ldsm4(uint32_t (&r)[4], uint32_t a) {
    asm volatile("ldmatrix.sync.aligned.m8n8.x4.shared.b16 {%0,%1,%2,%3}, [%4];"
                 : "=r"(r[0]), "=r"(r[1]), "=r"(r[2]), "=r"(r[3]) : "r"(a) : "memory");
}
__device__ __forceinline__ void ldsm4t(uint32_t (&r)[4], uint32_t a) {
    asm volatile("ldmatrix.sync.aligned.m8n8.x4.trans.shared.b16 {%0,%1,%2,%3}, [%4];"
                 : "=r"(r[0]), "=r"(r[1]), "=r"(r[2]), "=r"(r[3]) : "r"(a) : "memory");
}
__device__ __forceinline__ void mma(float (&c)[4], uint32_t a0, uint32_t a1, uint32_t a2, uint32_t a3, uint32_t b0, uint32_t b1) {
    asm volatile("mma.sync.aligned.m16n8k16.row.col.f32.bf16.bf16.f32 {%0,%1,%2,%3}, {%4,%5,%6,%7}, {%8,%9}, {%0,%1,%2,%3};"
                 : "+f"(c[0]), "+f"(c[1]), "+f"(c[2]), "+f"(c[3])
                 : "r"(a0), "r"(a1), "r"(a2), "r"(a3), "r"(b0), "r"(b1));
}
__device__ __forceinline__ uint32_t movm(uint32_t a) {
    uint32_t d;
    asm volatile("movmatrix.sync.aligned.m8n8.trans.b16 %0, %1;" : "=r"(d) : "r"(a));
    return d;
}
__device__ __forceinline__ uint32_t lds32(uint32_t a) { uint32_t v; asm volatile("ld.shared.b32 %0, [%1];" : "=r"(v) : "r"(a) : "memory"); return v; }
__device__ __forceinline__ float2 lds64f(uint32_t a) { float2 v; asm volatile("ld.shared.v2.f32 {%0,%1}, [%2];" : "=f"(v.x), "=f"(v.y) : "r"(a) : "memory"); return v; }
__device__ __forceinline__ uint4 lds128(uint32_t a) { uint4 v; asm volatile("ld.shared.v4.b32 {%0,%1,%2,%3}, [%4];" : "=r"(v.x), "=r"(v.y), "=r"(v.z), "=r"(v.w) : "r"(a) : "memory"); return v; }
__device__ __forceinline__ void sts32(uint32_t a, uint32_t v) { asm volatile("st.shared.b32 [%0], %1;" ::"r"(a), "r"(v) : "memory"); }
__device__ __forceinline__ void sts16(uint32_t a, uint16_t v) { asm volatile("st.shared.b16 [%0], %1;" ::"r"(a), "h"(v) : "memory"); }
__device__ __forceinline__ void sts64(uint32_t a, uint32_t x, uint32_t y) { asm volatile("st.shared.v2.b32 [%0], {%1,%2};" ::"r"(a), "r"(x), "r"(y) : "memory"); }
__device__ __forceinline__ void sts128(uint32_t a, uint32_t x, uint32_t y, uint32_t z, uint32_t w) {
    asm volatile("st.shared.v4.b32 [%0], {%1,%2,%3,%4};" ::"r"(a), "r"(x), "r"(y), "r"(z), "r"(w) : "memory");
}
__device__ __forceinline__ void sts128f(uint32_t a, const float (&c)[4]) {
    sts128(a, __float_as_uint(c[0]), __float_as_uint(c[1]), __float_as_uint(c[2]), __float_as_uint(c[3]));
}

__device__ __forceinline__ float sel4(const float (&c)[4], int t) { return (t & 2) ? ((t & 1) ? c[3] : c[2]) : ((t & 1) ? c[1] : c[0]); }

__device__ __forceinline__ uint32_t pin(uint32_t v) { return __shfl_xor_sync(0xffffffffu, v, 0); }
template <typename T>
__device__ __forceinline__ T* at(T* base, uint32_t bytes) { return reinterpret_cast<T*>(reinterpret_cast<char*>(base) + bytes); }

__device__ __forceinline__ uint32_t clock32(uint32_t dep) {
    uint32_t t;
    asm volatile("{\n.reg .pred p;\nsetp.eq.u32 p, %1, 0x9e3779b9;\n@p nanosleep.u32 1;\nmov.u32 %0, %clock;\n}" : "=r"(t) : "r"(dep) : "memory");
    return t;
}

__device__ __forceinline__ uint32_t nz(uint32_t v) { return v ? v : 0x80000000u; }
__device__ __forceinline__ void st1(uint32_t* p, uint32_t a) { asm volatile("st.relaxed.gpu.global.b32 [%0], %1;" ::"l"(p), "r"(a) : "memory"); }
__device__ __forceinline__ void st2(uint32_t* p, uint32_t a, uint32_t b) {
    asm volatile("st.relaxed.gpu.global.v2.b32 [%0], {%1,%2};" ::"l"(p), "r"(a), "r"(b) : "memory");
}
__device__ __forceinline__ void zero4(uint32_t* p) { asm volatile("st.relaxed.gpu.global.v4.b32 [%0], {%1,%1,%1,%1};" ::"l"(p), "r"(0) : "memory"); }
__device__ __forceinline__ void put1d(uint32_t* p, uint32_t a) { a = nz(a), st1(p, a), st1(p + 1024, a); }
__device__ __forceinline__ void put2d(uint32_t* p, uint32_t a, uint32_t b) { a = nz(a), b = nz(b), st2(p, a, b), st2(p + 1024, a, b); }
__device__ __forceinline__ uint32_t ld1(const uint32_t* p) {
    uint32_t v;
    asm volatile("ld.relaxed.gpu.global.b32 %0, [%1];" : "=r"(v) : "l"(p) : "memory");
    return v;
}
template <int N, int V>
__device__ __forceinline__ void fetch(const uint32_t* p, int stride, uint32_t (&a)[N * V]) {
#pragma unroll
    for (int i = 0; i < N; i++) {
        if (V == 1)
            asm volatile("{\n.reg .pred p;\nsetp.eq.u32 p, %0, 0;\n@p ld.relaxed.gpu.global.b32 %0, [%1];\n}"
                         : "+r"(a[i]) : "l"(p + i * stride) : "memory");
        if (V == 4)
            asm volatile("{\n.reg .pred p;\nsetp.eq.u32 p, %4, 0;\n@p ld.relaxed.gpu.global.v4.b32 {%0,%1,%2,%3}, [%5];\n}"
                         : "+r"(a[V * i]), "+r"(a[V * i + V / 4]), "+r"(a[V * i + V / 2]), "+r"(a[V * i + V - 1])
                         : "r"(min(min(a[V * i], a[V * i + V / 4]), min(a[V * i + V / 2], a[V * i + V - 1]))), "l"(p + i * stride) : "memory");
    }
}
template <int N>
__device__ __forceinline__ bool missing(const uint32_t (&a)[N]) {
    uint32_t lo = a[0];
#pragma unroll
    for (int i = 1; i < N; i++) lo = min(lo, a[i]);
    return __any_sync(0xffffffffu, lo == 0);
}
template <int N, int V>
__device__ __forceinline__ void get(const uint32_t* p, int stride, uint32_t (&a)[N * V]) {
    int it = 0;
    do fetch<N, V>(p, stride, a);
    while (missing(a) & (++it < SPIN_LIMIT));
}
__device__ __forceinline__ void cp16(uint32_t dst, const void* src) {
    asm volatile("cp.async.cg.shared.global [%0], [%1], 16;" ::"r"(dst), "l"(src) : "memory");
}

__device__ __forceinline__ uint32_t pack2(float lo, float hi) {
    uint32_t r;
    asm("cvt.rn.bf16x2.f32 %0, %1, %2;" : "=r"(r) : "f"(hi), "f"(lo));
    return r;
}
__device__ __forceinline__ float rbf(float x) { return __uint_as_float(pack2(0.f, x)); }
__device__ __forceinline__ float blo(uint32_t v) { return __uint_as_float(v << 16); }
__device__ __forceinline__ float bhi(uint32_t v) { return __uint_as_float(v & 0xffff0000u); }
__device__ __forceinline__ uint32_t badd2(uint32_t a, uint32_t b) { uint32_t r; asm("add.rn.bf16x2 %0, %1, %2;" : "=r"(r) : "r"(a), "r"(b)); return r; }
__device__ __forceinline__ uint32_t bsub2(uint32_t a, uint32_t b) { uint32_t r; asm("sub.rn.bf16x2 %0, %1, %2;" : "=r"(r) : "r"(a), "r"(b)); return r; }
__device__ __forceinline__ uint32_t bmul2(uint32_t a, uint32_t b) { uint32_t r; asm("mul.rn.bf16x2 %0, %1, %2;" : "=r"(r) : "r"(a), "r"(b)); return r; }
__device__ __forceinline__ float ex2(float x) { float r; asm("ex2.approx.ftz.f32 %0, %1;" : "=f"(r) : "f"(x)); return r; }
__device__ __forceinline__ float rcp(float x) { float r; asm("rcp.approx.ftz.f32 %0, %1;" : "=f"(r) : "f"(x)); return r; }
__device__ __forceinline__ float sqrt_f(float x) { float r; asm("sqrt.approx.ftz.f32 %0, %1;" : "=f"(r) : "f"(x)); return r; }
constexpr float LOG2E = 1.4426950408889634f;
constexpr uint32_t ONE2 = 0x3f803f80u;
__device__ __forceinline__ float sigmoid_f(float x) { return rcp(1.0f + ex2(-LOG2E * x)); }
__device__ __forceinline__ uint32_t silu2(uint32_t v) {
    const float a = blo(v), b = bhi(v);
    return pack2(a * sigmoid_f(a), b * sigmoid_f(b));
}
__device__ __forceinline__ float quad_sum(float v) {
    v += __shfl_xor_sync(0xffffffffu, v, 1);
    return v + __shfl_xor_sync(0xffffffffu, v, 2);
}
__device__ __forceinline__ void ln_partial(const uint32_t (&v)[8], uint32_t dst, bool writer) {
    float s0 = 0.f, s1 = 0.f;
#pragma unroll
    for (int i = 0; i < 8; i++) {
        s0 += blo(v[i]);
        s1 += bhi(v[i]);
    }
    const float mean = quad_sum(s0 + s1) * (1.0f / 64);
    s0 = s1 = 0.f;
#pragma unroll
    for (int i = 0; i < 8; i++) {
        const float a = blo(v[i]) - mean, b = bhi(v[i]) - mean;
        s0 = fmaf(a, a, s0);
        s1 = fmaf(b, b, s1);
    }
    s0 = quad_sum(s0 + s1);
    if (writer) sts64(dst, __float_as_uint(mean), __float_as_uint(s0));
}
__device__ __forceinline__ void ln_combine(uint32_t src, uint32_t& mean2, float& inv) {
    float m[10], q0 = 0.f, q1 = 0.f, s = 0.f;
#pragma unroll
    for (int i = 0; i < 5; i++) {
        const uint4 v = lds128(src + i * 16);
        m[2 * i] = __uint_as_float(v.x);
        m[2 * i + 1] = __uint_as_float(v.z);
        q0 += __uint_as_float(v.y);
        if (i < 4) q1 += __uint_as_float(v.w);
    }
    const float mean = (((m[0] + m[1]) + (m[2] + m[3])) + ((m[4] + m[5]) + (m[6] + m[7])) + m[8]) * (1.0f / 9);
#pragma unroll
    for (int i = 0; i < 9; i++) s = fmaf(m[i] - mean, m[i] - mean, s);
    const float var = fmaf(s, 64.f, q0 + q1) * (1.0f / DM);
    mean2 = pack2(mean, mean);
    inv = rcp(rbf(sqrt_f(rbf(rbf(var) + 1e-5f))));
}
__device__ __forceinline__ uint32_t modulate2(uint32_t x, uint32_t mean2, float inv, uint32_t shift, uint32_t onep) {
    const uint32_t d = bsub2(x, mean2);
    return badd2(bmul2(pack2(blo(d) * inv, bhi(d) * inv), onep), shift);
}
template <int N>
__device__ __forceinline__ void sum_frags(float (&c)[4], uint32_t addr, int stride) {
#pragma unroll
    for (int w = 0; w < N; w++) {
        const uint4 v = lds128(addr + w * stride);
        c[0] += __uint_as_float(v.x); c[1] += __uint_as_float(v.y);
        c[2] += __uint_as_float(v.z); c[3] += __uint_as_float(v.w);
    }
}

template <int ST>
__device__ __forceinline__ void project(uint32_t sm, const uint32_t* src, uint32_t* dst, uint32_t rowoff, uint32_t reds, int warp, int lane) {
    constexpr int NW = ST ? 9 : 8;
    const uint32_t red = sm + (ST ? OFF_WO : OFF_P);
    if (warp < NW) {
        const uint32_t wbar = sm + OFF_BAR + ((ST ? BAR_WD : BAR_WO) + (warp >> 1)) * 8;
        const uint32_t ab = sm + (ST ? OFF_WD : OFF_WO) + rowoff;
        const uint32_t ax = sm + (ST ? OFF_DX : OFF_OX) + ((rowoff >> 7) << 4);
        uint32_t a[10][4] = {}, b[4] = {};
        bool have_w = false;
        int it = 0;
        do {
            if (!have_w && __all_sync(0xffffffffu, mbar_test(wbar, 0))) {
                have_w = true;
#pragma unroll
                for (int i = 0; i < 10; i++) ldsm4t(a[i], i % 5 < 4 ? (ab ^ ((i % 5) << 5)) + (i / 5) * 2048 : ax + (i / 5) * 256);
            }
            if (ST) fetch<4, 1>(src, 32, b);
            else fetch<1, 4>(src, 0, b);
        } while ((missing(b) | !have_w) & (++it < SPIN_LIMIT));
        if (warp == 0) TSL(ST ? 24 : 21);
        float acc[5][4] = {};
#pragma unroll
        for (int i = 0; i < 10; i++) mma(acc[i % 5], a[i][0], a[i][1], a[i][2], a[i][3], b[2 * (i / 5)], b[2 * (i / 5) + 1]);
#pragma unroll
        for (int u = 0; u < 9; u++)
            sts64(red + u * 2304 + (reds & 0xffff), __float_as_uint(acc[u >> 1][2 * (u & 1)]), __float_as_uint(acc[u >> 1][2 * (u & 1) + 1]));
    }
    bar_sync(3, 288);
    float s[2][2] = {};
#pragma unroll
    for (int w = 0; w < NW; w++) {
        const float2 v = lds64f(red + (reds >> 16) + w * 256);
        s[w & 1][0] += v.x;
        s[w & 1][1] += v.y;
    }
    const uint32_t p0 = (__float_as_uint(s[0][0] + s[1][0]) | 1) ^ ST, p1 = (__float_as_uint(s[0][1] + s[1][1]) | 1) ^ ST;
    st2(dst, p0, p1), st2(dst + 1024, p0, p1);
}

template <int ST>
__device__ __forceinline__ uint32_t reduce16(const uint32_t* src, int lane) {
    uint32_t a[8], bad[4] = {1, 1, 1, 1};
    int it = 0;
#pragma unroll
    for (int i = 0; i < 8; i++) a[i] = 0;
    do {
#pragma unroll
        for (int i = 0; i < 4; i++)
            asm volatile("{\n.reg .pred p;\nsetp.ne.u32 p, %2, 0;\n@p ld.relaxed.gpu.global.v2.b32 {%0,%1}, [%3];\n}"
                         : "+r"(a[2 * i]), "+r"(a[2 * i + 1]) : "r"(bad[i]), "l"(src + i * 64) : "memory");
#pragma unroll
        for (int i = 0; i < 4; i++) bad[i] = (ST ? a[2 * i] | a[2 * i + 1] : ~(a[2 * i] & a[2 * i + 1])) & 1;
    } while (__any_sync(0xffffffffu, (bad[0] | bad[1] | bad[2] | bad[3]) != 0) & (++it < SPIN_LIMIT));
    float s0 = (__uint_as_float(a[0]) + __uint_as_float(a[2])) + (__uint_as_float(a[4]) + __uint_as_float(a[6]));
    float s1 = (__uint_as_float(a[1]) + __uint_as_float(a[3])) + (__uint_as_float(a[5]) + __uint_as_float(a[7]));
#pragma unroll
    for (int o = 8; o < 32; o <<= 1) {
        s0 += __shfl_xor_sync(0xffffffffu, s0, o);
        s1 += __shfl_xor_sync(0xffffffffu, s1, o);
    }
    const uint32_t y = pack2(s0, s1);
    return __byte_perm(y, __shfl_xor_sync(0xffffffffu, y, 4), (lane & 4) ? 0x3276 : 0x5410);
}

__global__ void __launch_bounds__(NTHREADS, 1) fused_kernel(const __grid_constant__ Params P) {
    extern __shared__ __align__(1024) char smem_raw[];
    constexpr uint32_t sm = 1024;
    const int tid = threadIdx.x, lane = tid & 31;
    const int cta = blockIdx.x, grp = cta >> 3, sub = cta & 7;
    const uint32_t bars = sm + OFF_BAR;
    const int row0 = (sub * HKV + grp) * SK + (SK - WIN);
    u64 pol;
    asm volatile("createpolicy.fractional.L2::evict_first.b64 %0, 1.0;" : "=l"(pol));
    if (tid == NCW * 32) {
        TS(0);
        const int n0 = cta < 108 ? 0 : 3;
#pragma unroll
        for (int i = 0; i < 6; i++) mbar_init(bars + i * 8, 1);
        asm volatile("fence.mbarrier_init.release.cluster;" ::: "memory");
#pragma unroll
        for (int i = 0; i < 3; i++) {
            mbar_expect(bars + (n0 + i) * 8, 12288);
            tma3d(sm + OFF_WM + (n0 + i) * 12288, &P.m[cta < 36 ? M_WA : cta < 108 ? M_WM : M_WQ], cta < 36 ? 16 * cta : 32 * cta,
                  i * 192, 0, bars + (n0 + i) * 8);
            TI(n0 + i);
        }
        TS(26);
    }
    if (tid == NCW * 32 + 32) {
#pragma unroll
        for (int i = 0; i < 4; i++) mbar_init(bars + (BAR_FULL + i) * 8, 1);
        asm volatile("fence.mbarrier_init.release.cluster;" ::: "memory");
#pragma unroll
        for (int t = 0; t < NK0; t++) {
            mbar_expect(bars + (BAR_FULL + t) * 8, TILE_BYTES);
            tma3d_hint(sm + OFF_RING + t * TILE_BYTES, &P.m[M_K], 0, row0 + t * 32, 0, bars + (BAR_FULL + t) * 8, pol);
            TI(6 + t);
        }
    }
    if (tid < 288 && cta < 108) {
#pragma unroll
        for (int i = 0; i < 2; i++) {
            const int row = (lane >> 3) + 4 * i, so = row * DM + (tid >> 5) * 64 + (lane & 7) * 8;
            const uint32_t d = sm + OFF_RED + (tid >> 5) * 2048 + row * 128 + (((lane & 7) ^ row) << 4);
            cp16(d, P.c + so);
            if (cta < 36) cp16(d + 1024, P.x + so);
        }
    }
    uint32_t* const g0 = P.scratch;
    const uint32_t epoch = ld1(g0 + G_EPOCH);
    const int warp = __shfl_sync(0xffffffffu, tid >> 5, 0);
    auto pace = [&](int t, int gain) {
        const int d = (int)atomicAdd(g0 + (epoch & 1) * G_SET + G_CNT, 1u) - 32 * (t - 16) - 16;
        sts32(sm + OFF_WIN, min(max((d * gain + 32) >> 6, W_MIN), W_MAX));
    };

    if (warp >= NCW) {
        const int pw = warp - NCW;
        bar_arrive(1, (NCW + 1) * 32);
        if (pw && lane < M_WQ) asm volatile("prefetch.tensormap [%0];" ::"l"(&P.m[M_WQ - lane]) : "memory");
        if (tid == NCW * 32) sts32(sm + OFF_WIN, 0);
        __syncwarp();
        bar_sync(15, NTHREADS);
        if (lane == 0) {
            if (pw == 0 && cta < 108) {
#pragma unroll 1
                for (int n = 3; n < 6; n++) {
                    mbar_expect(bars + n * 8, 12288);
                    mbar_wait(bars + (n - 3) * 8, 0);
                    tma3d(sm + OFF_WM + n * 12288, &P.m[M_WQ], 32 * cta, (n - 3) * 192, 0, bars + n * 8);
                    TI(n);
                }
            }
#pragma unroll 1
            for (int t = (2 - pw) * NK0; t < 2 * NK0 + 3 * (1 - pw); t++) {
                mbar_expect(bars + (BAR_FULL + t) * 8, TILE_BYTES);
                mbar_wait(bars + (t + (pw ? BAR_FULL - NK0 : 3 - 2 * NK0)) * 8, 0);
                tma3d_hint(sm + OFF_RING + t * TILE_BYTES, &P.m[M_K], 0, row0 + t * 32, 0, bars + (BAR_FULL + t) * 8, pol);
                TI(6 + t);
            }
            if (pw == 0) {
#pragma unroll 1
                for (int t = 2 * NK0 + 3; t < 2 * NT; t++) {
                    if (t == 14 && cta < 108) mbar_wait(bars + BAR_WMF * 8, 0);
                    if (t == 15) TS(30);
                    const int m = t - ((W_KV + (int)lds32(sm + OFF_WIN) + ((0xd8 >> (2 * t & 6)) & 3)) >> 2);
                    const uint32_t fb = bars + (BAR_FULL + (t & 15)) * 8;
                    mbar_wait(fb + (BAR_EMPTY - BAR_FULL) * 8, (~t >> 4) & 1);
                    mbar_expect(fb, TILE_BYTES);
                    mbar_wait(bars + (BAR_FULL + (m & 15)) * 8, (m >> 4) & 1);
                    tma3d_hint(sm + OFF_RING + (t & 15) * TILE_BYTES, &P.m[t >> 6], 0, row0 + (t & (NT - 1)) * 32, 0, fb, pol);
                    TI(6 + t);
                    if (t == T_CLEAR) mbar_arrive(bars + (BAR_SYNC + 1) * 8);
                }
                mbar_arrive(bars + (BAR_SYNC + 2) * 8);
                mbar_wait(bars + BAR_SYNC * 8, 0);
                auto window = [&](int b, int w) {
                    b -= max((w + (int)lds32(sm + OFF_WIN) + ((0xd8 >> (2 * b & 6)) & 3)) >> 2, 1);
                    b = min(b, BAR_GU + B_CAP);
                    mbar_wait(bars + b * 8, b < BAR_WO);
                };
#pragma unroll 1
                for (int i = 0; i < 4; i++) {
                    window(BAR_WO + i, W_WO);
                    tma3d(sm + OFF_WO + i * 8192, &P.m[M_OD], 64 * sub, grp * 256 + i * 64, P.zo, bars + (BAR_WO + i) * 8);
                    tma3d(sm + OFF_OX + i * 1024, &P.m[M_OX], 512 + 8 * sub, grp * 256 + i * 64, P.zo, bars + (BAR_WO + i) * 8);
                    TI(134 + i);
                }
                TS(28);
#pragma unroll 1
                for (int i = 0; i < 9; i++) {
                    mbar_wait(bars + (BAR_EMPTY + i) * 8, 1);
                    window(BAR_GU + i, sub < 4 ? W_GU : W_GU2);
                    tma3d(sm + OFF_GU + i * 8192, &P.m[M_GU], grp * 288 + 32 * sub, i * 64, 0, bars + (BAR_GU + i) * 8);
                    if (sub < 4) tma3d(sm + OFF_GX + i * 2048, &P.m[M_GX], grp * 288 + 256 + 8 * sub, i * 64, 0, bars + (BAR_GU + i) * 8);
                    TI(138 + i);
                }
                TS(29);
#pragma unroll 1
                for (int i = 0; i < 5; i++) {
                    const int r = min(i * 64, 224);
                    mbar_wait(bars + (BAR_EMPTY + 9 + i) * 8, 1);
                    window(BAR_WD + i, W_WD);
                    tma3d(sm + OFF_WD + r * 128, &P.m[M_OD], 64 * sub, grp * 288 + r, P.zo ^ 1, bars + (BAR_WD + i) * 8);
                    tma3d(sm + OFF_DX + r * 16, &P.m[M_OX], 512 + 8 * sub, grp * 288 + r, P.zo ^ 1, bars + (BAR_WD + i) * 8);
                    TI(147 + i);
                }
            } else {
#pragma unroll 1
                for (int i = BAR_WO; i < BAR_WD + 5; i++) mbar_expect(bars + i * 8, i < BAR_GU || i >= BAR_WD ? 9216 : sub < 4 ? 10240 : 8192);
                mbar_arrive(bars + BAR_SYNC * 8);
                mbar_wait(bars + (BAR_SYNC + 2) * 8, 0);
#pragma unroll 1
                for (int t = 124 + (cta & 3); t < 144; t += 4) {
                    mbar_wait(bars + (BAR_FULL - 112 + t) * 8, t < 128);
                    pace(t, GAIN_TAIL);
                }
            }
        }
        return;
    }

    if (lane == 0) {
#pragma unroll
        for (int i = 0; i < 6; i++) mbar_init(bars + (10 + warp * 6 + i) * 8, 1);
        asm volatile("fence.mbarrier_init.release.cluster;" ::: "memory");
    }
    __syncwarp();
    if (warp < 9) bar_arrive(15, NTHREADS);
    const int g = lane >> 2, t4 = lane & 3;
    uint32_t* const gs = g0 + (epoch & 1) * G_SET;

    if (warp < 9) {
        const int off_h = (cta < 36 ? dual(D_H + 2 * cta * 32) : G_M + 4 * (cta - 36) * 32) + tid;
        const int off_h2 = off_h + (cta < 36 ? 1024 : 64);
        const int off_q = dual(D_Q + g * (HQ * 64) + cta * 16) + warp * 8 + t4 * 2;
        uint32_t bf[8] = {}, xp = 0, mean2 = 0;
        float inv = 0.f;
        if (cta < 36) xp = __ldg(reinterpret_cast<const uint32_t*>(P.x) + g * (DM / 2) + 8 * cta + 4 * (warp & 1) + t4);
        if (warp < 2) {
            st2(gs + off_q, 0, 0), st2(gs + off_q + 1024, 0, 0);
            if (cta < 36) st1(gs + off_h, 0), st1(gs + off_h2, 0);
        }
        if (cta < 108) {
            asm volatile("cp.async.wait_all;" ::: "memory");
            __syncwarp();
            const uint32_t fa = sm + OFF_RED + warp * 2048 + (lane & 7) * 128 + (((lane >> 3) ^ (lane & 7)) << 4);
            ldsm4(reinterpret_cast<uint32_t(&)[4]>(bf[0]), fa);
            ldsm4(reinterpret_cast<uint32_t(&)[4]>(bf[4]), fa ^ 64);
            if (cta < 36) {
                uint32_t xv[8];
                ldsm4(reinterpret_cast<uint32_t(&)[4]>(xv[0]), fa + 1024);
                ldsm4(reinterpret_cast<uint32_t(&)[4]>(xv[4]), (fa ^ 64) + 1024);
                ln_partial(xv, sm + OFF_ST + g * 80 + warp * 8, t4 == 0);
            }
#pragma unroll
            for (int i = 0; i < 8; i++) bf[i] = silu2(bf[i]);
        }
        if (warp == 0) TSL(18);
        bar_sync(1, (NCW + 1) * 32);
        if (cta < 36 && warp < 2) ln_combine(sm + OFF_ST + g * 80, mean2, inv);
        const int r = warp * 64 + (lane >> 4) * 8 + (lane & 7), hi8 = (lane >> 3) & 1, box = warp / 3;
#pragma unroll 1
        for (int pass = cta < 108 ? 0 : 1; pass < 2; pass++) {
            const bool pa = pass == 0 && cta < 36;
            const uint32_t ab = sm + OFF_WM + pass * 36864 +
                                (pa ? (box + hi8) * 6144 + r * 32 + ((lane & 4) << 2) : r * 64 + (((2 * hi8) ^ ((r >> 1) & 3)) << 4));
            const uint32_t as = pa ? 512 : 1024, red = sm + OFF_RED + pass * 9216;
            mbar_wait(bars + (pass * 3 + box) * 8, 0);
            if (warp == 8) TSL(pass ? 31 : 19);
            uint32_t a[4][2][4];
#pragma unroll
            for (int i = 0; i < 4; i++) {
                ldsm4t(a[i][0], ab + i * as);
                ldsm4t(a[i][1], (ab ^ 16) + i * as);
            }
            if (pass) {
                bar_sync(8, NCW * 32);
#pragma unroll
                for (int i = 0; i < 8; i++) bf[i] = 0;
                get<8, 1>(gs + near(D_H + warp * 256, lds32(sm + OFF_WIN + 4)) + lane, 32, bf);
                if (warp == 0) TSL(3);
            }
            float acc[2][4] = {};
#pragma unroll
            for (int i = 0; i < 4; i++)
#pragma unroll
                for (int m = 0; m < 2; m++) mma(acc[m], a[i][m][0], a[i][m][1], a[i][m][2], a[i][m][3], bf[2 * i], bf[2 * i + 1]);
            sts128f(red + tid * 16, acc[0]);
            sts128f(red + 4608 + tid * 16, acc[1]);
            bar_sync(3, 288);
            if (warp < 2) {
                float c[4] = {};
                sum_frags<9>(c, red + warp * 4608 + lane * 16, 512);
                uint32_t lo = movm(pack2(c[0], c[1])), hi = movm(pack2(c[2], c[3]));
                if (pass) {
                    put2d(gs + off_q, lo, hi);
                    if (warp == 0) TSL(4);
                } else {
                    const uint32_t hi1 = badd2(hi, ONE2);
                    if (pa) hi = lo = modulate2(xp, mean2, inv, lo, hi1);
                    if (cta >= 72 && cta < 90) lo = badd2(lo, ONE2), hi = hi1;
                    st1(gs + off_h, nz(lo));
                    st1(gs + off_h2, nz(hi));
                    if (warp == 0 && pa) TSL(2);
                }
            } else if (tid == 64 && pass == 0) {
                mbar_arrive(bars + BAR_WMF * 8);
            }
        }
    } else {
        if ((uint32_t)__cvta_generic_to_shared(smem_raw) != sm) __trap();
        uint32_t* const ping = g0 + dual(D_PING) + cta * 8;
        if (lane < 16) st1(ping + (lane >> 3) * 1024 + (lane & 7), 0);
        bar_sync(15, NTHREADS);
        uint32_t best[2] = {~0u, ~0u}, v = 0;
#pragma unroll 1
        for (int part = 0; part < 2; part++) {
            if (lane == 0) {
#pragma unroll 1
                for (int r = part ? NPING1 : NPING0; r > 0; r--) {
#pragma unroll
                    for (int k = 0; k < 2; k++) {
                        const uint32_t t0 = clock32(v);
                        v = atomicExch(ping + k * 1024, t0);
                        best[k] = min(best[k], clock32(v) - t0);
                    }
                }
                sts32(sm + OFF_WIN + 4 + 4 * part, ((best[1] < best[0]) ^ __popc(D_PING & 0x16400)) & 1);
            }
            __syncwarp();
            if (part) break;
            TSL(20);
            bar_arrive(8, NCW * 32);
            mbar_wait(bars + 5 * 8, 0);
            uint32_t a[4] = {};
            get<1, 4>(gs + near(D_Q + (sub * HQ + 2 * grp) * 64, lds32(sm + OFF_WIN + 4)) + lane * 4, 0, a);
            sts128(sm + OFF_QS + lane * 16, a[0], a[1], a[2], a[3]);
            __syncwarp();
            TSL(5);
            bar_arrive(4, 288);
        }
#pragma unroll
        for (int i = lane; i < 72; i += 32) cp16(sm + OFF_WR + i * 16, P.wr + i * 8);
        asm volatile("cp.async.wait_all;" ::: "memory");
        __syncwarp();
        bar_arrive(2, NCW * 32);
        if (cta == 0 && lane == 0) st1(g0 + (~epoch & 1) * G_SET + G_CNT, 0);
        mbar_wait(bars + (BAR_SYNC + 1) * 8, 0);
#pragma unroll 1
        for (int c = 0; c < 4; c++) {
            uint32_t* const pg = g0 + (c >> 1) * G_SET + (c & 1) * 1024;
            zero4(pg + dual(D_O + cta * 128) + lane * 4);
            zero4(pg + dual(D_ACT + (grp * 36 + 4 * sub) * 32) + lane * 4);
            if (lane < 8 ? sub < 4 : lane < 16 && cta < 72)
                zero4(pg + dual(lane < 8 ? D_ACT + (grp * 36 + 32 + sub) * 32 : D_X1 + cta * 32) + (lane & 7) * 4);
        }
#pragma unroll 1
        for (int u = 0; u < 9; u++) zero4(g0 + dual(d_part(u < 8 ? 8 * sub + u : 64 + sub)) + (lane >> 4) * 1024 + grp * 64 + (lane & 15) * 4);
        __syncwarp();
        bar_arrive(5, NCW * 32);
        {
            uint32_t* const nx = g0 + (~epoch & 1) * G_SET;
            uint32_t* const q = nx + dual(D_Q + g * (HQ * 64) + cta * 16) + t4 * 4;
            zero4(q), zero4(q + 1024);
            if (cta < 108) zero4(nx + (cta < 36 ? dual(D_H + 2 * cta * 32) + (lane >> 4) * (1024 - 64) : G_M + 4 * (cta - 36) * 32) + lane * 4);
        }
        return;
    }

    const uint32_t tile = sm + OFF_RING + warp * TILE_BYTES;
    const uint32_t fullb = bars + (BAR_FULL + warp) * 8;
    const uint32_t pw = sm + OFF_P + warp * (2 * P_PITCH);
    const bool pacer = (tid & 127) == (cta & 3) * 32;
    if (warp < 8) {
        {
            uint32_t q0[8], q1[8];
            bar_sync(4, 288);
#pragma unroll
            for (int i = 0; i < 8; i++) {
                const float2 v = lds64f(sm + OFF_QS + (g & 1) * 256 + i * 32 + t4 * 8);
                q0[i] = __float_as_uint(v.x), q1[i] = __float_as_uint(v.y);
            }
            uint32_t sp = pw + (t4 & 1) * P_PITCH + ((t4 >> 1) * 8 + g) * 2;
#pragma unroll 1
            for (int it = 0; it < 8; it++, sp += 64) {
                const uint32_t ab = tile + (it & 1) * (8 * TILE_BYTES) + (lane & 15) * 128 + (((lane >> 4) ^ (lane & 7)) << 4);
                mbar_wait(fullb + (it & 1) * 64, (it >> 1) & 1);
                float acc[2][2][4] = {};
#pragma unroll
                for (int ks = 0; ks < 8; ks++)
#pragma unroll
                    for (int m = 0; m < 2; m++) {
                        uint32_t a[4];
                        ldsm4(a, (ab ^ ((ks & 3) << 5)) + (ks >> 2) * 4096 + m * 2048);
                        mma(acc[m][ks & 1], a[0], a[1], a[2], a[3], (ks & 1) ? q1[ks - 1] : q0[ks], (ks & 1) ? q1[ks] : q0[ks + 1]);
                    }
                __syncwarp();
                if (lane == 0) mbar_arrive(fullb + (it & 1) * 64 + (BAR_EMPTY - BAR_FULL) * 8);
#pragma unroll
                for (int m = 0; m < 2; m++) {
                    const float s = sel4(acc[m][0], t4) + sel4(acc[m][1], t4);
                    sts16(sp + m * 32, (uint16_t)pack2(rbf(s) * 0.08838834764831845f, 0.f));
                }
                if (pacer && it >= 2) pace(it * 8 + warp, GAIN_KV);
                __syncwarp();
            }
        }
        __syncwarp();
        if (warp == 7) TSL(6);
        const uint32_t pa = pw + (lane >> 4) * P_PITCH + (lane & 15) * 32;
        const uint32_t sa = sm + OFF_SM + (lane >> 4) * 64;
        const uint4 v0 = lds128(pa), v1 = lds128(pa + 16);
        const uint32_t sv[8] = {v0.x, v0.y, v0.z, v0.w, v1.x, v1.y, v1.z, v1.w};
        float e[16];
        float m = -INFINITY;
#pragma unroll
        for (int i = 0; i < 8; i++) {
            e[2 * i] = blo(sv[i]);
            e[2 * i + 1] = bhi(sv[i]);
            m = fmaxf(m, fmaxf(e[2 * i], e[2 * i + 1]));
        }
#pragma unroll
        for (int o = 8; o; o >>= 1) m = fmaxf(m, __shfl_xor_sync(0xffffffffu, m, o));
        float l = 0.f;
#pragma unroll
        for (int i = 0; i < 16; i++) {
            e[i] = ex2((e[i] - m) * LOG2E);
            l += e[i];
        }
#pragma unroll
        for (int o = 8; o; o >>= 1) l += __shfl_xor_sync(0xffffffffu, l, o);
        if ((lane & 15) == 0) sts64(sa + warp * 8, __float_as_uint(m), __float_as_uint(l));
        bar_sync(2, NCW * 32);
        const float2 v = lds64f(sa + (lane & 7) * 8);
        float M = v.x;
#pragma unroll
        for (int o = 4; o; o >>= 1) M = fmaxf(M, __shfl_xor_sync(0xffffffffu, M, o));
        float L = v.y * ex2((v.x - M) * LOG2E);
#pragma unroll
        for (int o = 4; o; o >>= 1) L += __shfl_xor_sync(0xffffffffu, L, o);
        const float sc = ex2((m - M) * LOG2E) * rcp(L);
        sts128(pa, pack2(e[0] * sc, e[1] * sc), pack2(e[2] * sc, e[3] * sc), pack2(e[4] * sc, e[5] * sc), pack2(e[6] * sc, e[7] * sc));
        sts128(pa + 16, pack2(e[8] * sc, e[9] * sc), pack2(e[10] * sc, e[11] * sc), pack2(e[12] * sc, e[13] * sc), pack2(e[14] * sc, e[15] * sc));
        __syncwarp();
    } else {
        bar_sync(2, NCW * 32);
    }

    const bool reducer = cta < 72 && warp < 4;
    const int rbat = 2 * t4 + (g & 1);
    uint32_t sh[8] = {}, op[8] = {}, rx = 0, rg[2] = {};
    {
        const uint32_t* const src_m = gs + G_M + (72 + warp * 8) * 32 + lane;
        fetch<8, 1>(src_m + 72 * 32, 32, op);
        if (reducer) {
            rx = __ldg(reinterpret_cast<const uint32_t*>(P.x) + rbat * (DM / 2) + 4 * cta + warp);
            get<2, 1>(gs + G_M + cta * 32 + rbat * 4 + warp, 216 * 32, rg);
        }
        get<8, 1>(src_m, 32, sh);
        get<8, 1>(src_m + 72 * 32, 32, op);
    }
    const int side = lds32(sm + OFF_WIN + 8), set = (epoch & 1) * G_SET, rr = (lane >> 4) * 8 + (lane & 7);
    const uint32_t dst_o = pin(4 * (set + dual(D_O + cta * 128) + (tid & 0x70) + (tid & 3) * 4 + ((tid >> 2) & 3)));
    const uint32_t src_o = pin(4 * (set + near(D_O + grp * 1024, side) + g * 128 + warp * 16 + t4 * 4));
    const uint32_t dst_p = pin(4 * (dual(d_part(warp < 8 ? 8 * sub + warp : 64 + sub)) + grp * 64 + lane * 2));
    const uint32_t src_p = pin(4 * (near(d_part(cta), side) + (lane >> 3) * 256 + 16 * warp + (lane & 7) * 2));
    const uint32_t dst_x = pin(4 * (set + dual(D_X1 + cta * 32) + (lane >> 3) * 1024 + warp * 8 + (lane & 7)));
    const uint32_t src_x = pin(4 * (set + near(D_X1 + warp * 256, side) + t4 * 8 + (g & 1) * 4 + (g >> 1)));
    const uint32_t dst_a = pin(4 * (set + dual(D_ACT + (grp * 36 + (warp < 4 ? 4 * sub + warp : 32 + sub)) * 32) + lane));
    const uint32_t src_a = pin(4 * (set + near(D_ACT + (grp * 36 + 4 * warp) * 32, side) + lane));
    const uint32_t dst_out = pin(4 * (rbat * (DM / 2) + 4 * cta + warp));
    const uint32_t rowoff = pin((warp * 32 + rr) * 128 + ((((lane >> 3) & 1) ^ (lane & 7)) << 4));
    const uint32_t reds = pin((tid * 8) | (warp * 2304 + lane * 8) << 16);
    const uint32_t ored = pin((warp * 1088 + (t4 & 1) * 576 + ((t4 >> 1) * 8 + g) * 4) | ((tid >> 6) * 64 + tid * 8) << 16);

    if (warp < 8) {
        float acc[8][4] = {};
        uint32_t pp = pw + (lane & 1) * P_PITCH + (lane >> 3) * 16;
#pragma unroll 1
        for (int it = 0; it < 8; it++, pp += 64) {
            const uint32_t ab = tile + (it & 1) * (8 * TILE_BYTES) + ((lane & 7) + (lane >> 4) * 8) * 128 + ((((lane >> 3) & 1) ^ (lane & 7)) << 4);
            uint32_t pb[4];
            ldsm4(pb, pp);
            mbar_wait(fullb + (it & 1) * 64, (it >> 1) & 1);
#pragma unroll
            for (int ks = 0; ks < 2; ks++)
#pragma unroll
                for (int m = 0; m < 8; m++) {
                    uint32_t a[4];
                    ldsm4t(a, (ab ^ ((m & 3) << 5)) + (m >> 2) * 4096 + ks * 2048);
                    mma(acc[m], a[0], a[1], a[2], a[3], pb[2 * ks], pb[2 * ks + 1]);
                }
            __syncwarp();
            if (lane == 0) mbar_arrive(fullb + (it & 1) * 64 + (BAR_EMPTY - BAR_FULL) * 8);
            if (pacer && it * 8 + warp < NT - 4) pace(NT + it * 8 + warp, GAIN_KV);
            __syncwarp();
        }
        if (warp == 7) TSL(7);
        const uint32_t ra = sm + OFF_ORED + (ored & 0xffff);
#pragma unroll
        for (int m = 0; m < 8; m++) sts32(ra + m * 64, __float_as_uint(sel4(acc[m], t4)));
    }
    bar_sync(5, NCW * 32);
    if (warp < 4) {
        float s[2][2] = {};
#pragma unroll
        for (int w = 0; w < 8; w++) {
            const float2 v = lds64f(sm + OFF_ORED + w * 1088 + (ored >> 16));
            s[w & 1][0] += v.x;
            s[w & 1][1] += v.y;
        }
        put1d(at(g0, dst_o), pack2(s[0][0] + s[1][0], s[0][1] + s[1][1]));
        if (warp == 0) TSL(8);
    }

    project<0>(sm, at(g0, src_o), at(g0, dst_p), rowoff, reds, warp, lane);
    if (warp == 0) TSL(9);
    if (reducer) {
        rx = badd2(rx, bmul2(rg[0], reduce16<0>(at(g0, src_p), lane)));
        if (lane < 16) st1(at(g0, dst_x), nz(rx));
        if (warp == 0) TSL(10);
    }

    const uint32_t gbar = bars + (BAR_GU + warp) * 8;
    const int pl = ((lane >> 3) & 1) ^ P.zg;
    const uint32_t ab = sm + OFF_GU + warp * 8192 + pl * 4096 + rr * 64 + ((lane & 6) << 3);
    const uint32_t ax = sm + OFF_GX + warp * 2048 + pl * 1024 + rr * 16;
    uint32_t a[20][4] = {}, h[8] = {};
    auto load_gu = [&]() {
#pragma unroll
        for (int i = 0; i < 20; i++) ldsm4t(a[i], i % 5 < 4 ? (ab ^ ((i % 5) << 4)) + (i / 5) * 1024 : ax + (i / 5) * 256);
    };
    bool gpre = false;
    {
        int it = 0;
        do {
            if (!gpre && __all_sync(0xffffffffu, mbar_test(gbar, 0))) gpre = true, load_gu();
            fetch<8, 1>(at(g0, src_x), 32, h);
        } while (missing(h) & (++it < SPIN_LIMIT));
    }
    if (warp == 0) TSL(11);
    ln_partial(h, sm + OFF_ST + g * 80 + warp * 8, t4 == 0);
    bar_sync(3, 288);
    {
        uint32_t mean2;
        float inv;
        ln_combine(sm + OFF_ST + g * 80, mean2, inv);
#pragma unroll
        for (int i = 0; i < 8; i++) h[i] = modulate2(h[i], mean2, inv, sh[i], op[i]);
    }
    if (warp == 0) TSL(12);
    if (!gpre) {
        mbar_wait(gbar, 0);
        load_gu();
    }
    if (warp == 8) TSL(17);
    {
        float acc[5][4] = {};
#pragma unroll
        for (int i = 0; i < 20; i++) mma(acc[i % 5], a[i][0], a[i][1], a[i][2], a[i][3], h[2 * (i / 5)], h[2 * (i / 5) + 1]);
#pragma unroll
        for (int m = 0; m < 5; m++) sts128f(sm + OFF_RED + m * 4608 + 2 * (reds & 0xffff), acc[m]);
    }
    bar_sync(3, 288);
    if (warp < 5) {
        float c[4] = {};
        sum_frags<9>(c, sm + OFF_RED + 2 * (reds >> 16), 512);
        const uint32_t w = movm(bmul2(silu2(pack2(c[0], c[1])), pack2(c[2], c[3])));
        if (warp < 4 || sub < 4) put1d(at(g0, dst_a), w);
        if (warp == 1) TSL(13);
    }
    if (cta < 72) {
        float r = 0.f;
#pragma unroll
        for (int i = 0; i < 8; i++) {
            const uint32_t wr = lds32(sm + OFF_WR + (warp * 32 + i * 4 + t4) * 4);
            r = fmaf(blo(h[i]), blo(wr), fmaf(bhi(h[i]), bhi(wr), r));
            if (warp * 8 + i == cta) sts32(sm + OFF_HU + lane * 4, h[i]);
        }
        r = quad_sum(r);
        if (t4 == 0) sts32(sm + OFF_RT + g * 48 + warp * 4, __float_as_uint(r));
    }

    project<1>(sm, at(g0, src_a), at(g0, dst_p), rowoff, reds, warp, lane);
    if (warp == 0) TSL(14);
    if (reducer) {
        const uint4 r0 = lds128(sm + OFF_RT + rbat * 48), r1 = lds128(sm + OFF_RT + rbat * 48 + 16);
        float r = __uint_as_float(lds32(sm + OFF_RT + rbat * 48 + 32));
        r += ((__uint_as_float(r0.x) + __uint_as_float(r0.y)) + (__uint_as_float(r0.z) + __uint_as_float(r0.w))) +
             ((__uint_as_float(r1.x) + __uint_as_float(r1.y)) + (__uint_as_float(r1.z) + __uint_as_float(r1.w)));
        r = sigmoid_f(rbf(r));
        const uint32_t rh = lds32(sm + OFF_HU + (rbat * 4 + warp) * 4);
        const uint32_t y = badd2(rh, bmul2(reduce16<1>(at(g0, src_p), lane), pack2(r, r)));
        if (lane < 8) *at(reinterpret_cast<uint32_t*>(P.out), dst_out) = badd2(rx, bmul2(rg[1], y));
        if (cta == 0 && tid == 0) g0[G_EPOCH] = epoch + 1;
        if (warp == 0) TSL(15);
    }
}

typedef CUresult (*EncodeFn)(CUtensorMap*, CUtensorMapDataType, cuuint32_t, void*, const cuuint64_t*, const cuuint64_t*,
                             const cuuint32_t*, const cuuint32_t*, CUtensorMapInterleave, CUtensorMapSwizzle,
                             CUtensorMapL2promotion, CUtensorMapFloatOOBfill);

void make_map(EncodeFn enc, CUtensorMap* m, void* p, int cols, int rows, int pitch, int bc, int br, int bp, int planes, size_t pstride,
              CUtensorMapSwizzle sw, int promo) {
    cuuint64_t dims[3] = {(cuuint64_t)cols, (cuuint64_t)rows, (cuuint64_t)planes};
    cuuint64_t strides[2] = {(cuuint64_t)pitch * 2, (cuuint64_t)pstride};
    cuuint32_t box[3] = {(cuuint32_t)bc, (cuuint32_t)br, (cuuint32_t)bp};
    cuuint32_t es[3] = {1, 1, 1};
    enc(m, CU_TENSOR_MAP_DATA_TYPE_BFLOAT16, 3, p, dims, strides, box, es, CU_TENSOR_MAP_INTERLEAVE_NONE, sw,
        (CUtensorMapL2promotion)promo, CU_TENSOR_MAP_FLOAT_OOB_FILL_NONE);
}

}

extern "C" void kernel_launch(void* const* d_in, const int* in_sizes, int n_in, void* d_out, int out_size) {
    static EncodeFn enc = nullptr;
    static uint32_t* scratch = nullptr;
    if (!enc) {
        void* fn = nullptr;
        cudaDriverEntryPointQueryResult st;
        cudaGetDriverEntryPoint("cuTensorMapEncodeTiled", &fn, cudaEnableDefault, &st);
        enc = (EncodeFn)fn;
        cudaGetSymbolAddress(&fn, g_scratch);
        scratch = (uint32_t*)(((uintptr_t)fn + 8 * G_SET - 1) & ~(uintptr_t)(8 * G_SET - 1));
        cudaFuncSetAttribute(fused_kernel, cudaFuncAttributeMaxDynamicSharedMemorySize, SMEM_BYTES);
    }
    Params P;
    const CUtensorMapSwizzle none = CU_TENSOR_MAP_SWIZZLE_NONE;
    make_map(enc, &P.m[M_K], d_in[1], 64, NB * HKV * SK, DH, 64, 32, 2, 2, 128, CU_TENSOR_MAP_SWIZZLE_128B, PROMO_KV);
    make_map(enc, &P.m[M_V], d_in[2], 64, NB * HKV * SK, DH, 64, 32, 2, 2, 128, CU_TENSOR_MAP_SWIZZLE_128B, PROMO_KV);
    make_map(enc, &P.m[M_WQ], d_in[3], HQ * DH, DM, HQ * DH, 32, 192, 1, 1, 16, CU_TENSOR_MAP_SWIZZLE_64B, PROMO_W);
    make_map(enc, &P.m[M_WM], d_in[11], 6 * DM, DM, 6 * DM, 32, 192, 1, 1, 16, CU_TENSOR_MAP_SWIZZLE_64B, PROMO_W);
    make_map(enc, &P.m[M_WA], d_in[11], DM, DM, 6 * DM, 16, 192, 2, 2, DM * 2, CU_TENSOR_MAP_SWIZZLE_32B, PROMO_W);
    char *wg = (char*)d_in[7], *wu = (char*)d_in[8], *wo = (char*)d_in[4], *wd = (char*)d_in[9];
    P.zg = wg > wu;
    P.zo = wo > wd;
    const size_t sg = P.zg ? wg - wu : wu - wg, so = P.zo ? wo - wd : wd - wo;
    make_map(enc, &P.m[M_GU], P.zg ? wu : wg, FF, DM, FF, 32, 64, 2, 2, sg, CU_TENSOR_MAP_SWIZZLE_64B, PROMO_GU);
    make_map(enc, &P.m[M_GX], P.zg ? wu : wg, FF, DM, FF, 8, 64, 2, 2, sg, none, PROMO_GX);
    make_map(enc, &P.m[M_OD], P.zo ? wd : wo, DM, FF, DM, 64, 64, 1, 2, so, CU_TENSOR_MAP_SWIZZLE_128B, PROMO_W);
    make_map(enc, &P.m[M_OX], P.zo ? wd : wo, DM, FF, DM, 8, 64, 1, 2, so, none, PROMO_OX);
    P.x = (const __nv_bfloat16*)d_in[0];
    P.wr = (const __nv_bfloat16*)d_in[6];
    P.c = (const __nv_bfloat16*)d_in[10];
    P.out = (__nv_bfloat16*)d_out;
    P.scratch = scratch;
    fused_kernel<<<NCTA, NTHREADS, SMEM_BYTES>>>(P);
}
```

```cpp
#include <cuda_runtime.h>
#include <cuda_bf16.h>
#include <cuda.h>
#include <stdint.h>

typedef unsigned long long u64;

#define W_KV 20
#define W_WO 19
#define W_GU 19
#define W_GU2 W_GU
#define W_WD 13
#define W_MIN -8
#define W_MAX 8
#define GAIN_KV 2
#define GAIN_TAIL 3
#define NK0 2
#define T_CLEAR 116
#define B_CAP 8
#define WD_ROT 0
#define DX_EARLY 0
#define NPING0 4
#define NPING1 16
#define PROMO_W CU_TENSOR_MAP_L2_PROMOTION_L2_128B
#define PROMO_GX 2
#define PROMO_OX 2
#define PROMO_GU 2
#define PROMO_KV CU_TENSOR_MAP_L2_PROMOTION_L2_256B

namespace {

constexpr int NB = 8, DM = 576, HQ = 32, HKV = 16, SK = 8192, WIN = 2048, DH = 128, FF = 4608;
constexpr int NCTA = 128;
constexpr int NCW = 10;
constexpr int NTHREADS = (NCW + 2) * 32;
constexpr int TILE_BYTES = 8192, NSLOT = 16, NT = 64;
constexpr int SPIN_LIMIT = 1 << 22;

constexpr int OFF_RING = 0;
constexpr int OFF_WM = 121856;
constexpr int OFF_WQ = OFF_WM + 36864;
constexpr int OFF_GU = 0;
constexpr int OFF_WD = 73728;
constexpr int OFF_OX = 131072;
constexpr int OFF_DX = OFF_OX + 4096;
constexpr int OFF_GX = OFF_DX + 4608;
constexpr int OFF_WO = OFF_WQ;
constexpr int OFF_P = OFF_WQ + 36864;
constexpr int P_PITCH = 528;
constexpr int OFF_RED = OFF_P + 16 * P_PITCH;
constexpr int OFF_ORED = OFF_RED + 5 * 4608 - 8704;
constexpr int OFF_ST = OFF_RED + 5 * 4608;
constexpr int OFF_SM = OFF_ST + 640;
constexpr int OFF_RT = OFF_SM + 128;
constexpr int OFF_HU = OFF_RT + 384;
constexpr int OFF_QS = OFF_HU + 128;
constexpr int OFF_WR = OFF_QS + 512;
constexpr int OFF_WIN = OFF_WR + 1152;
constexpr int OFF_BAR = OFF_WIN + 16;
constexpr int BAR_FULL = 6, BAR_WO = 22, BAR_GU = 26, BAR_WD = 35, BAR_EMPTY = 40, BAR_SYNC = 56, BAR_WMF = 59, NBAR = 70;
constexpr int SMEM_BYTES = OFF_BAR + NBAR * 8;

constexpr int D_X1 = 0;
constexpr int D_O = 3072;
constexpr int D_ACT = D_O + 512 * 32;
constexpr int D_H = D_ACT + 576 * 32;
constexpr int D_Q = D_H + 3072;
constexpr int G_M = 2 * (D_Q + NB * HQ * 64);
constexpr int G_CNT = G_M + 288 * 32;
constexpr int G_SET = 1 << 18;
__device__ __forceinline__ int d_part(int unit) { return (64 + unit + (unit & 64)) * 1024; }
constexpr int D_PING = 200 * 1024;
constexpr int G_EPOCH = 201 * 2048;
static_assert(G_CNT < 64 * 2048, "scratch layout");
__device__ uint32_t g_scratch[4 * G_SET];
__device__ __forceinline__ int dual(int w) { return w + (w & ~1023); }
__device__ __forceinline__ int near(int w, int side) { return dual(w) + (((__popc(w & 0x16400) ^ side) & 1) << 10); }

#define TI(i)
#define TS(i)
#define TSL(i)

enum { M_K, M_V, M_GU, M_GX, M_OD, M_OX, M_WQ, M_WM, M_WA, NMAP };
struct Params {
    CUtensorMap m[NMAP];
    const __nv_bfloat16 *x, *c, *wr;
    __nv_bfloat16* out;
    uint32_t* scratch;
    int zg, zo;
};

__device__ __forceinline__ void mbar_init(uint32_t bar, int cnt) {
    asm volatile("mbarrier.init.shared::cta.b64 [%0], %1;" ::"r"(bar), "r"(cnt));
}
__device__ __forceinline__ void mbar_expect(uint32_t bar, uint32_t bytes) {
    asm volatile("mbarrier.arrive.expect_tx.shared::cta.b64 _, [%0], %1;" ::"r"(bar), "r"(bytes) : "memory");
}
__device__ __forceinline__ void mbar_arrive(uint32_t bar) {
    asm volatile("mbarrier.arrive.shared::cta.b64 _, [%0];" ::"r"(bar) : "memory");
}
__device__ __forceinline__ void mbar_wait(uint32_t bar, uint32_t parity) {
    asm volatile("{\n.reg .pred p;\n.reg .u32 c;\n"
                 "mbarrier.try_wait.parity.shared::cta.b64 p, [%0], %1;\n@p bra DONE;\nmov.u32 c, %2;\n"
                 "AGAIN:\nmbarrier.try_wait.parity.shared::cta.b64 p, [%0], %1;\nsub.u32 c, c, 1;\n"
                 "setp.eq.or.u32 p, c, 0, p;\n@!p bra AGAIN;\nDONE:\n}"
                 ::"r"(bar), "r"(parity), "n"(SPIN_LIMIT) : "memory");
}
__device__ __forceinline__ bool mbar_test(uint32_t bar, uint32_t parity) {
    uint32_t ok;
    asm volatile("{\n.reg .pred p;\nmbarrier.test_wait.parity.shared::cta.b64 p, [%1], %2;\nselp.u32 %0, 1, 0, p;\n}"
                 : "=r"(ok) : "r"(bar), "r"(parity) : "memory");
    return ok;
}
__device__ __forceinline__ void mbar_wait_lanes(uint32_t bar) {
    mbar_wait(bar, 0);
    __syncwarp();
}
__device__ __forceinline__ void tma3d_hint(uint32_t dst, const CUtensorMap* m, int x, int y, int z, uint32_t bar, u64 pol) {
    asm volatile("cp.async.bulk.tensor.3d.shared::cluster.global.mbarrier::complete_tx::bytes.L2::cache_hint"
                 " [%0], [%1, {%2, %3, %4}], [%5], %6;"
                 ::"r"(dst), "l"(m), "r"(x), "r"(y), "r"(z), "r"(bar), "l"(pol) : "memory");
}
__device__ __forceinline__ void tma3d(uint32_t dst, const CUtensorMap* m, int x, int y, int z, uint32_t bar) {
    asm volatile("cp.async.bulk.tensor.3d.shared::cluster.global.mbarrier::complete_tx::bytes [%0], [%1, {%2, %3, %4}], [%5];"
                 ::"r"(dst), "l"(m), "r"(x), "r"(y), "r"(z), "r"(bar) : "memory");
}
__device__ __forceinline__ void bar_sync(int id, int n) { asm volatile("bar.sync %0, %1;" ::"r"(id), "r"(n) : "memory"); }
__device__ __forceinline__ void bar_arrive(int id, int n) { asm volatile("bar.arrive %0, %1;" ::"r"(id), "r"(n) : "memory"); }
__device__ __forceinline__ void ldsm4(uint32_t (&r)[4], uint32_t a) {
    asm volatile("ldmatrix.sync.aligned.m8n8.x4.shared.b16 {%0,%1,%2,%3}, [%4];"
                 : "=r"(r[0]), "=r"(r[1]), "=r"(r[2]), "=r"(r[3]) : "r"(a) : "memory");
}
__device__ __forceinline__ void ldsm4t(uint32_t (&r)[4], uint32_t a) {
    asm volatile("ldmatrix.sync.aligned.m8n8.x4.trans.shared.b16 {%0,%1,%2,%3}, [%4];"
                 : "=r"(r[0]), "=r"(r[1]), "=r"(r[2]), "=r"(r[3]) : "r"(a) : "memory");
}
__device__ __forceinline__ void mma(float (&c)[4], uint32_t a0, uint32_t a1, uint32_t a2, uint32_t a3, uint32_t b0, uint32_t b1) {
    asm volatile("mma.sync.aligned.m16n8k16.row.col.f32.bf16.bf16.f32 {%0,%1,%2,%3}, {%4,%5,%6,%7}, {%8,%9}, {%0,%1,%2,%3};"
                 : "+f"(c[0]), "+f"(c[1]), "+f"(c[2]), "+f"(c[3])
                 : "r"(a0), "r"(a1), "r"(a2), "r"(a3), "r"(b0), "r"(b1));
}
__device__ __forceinline__ uint32_t movm(uint32_t a) {
    uint32_t d;
    asm volatile("movmatrix.sync.aligned.m8n8.trans.b16 %0, %1;" : "=r"(d) : "r"(a));
    return d;
}
__device__ __forceinline__ uint32_t lds32(uint32_t a) { uint32_t v; asm volatile("ld.shared.b32 %0, [%1];" : "=r"(v) : "r"(a) : "memory"); return v; }
__device__ __forceinline__ float2 lds64f(uint32_t a) { float2 v; asm volatile("ld.shared.v2.f32 {%0,%1}, [%2];" : "=f"(v.x), "=f"(v.y) : "r"(a) : "memory"); return v; }
__device__ __forceinline__ uint4 lds128(uint32_t a) { uint4 v; asm volatile("ld.shared.v4.b32 {%0,%1,%2,%3}, [%4];" : "=r"(v.x), "=r"(v.y), "=r"(v.z), "=r"(v.w) : "r"(a) : "memory"); return v; }
__device__ __forceinline__ void sts32(uint32_t a, uint32_t v) { asm volatile("st.shared.b32 [%0], %1;" ::"r"(a), "r"(v) : "memory"); }
__device__ __forceinline__ void sts16(uint32_t a, uint16_t v) { asm volatile("st.shared.b16 [%0], %1;" ::"r"(a), "h"(v) : "memory"); }
__device__ __forceinline__ void sts64(uint32_t a, uint32_t x, uint32_t y) { asm volatile("st.shared.v2.b32 [%0], {%1,%2};" ::"r"(a), "r"(x), "r"(y) : "memory"); }
__device__ __forceinline__ void sts128(uint32_t a, uint32_t x, uint32_t y, uint32_t z, uint32_t w) {
    asm volatile("st.shared.v4.b32 [%0], {%1,%2,%3,%4};" ::"r"(a), "r"(x), "r"(y), "r"(z), "r"(w) : "memory");
}
__device__ __forceinline__ void sts128f(uint32_t a, const float (&c)[4]) {
    sts128(a, __float_as_uint(c[0]), __float_as_uint(c[1]), __float_as_uint(c[2]), __float_as_uint(c[3]));
}

__device__ __forceinline__ float sel4(const float (&c)[4], int t) { return (t & 2) ? ((t & 1) ? c[3] : c[2]) : ((t & 1) ? c[1] : c[0]); }

template <int LUT>
__device__ __forceinline__ uint32_t lop3(uint32_t a, uint32_t b, uint32_t c) {
    uint32_t d;
    asm("lop3.b32 %0, %1, %2, %3, %4;" : "=r"(d) : "r"(a), "r"(b), "r"(c), "n"(LUT));
    return d;
}
__device__ __forceinline__ uint32_t pin(uint32_t v) { return __shfl_xor_sync(0xffffffffu, v, 0); }
template <typename T>
__device__ __forceinline__ T* at(T* base, uint32_t bytes) { return reinterpret_cast<T*>(reinterpret_cast<char*>(base) + bytes); }

__device__ __forceinline__ uint32_t clock32(uint32_t dep) {
    uint32_t t;
    asm volatile("{\n.reg .pred p;\nsetp.eq.u32 p, %1, 0x9e3779b9;\n@p nanosleep.u32 1;\nmov.u32 %0, %clock;\n}" : "=r"(t) : "r"(dep) : "memory");
    return t;
}

__device__ __forceinline__ uint32_t nz(uint32_t v) { return v ? v : 0x80000000u; }
__device__ __forceinline__ void st1(uint32_t* p, uint32_t a) { asm volatile("st.relaxed.gpu.global.b32 [%0], %1;" ::"l"(p), "r"(a) : "memory"); }
__device__ __forceinline__ void st2(uint32_t* p, uint32_t a, uint32_t b) {
    asm volatile("st.relaxed.gpu.global.v2.b32 [%0], {%1,%2};" ::"l"(p), "r"(a), "r"(b) : "memory");
}
__device__ __forceinline__ void zero4(uint32_t* p) { asm volatile("st.relaxed.gpu.global.v4.b32 [%0], {%1,%1,%1,%1};" ::"l"(p), "r"(0) : "memory"); }
__device__ __forceinline__ void put1d(uint32_t* p, uint32_t a) { a = nz(a), st1(p, a), st1(p + 1024, a); }
__device__ __forceinline__ void put2d(uint32_t* p, uint32_t a, uint32_t b) { a = nz(a), b = nz(b), st2(p, a, b), st2(p + 1024, a, b); }
__device__ __forceinline__ uint32_t ld1(const uint32_t* p) {
    uint32_t v;
    asm volatile("ld.relaxed.gpu.global.b32 %0, [%1];" : "=r"(v) : "l"(p) : "memory");
    return v;
}
template <int N, int V>
__device__ __forceinline__ void fetch(const uint32_t* p, int stride, uint32_t (&a)[N * V]) {
#pragma unroll
    for (int i = 0; i < N; i++) {
        if (V == 1)
            asm volatile("{\n.reg .pred p;\nsetp.eq.u32 p, %0, 0;\n@p ld.relaxed.gpu.global.b32 %0, [%1];\n}"
                         : "+r"(a[i]) : "l"(p + i * stride) : "memory");
        if (V == 4)
            asm volatile("{\n.reg .pred p;\nsetp.eq.u32 p, %4, 0;\n@p ld.relaxed.gpu.global.v4.b32 {%0,%1,%2,%3}, [%5];\n}"
                         : "+r"(a[V * i]), "+r"(a[V * i + V / 4]), "+r"(a[V * i + V / 2]), "+r"(a[V * i + V - 1])
                         : "r"(min(min(a[V * i], a[V * i + V / 4]), min(a[V * i + V / 2], a[V * i + V - 1]))), "l"(p + i * stride) : "memory");
    }
}
template <int N>
__device__ __forceinline__ bool missing(const uint32_t (&a)[N]) {
    uint32_t lo = a[0];
#pragma unroll
    for (int i = 1; i < N; i++) lo = min(lo, a[i]);
    return __any_sync(0xffffffffu, lo == 0);
}
template <int N, int V>
__device__ __forceinline__ void get(const uint32_t* p, int stride, uint32_t (&a)[N * V]) {
    int it = 0;
    do fetch<N, V>(p, stride, a);
    while (missing(a) & (++it < SPIN_LIMIT));
}
__device__ __forceinline__ void cp16(uint32_t dst, const void* src) {
    asm volatile("cp.async.cg.shared.global [%0], [%1], 16;" ::"r"(dst), "l"(src) : "memory");
}

__device__ __forceinline__ uint32_t pack2(float lo, float hi) {
    uint32_t r;
    asm("cvt.rn.bf16x2.f32 %0, %1, %2;" : "=r"(r) : "f"(hi), "f"(lo));
    return r;
}
__device__ __forceinline__ float rbf(float x) { return __uint_as_float(pack2(0.f, x)); }
__device__ __forceinline__ float blo(uint32_t v) { return __uint_as_float(v << 16); }
__device__ __forceinline__ float bhi(uint32_t v) { return __uint_as_float(v & 0xffff0000u); }
__device__ __forceinline__ uint32_t badd2(uint32_t a, uint32_t b) { uint32_t r; asm("add.rn.bf16x2 %0, %1, %2;" : "=r"(r) : "r"(a), "r"(b)); return r; }
__device__ __forceinline__ uint32_t bsub2(uint32_t a, uint32_t b) { uint32_t r; asm("sub.rn.bf16x2 %0, %1, %2;" : "=r"(r) : "r"(a), "r"(b)); return r; }
__device__ __forceinline__ uint32_t bmul2(uint32_t a, uint32_t b) { uint32_t r; asm("mul.rn.bf16x2 %0, %1, %2;" : "=r"(r) : "r"(a), "r"(b)); return r; }
__device__ __forceinline__ float ex2(float x) { float r; asm("ex2.approx.ftz.f32 %0, %1;" : "=f"(r) : "f"(x)); return r; }
__device__ __forceinline__ float rcp(float x) { float r; asm("rcp.approx.ftz.f32 %0, %1;" : "=f"(r) : "f"(x)); return r; }
__device__ __forceinline__ float sqrt_f(float x) { float r; asm("sqrt.approx.ftz.f32 %0, %1;" : "=f"(r) : "f"(x)); return r; }
constexpr float LOG2E = 1.4426950408889634f;
constexpr uint32_t ONE2 = 0x3f803f80u;
__device__ __forceinline__ float sigmoid_f(float x) { return rcp(1.0f + ex2(-LOG2E * x)); }
__device__ __forceinline__ uint32_t silu2(uint32_t v) {
    const float a = blo(v), b = bhi(v);
    return pack2(a * sigmoid_f(a), b * sigmoid_f(b));
}
__device__ __forceinline__ float quad_sum(float v) {
    v += __shfl_xor_sync(0xffffffffu, v, 1);
    return v + __shfl_xor_sync(0xffffffffu, v, 2);
}
__device__ __forceinline__ void ln_partial(const uint32_t (&v)[8], uint32_t dst, bool writer) {
    float s0 = 0.f, s1 = 0.f;
#pragma unroll
    for (int i = 0; i < 8; i++) {
        s0 += blo(v[i]);
        s1 += bhi(v[i]);
    }
    const float mean = quad_sum(s0 + s1) * (1.0f / 64);
    s0 = s1 = 0.f;
#pragma unroll
    for (int i = 0; i < 8; i++) {
        const float a = blo(v[i]) - mean, b = bhi(v[i]) - mean;
        s0 = fmaf(a, a, s0);
        s1 = fmaf(b, b, s1);
    }
    s0 = quad_sum(s0 + s1);
    if (writer) sts64(dst, __float_as_uint(mean), __float_as_uint(s0));
}
__device__ __forceinline__ void ln_combine(uint32_t src, uint32_t& mean2, float& inv) {
    float m[10], q0 = 0.f, q1 = 0.f, s = 0.f;
#pragma unroll
    for (int i = 0; i < 5; i++) {
        const uint4 v = lds128(src + i * 16);
        m[2 * i] = __uint_as_float(v.x);
        m[2 * i + 1] = __uint_as_float(v.z);
        q0 += __uint_as_float(v.y);
        if (i < 4) q1 += __uint_as_float(v.w);
    }
    const float mean = (((m[0] + m[1]) + (m[2] + m[3])) + ((m[4] + m[5]) + (m[6] + m[7])) + m[8]) * (1.0f / 9);
#pragma unroll
    for (int i = 0; i < 9; i++) s = fmaf(m[i] - mean, m[i] - mean, s);
    const float var = fmaf(s, 64.f, q0 + q1) * (1.0f / DM);
    mean2 = pack2(mean, mean);
    inv = rcp(rbf(sqrt_f(rbf(rbf(var) + 1e-5f))));
}
__device__ __forceinline__ uint32_t modulate2(uint32_t x, uint32_t mean2, float inv, uint32_t shift, uint32_t onep) {
    const uint32_t d = bsub2(x, mean2);
    return badd2(bmul2(pack2(blo(d) * inv, bhi(d) * inv), onep), shift);
}
template <int N>
__device__ __forceinline__ void sum_frags(float (&c)[4], uint32_t addr, int stride) {
#pragma unroll
    for (int w = 0; w < N; w++) {
        const uint4 v = lds128(addr + w * stride);
        c[0] += __uint_as_float(v.x); c[1] += __uint_as_float(v.y);
        c[2] += __uint_as_float(v.z); c[3] += __uint_as_float(v.w);
    }
}

template <int ST>
__device__ __forceinline__ void project(uint32_t sm, const uint32_t* src, uint32_t* dst, uint32_t rowoff, uint32_t reds, int warp, int lane) {
    constexpr int NW = ST ? 9 : 8;
    const uint32_t red = sm + (ST ? OFF_WO : OFF_P);
    if (warp < NW) {
        const uint32_t wbar = sm + OFF_BAR + (ST ? BAR_WD + (warp < 8 ? ((warp >> 1) - WD_ROT) & 3 : 4) : BAR_WO + (warp >> 1)) * 8;
        const uint32_t ab = sm + (ST ? OFF_WD : OFF_WO) + rowoff;
        const uint32_t ax = sm + (ST ? OFF_DX : OFF_OX) + ((rowoff >> 7) << 4);
        uint32_t a[10][4] = {}, b[4] = {};
        bool have_w = false, need_b = true;
        int it = 0;
        do {
            if (!need_b) mbar_wait(wbar, 0);
            if (!need_b || (!have_w && __all_sync(0xffffffffu, mbar_test(wbar, 0)))) {
                have_w = true;
#pragma unroll
                for (int i = 0; i < 10; i++) ldsm4t(a[i], i % 5 < 4 ? (ab ^ ((i % 5) << 5)) + (i / 5) * 2048 : ax + (i / 5) * 256);
                if (!need_b) break;
            }
            if (ST) fetch<4, 1>(src, 32, b);
            else fetch<1, 4>(src, 0, b);
            need_b = missing(b) & (++it < SPIN_LIMIT);
        } while (need_b | !have_w);
        if (warp == 0) TSL(ST ? 24 : 21);
        float acc[5][4] = {};
#pragma unroll
        for (int i = 0; i < 10; i++) mma(acc[i % 5], a[i][0], a[i][1], a[i][2], a[i][3], b[2 * (i / 5)], b[2 * (i / 5) + 1]);
#pragma unroll
        for (int u = 0; u < 9; u++)
            sts64(red + u * 2304 + (reds & 0xffff), __float_as_uint(acc[u >> 1][2 * (u & 1)]), __float_as_uint(acc[u >> 1][2 * (u & 1) + 1]));
    }
    bar_sync(3, 288);
    float s[2][2] = {};
#pragma unroll
    for (int w = 0; w < NW; w++) {
        const float2 v = lds64f(red + (reds >> 16) + w * 256);
        s[w & 1][0] += v.x;
        s[w & 1][1] += v.y;
    }
    const uint32_t p0 = (__float_as_uint(s[0][0] + s[1][0]) | 1) ^ ST, p1 = (__float_as_uint(s[0][1] + s[1][1]) | 1) ^ ST;
    st2(dst, p0, p1), st2(dst + 1024, p0, p1);
}

template <int ST>
__device__ __forceinline__ uint32_t reduce16(const uint32_t* src, int lane) {
    uint32_t a[8] = {}, bad[4] = {1, 1, 1, 1};
    int it = 0;
    do {
#pragma unroll
        for (int i = 0; i < 4; i++)
            asm volatile("{\n.reg .pred p;\nsetp.ne.u32 p, %2, 0;\n@p ld.relaxed.gpu.global.v2.b32 {%0,%1}, [%3];\n}"
                         : "+r"(a[2 * i]), "+r"(a[2 * i + 1]) : "r"(bad[i]), "l"(src + i * 64) : "memory");
#pragma unroll
        for (int i = 0; i < 4; i++) bad[i] = lop3<ST ? 0xa8 : 0x2a>(a[2 * i], a[2 * i + 1], 1);
    } while (__any_sync(0xffffffffu, (lop3<0xfe>(bad[0], bad[1], bad[2]) | bad[3]) != 0) & (++it < SPIN_LIMIT));
    float s0 = (__uint_as_float(a[0]) + __uint_as_float(a[2])) + (__uint_as_float(a[4]) + __uint_as_float(a[6]));
    float s1 = (__uint_as_float(a[1]) + __uint_as_float(a[3])) + (__uint_as_float(a[5]) + __uint_as_float(a[7]));
#pragma unroll
    for (int o = 8; o < 32; o <<= 1) {
        s0 += __shfl_xor_sync(0xffffffffu, s0, o);
        s1 += __shfl_xor_sync(0xffffffffu, s1, o);
    }
    const uint32_t y = pack2(s0, s1);
    return __byte_perm(y, __shfl_xor_sync(0xffffffffu, y, 4), (lane & 4) ? 0x3276 : 0x5410);
}

__global__ void __launch_bounds__(NTHREADS, 1) fused_kernel(const __grid_constant__ Params P) {
    extern __shared__ __align__(1024) char smem_raw[];
    constexpr uint32_t sm = 1024;
    const int tid = threadIdx.x, lane = tid & 31;
    const int cta = blockIdx.x, grp = cta >> 3, sub = cta & 7;
    const uint32_t bars = sm + OFF_BAR;
    const int row0 = (sub * HKV + grp) * SK + (SK - WIN);
    u64 pol;
    asm volatile("createpolicy.fractional.L2::evict_first.b64 %0, 1.0;" : "=l"(pol));
    if (tid == NCW * 32) {
        TS(0);
        const int n0 = cta < 108 ? 0 : 3;
#pragma unroll
        for (int i = 0; i < 6; i++) mbar_init(bars + i * 8, 1);
        asm volatile("fence.mbarrier_init.release.cluster;" ::: "memory");
#pragma unroll
        for (int i = 0; i < 3; i++) {
            mbar_expect(bars + (n0 + i) * 8, 12288);
            tma3d(sm + OFF_WM + (n0 + i) * 12288, &P.m[cta < 36 ? M_WA : cta < 108 ? M_WM : M_WQ], cta < 36 ? 16 * cta : 32 * cta,
                  i * 192, 0, bars + (n0 + i) * 8);
            TI(n0 + i);
        }
        TS(26);
    }
    if (tid == NCW * 32 + 32) {
#pragma unroll
        for (int i = 0; i < 4; i++) mbar_init(bars + (BAR_FULL + i) * 8, 1);
        asm volatile("fence.mbarrier_init.release.cluster;" ::: "memory");
#pragma unroll
        for (int t = 0; t < NK0; t++) {
            mbar_expect(bars + (BAR_FULL + t) * 8, TILE_BYTES);
            tma3d_hint(sm + OFF_RING + t * TILE_BYTES, &P.m[M_K], 0, row0 + t * 32, 0, bars + (BAR_FULL + t) * 8, pol);
            TI(6 + t);
        }
    }
    if (tid < 288 && cta < 108) {
#pragma unroll
        for (int i = 0; i < 2; i++) {
            const int row = (lane >> 3) + 4 * i, so = row * DM + (tid >> 5) * 64 + (lane & 7) * 8;
            const uint32_t d = sm + OFF_RED + (tid >> 5) * 2048 + row * 128 + (((lane & 7) ^ row) << 4);
            cp16(d, P.c + so);
            if (cta < 36) cp16(d + 1024, P.x + so);
        }
    }
    uint32_t* const g0 = P.scratch;
    const uint32_t epoch = ld1(g0 + G_EPOCH);
    const int warp = __shfl_sync(0xffffffffu, tid >> 5, 0);
    auto pace = [&](int t, int gain) {
        const int d = (int)atomicAdd(g0 + (epoch & 1) * G_SET + G_CNT, 1u) - 32 * (t - 16) - 16;
        sts32(sm + OFF_WIN, min(max((d * gain + 32) >> 6, W_MIN), W_MAX));
    };

    if (warp >= NCW) {
        const int pw = warp - NCW;
        bar_arrive(1, (NCW + 1) * 32);
        if (pw && lane < M_WQ) asm volatile("prefetch.tensormap [%0];" ::"l"(&P.m[M_WQ - lane]) : "memory");
        if (tid == NCW * 32) sts32(sm + OFF_WIN, 0);
        __syncwarp();
        bar_sync(15, NTHREADS);
        if (lane == 0) {
            if (pw == 0 && cta < 108) {
#pragma unroll 1
                for (int n = 3; n < 6; n++) {
                    mbar_expect(bars + n * 8, 12288);
                    mbar_wait(bars + (n - 3) * 8, 0);
                    tma3d(sm + OFF_WM + n * 12288, &P.m[M_WQ], 32 * cta, (n - 3) * 192, 0, bars + n * 8);
                    TI(n);
                }
            }
#pragma unroll 1
            for (int t = (2 - pw) * NK0; t < 2 * NK0 + 3 * (1 - pw); t++) {
                mbar_expect(bars + (BAR_FULL + t) * 8, TILE_BYTES);
                mbar_wait(bars + (t + (pw ? BAR_FULL - NK0 : 3 - 2 * NK0)) * 8, 0);
                tma3d_hint(sm + OFF_RING + t * TILE_BYTES, &P.m[M_K], 0, row0 + t * 32, 0, bars + (BAR_FULL + t) * 8, pol);
                TI(6 + t);
            }
            if (pw == 0) {
#pragma unroll 1
                for (int t = 2 * NK0 + 3; t < 2 * NT; t++) {
                    if (t == 14 && cta < 108) mbar_wait(bars + BAR_WMF * 8, 0);
                    if (t == 15) TS(30);
                    const int m = t - ((W_KV + (int)lds32(sm + OFF_WIN) + ((0xd8 >> (2 * t & 6)) & 3)) >> 2);
                    const uint32_t fb = bars + (BAR_FULL + (t & 15)) * 8;
                    mbar_wait(fb + (BAR_EMPTY - BAR_FULL) * 8, (~t >> 4) & 1);
                    mbar_expect(fb, TILE_BYTES);
                    mbar_wait(bars + (BAR_FULL + (m & 15)) * 8, (m >> 4) & 1);
                    tma3d_hint(sm + OFF_RING + (t & 15) * TILE_BYTES, &P.m[t >> 6], 0, row0 + (t & (NT - 1)) * 32, 0, fb, pol);
                    TI(6 + t);
                    if (t == T_CLEAR) mbar_arrive(bars + (BAR_SYNC + 1) * 8);
                }
                mbar_arrive(bars + (BAR_SYNC + 2) * 8);
                mbar_wait(bars + BAR_SYNC * 8, 0);
                auto window = [&](int b, int w) {
                    b -= max((w + (int)lds32(sm + OFF_WIN) + ((0xd8 >> (2 * b & 6)) & 3)) >> 2, 1);
                    b = min(b, BAR_GU + B_CAP);
                    mbar_wait(bars + b * 8, b < BAR_WO);
                };
#pragma unroll 1
                for (int i = 0; i < 4; i++) {
                    window(BAR_WO + i, W_WO);
                    tma3d(sm + OFF_WO + i * 8192, &P.m[M_OD], 64 * sub, grp * 256 + i * 64, P.zo, bars + (BAR_WO + i) * 8);
                    tma3d(sm + OFF_OX + i * 1024, &P.m[M_OX], 512 + 8 * sub, grp * 256 + i * 64, P.zo, bars + (BAR_WO + i) * 8);
                    TI(134 + i);
                }
                TS(28);
#pragma unroll 1
                for (int i = 0; i < 9; i++) {
                    mbar_wait(bars + (BAR_EMPTY + i) * 8, 1);
                    window(BAR_GU + i, sub < 4 ? W_GU : W_GU2);
                    tma3d(sm + OFF_GU + i * 8192, &P.m[M_GU], grp * 288 + 32 * sub, i * 64, 0, bars + (BAR_GU + i) * 8);
                    if (sub < 4) tma3d(sm + OFF_GX + i * 2048, &P.m[M_GX], grp * 288 + 256 + 8 * sub, i * 64, 0, bars + (BAR_GU + i) * 8);
                    if (DX_EARLY && i < 5) tma3d(sm + OFF_DX + min(i * 64, 224) * 16, &P.m[M_OX], 512 + 8 * sub, grp * 288 + min(i * 64, 224), P.zo ^ 1, bars + (BAR_GU + i) * 8);
                    TI(138 + i);
                }
                TS(29);
#pragma unroll 1
                for (int i = 0; i < 5; i++) {
                    const int blk = i < 4 ? (i + WD_ROT) & 3 : 4, r = min(blk * 64, 224);
                    mbar_wait(bars + (BAR_EMPTY + 9 + blk) * 8, 1);
                    window(BAR_WD + i, W_WD);
                    tma3d(sm + OFF_WD + r * 128, &P.m[M_OD], 64 * sub, grp * 288 + r, P.zo ^ 1, bars + (BAR_WD + i) * 8);
                    if (!DX_EARLY) tma3d(sm + OFF_DX + r * 16, &P.m[M_OX], 512 + 8 * sub, grp * 288 + r, P.zo ^ 1, bars + (BAR_WD + i) * 8);
                    TI(147 + i);
                }
            } else {
#pragma unroll 1
                for (int i = BAR_WO; i < BAR_WD + 5; i++) mbar_expect(bars + i * 8, i < BAR_GU ? 9216 : i >= BAR_WD ? 9216 - 1024 * DX_EARLY : (sub < 4 ? 10240 : 8192) + (i < BAR_GU + 5 ? 1024 * DX_EARLY : 0));
                mbar_arrive(bars + BAR_SYNC * 8);
                mbar_wait(bars + (BAR_SYNC + 2) * 8, 0);
#pragma unroll 1
                for (int t = 124 + (cta & 3); t < 144; t += 4) {
                    mbar_wait(bars + (BAR_FULL - 112 + t) * 8, t < 128);
                    pace(t, GAIN_TAIL);
                }
            }
        }
        return;
    }

    if (lane == 0) {
#pragma unroll
        for (int i = 0; i < 6; i++) mbar_init(bars + (10 + warp * 6 + i) * 8, 1);
        asm volatile("fence.mbarrier_init.release.cluster;" ::: "memory");
    }
    __syncwarp();
    if (warp < 9) bar_arrive(15, NTHREADS);
    const int g = lane >> 2, t4 = lane & 3;
    uint32_t* const gs = g0 + (epoch & 1) * G_SET;

    if (warp < 9) {
        const int off_h = (cta < 36 ? dual(D_H + 2 * cta * 32) : G_M + 4 * (cta - 36) * 32) + tid;
        const int off_h2 = off_h + (cta < 36 ? 1024 : 64);
        const int off_q = dual(D_Q + g * (HQ * 64) + cta * 16) + warp * 8 + t4 * 2;
        uint32_t bf[8] = {}, xp = 0, mean2 = 0;
        float inv = 0.f;
        if (cta < 36) xp = __ldg(reinterpret_cast<const uint32_t*>(P.x) + g * (DM / 2) + 8 * cta + 4 * (warp & 1) + t4);
        if (warp < 2) {
            st2(gs + off_q, 0, 0), st2(gs + off_q + 1024, 0, 0);
            if (cta < 36) st1(gs + off_h, 0), st1(gs + off_h2, 0);
        }
        if (cta < 108) {
            asm volatile("cp.async.wait_all;" ::: "memory");
            __syncwarp();
            const uint32_t fa = sm + OFF_RED + warp * 2048 + (lane & 7) * 128 + (((lane >> 3) ^ (lane & 7)) << 4);
            ldsm4(reinterpret_cast<uint32_t(&)[4]>(bf[0]), fa);
            ldsm4(reinterpret_cast<uint32_t(&)[4]>(bf[4]), fa ^ 64);
            if (cta < 36) {
                uint32_t xv[8];
                ldsm4(reinterpret_cast<uint32_t(&)[4]>(xv[0]), fa + 1024);
                ldsm4(reinterpret_cast<uint32_t(&)[4]>(xv[4]), (fa ^ 64) + 1024);
                ln_partial(xv, sm + OFF_ST + g * 80 + warp * 8, t4 == 0);
            }
#pragma unroll
            for (int i = 0; i < 8; i++) bf[i] = silu2(bf[i]);
        }
        if (warp == 0) TSL(18);
        bar_sync(1, (NCW + 1) * 32);
        if (cta < 36 && warp < 2) ln_combine(sm + OFF_ST + g * 80, mean2, inv);
        const int r = warp * 64 + (lane >> 4) * 8 + (lane & 7), hi8 = (lane >> 3) & 1, box = warp / 3;
#pragma unroll 1
        for (int pass = cta < 108 ? 0 : 1; pass < 2; pass++) {
            const bool pa = pass == 0 && cta < 36;
            const uint32_t ab = sm + OFF_WM + pass * 36864 +
                                (pa ? (box + hi8) * 6144 + r * 32 + ((lane & 4) << 2) : r * 64 + (((2 * hi8) ^ ((r >> 1) & 3)) << 4));
            const uint32_t as = pa ? 512 : 1024, red = sm + OFF_RED + pass * 9216;
            mbar_wait(bars + (pass * 3 + box) * 8, 0);
            if (warp == 8) TSL(pass ? 31 : 19);
            uint32_t a[4][2][4];
#pragma unroll
            for (int i = 0; i < 4; i++) {
                ldsm4t(a[i][0], ab + i * as);
                ldsm4t(a[i][1], (ab ^ 16) + i * as);
            }
            if (pass) {
                bar_sync(8, NCW * 32);
#pragma unroll
                for (int i = 0; i < 8; i++) bf[i] = 0;
                get<8, 1>(gs + near(D_H + warp * 256, lds32(sm + OFF_WIN + 4)) + lane, 32, bf);
                if (warp == 0) TSL(3);
            }
            float acc[2][4] = {};
#pragma unroll
            for (int i = 0; i < 4; i++)
#pragma unroll
                for (int m = 0; m < 2; m++) mma(acc[m], a[i][m][0], a[i][m][1], a[i][m][2], a[i][m][3], bf[2 * i], bf[2 * i + 1]);
            sts128f(red + tid * 16, acc[0]);
            sts128f(red + 4608 + tid * 16, acc[1]);
            bar_sync(3, 288);
            if (warp < 2) {
                float c[4] = {};
                sum_frags<9>(c, red + warp * 4608 + lane * 16, 512);
                uint32_t lo = movm(pack2(c[0], c[1])), hi = movm(pack2(c[2], c[3]));
                if (pass) {
                    put2d(gs + off_q, lo, hi);
                    if (warp == 0) TSL(4);
                } else {
                    const uint32_t hi1 = badd2(hi, ONE2);
                    if (pa) hi = lo = modulate2(xp, mean2, inv, lo, hi1);
                    if (cta >= 72 && cta < 90) lo = badd2(lo, ONE2), hi = hi1;
                    st1(gs + off_h, nz(lo));
                    st1(gs + off_h2, nz(hi));
                    if (warp == 0 && pa) TSL(2);
                }
            } else if (tid == 64 && pass == 0) {
                mbar_arrive(bars + BAR_WMF * 8);
            }
        }
    } else {
        if ((uint32_t)__cvta_generic_to_shared(smem_raw) != sm) __trap();
        uint32_t* const ping = g0 + dual(D_PING) + cta * 8;
        if (lane < 16) st1(ping + (lane >> 3) * 1024 + (lane & 7), 0);
        bar_sync(15, NTHREADS);
        uint32_t best[2] = {~0u, ~0u}, v = 0;
#pragma unroll 1
        for (int part = 0; part < 2; part++) {
            if (lane == 0) {
#pragma unroll 1
                for (int r = part ? NPING1 : NPING0; r > 0; r--) {
#pragma unroll
                    for (int k = 0; k < 2; k++) {
                        const uint32_t t0 = clock32(v);
                        v = atomicExch(ping + k * 1024, t0);
                        best[k] = min(best[k], clock32(v) - t0);
                    }
                }
                sts32(sm + OFF_WIN + 4 + 4 * part, ((best[1] < best[0]) ^ __popc(D_PING & 0x16400)) & 1);
            }
            __syncwarp();
            if (part) break;
            TSL(20);
            bar_arrive(8, NCW * 32);
            mbar_wait(bars + 5 * 8, 0);
            uint32_t a[4] = {};
            get<1, 4>(gs + near(D_Q + (sub * HQ + 2 * grp) * 64, lds32(sm + OFF_WIN + 4)) + lane * 4, 0, a);
            sts128(sm + OFF_QS + lane * 16, a[0], a[1], a[2], a[3]);
            __syncwarp();
            TSL(5);
            bar_arrive(4, 288);
        }
#pragma unroll
        for (int i = lane; i < 72; i += 32) cp16(sm + OFF_WR + i * 16, P.wr + i * 8);
        asm volatile("cp.async.wait_all;" ::: "memory");
        __syncwarp();
        bar_arrive(2, NCW * 32);
        if (cta == 0 && lane == 0) st1(g0 + (~epoch & 1) * G_SET + G_CNT, 0);
        mbar_wait(bars + (BAR_SYNC + 1) * 8, 0);
#pragma unroll 1
        for (int c = 0; c < 4; c++) {
            uint32_t* const pg = g0 + (c >> 1) * G_SET + (c & 1) * 1024;
            zero4(pg + dual(D_O + cta * 128) + lane * 4);
            zero4(pg + dual(D_ACT + (grp * 36 + 4 * sub) * 32) + lane * 4);
            if (lane < 8 ? sub < 4 : lane < 16 && cta < 72)
                zero4(pg + dual(lane < 8 ? D_ACT + (grp * 36 + 32 + sub) * 32 : D_X1 + cta * 32) + (lane & 7) * 4);
        }
#pragma unroll 1
        for (int u = 0; u < 9; u++) zero4(g0 + dual(d_part(u < 8 ? 8 * sub + u : 64 + sub)) + (lane >> 4) * 1024 + grp * 64 + (lane & 15) * 4);
        __syncwarp();
        bar_arrive(5, NCW * 32);
        {
            uint32_t* const nx = g0 + (~epoch & 1) * G_SET;
            uint32_t* const q = nx + dual(D_Q + g * (HQ * 64) + cta * 16) + t4 * 4;
            zero4(q), zero4(q + 1024);
            if (cta < 108) zero4(nx + (cta < 36 ? dual(D_H + 2 * cta * 32) + (lane >> 4) * (1024 - 64) : G_M + 4 * (cta - 36) * 32) + lane * 4);
        }
        return;
    }

    const uint32_t tile = sm + OFF_RING + warp * TILE_BYTES;
    const uint32_t fullb = bars + (BAR_FULL + warp) * 8;
    const uint32_t pw = sm + OFF_P + warp * (2 * P_PITCH);
    const bool pacer = (tid & 127) == (cta & 3) * 32;
    if (warp < 8) {
        {
            uint32_t q0[8], q1[8];
            bar_sync(4, 288);
#pragma unroll
            for (int i = 0; i < 8; i++) {
                const float2 v = lds64f(sm + OFF_QS + (g & 1) * 256 + i * 32 + t4 * 8);
                q0[i] = __float_as_uint(v.x), q1[i] = __float_as_uint(v.y);
            }
            uint32_t sp = pw + (t4 & 1) * P_PITCH + ((t4 >> 1) * 8 + g) * 2;
#pragma unroll 1
            for (int it = 0; it < 8; it++, sp += 64) {
                const uint32_t ab = tile + (it & 1) * (8 * TILE_BYTES) + (lane & 15) * 128 + (((lane >> 4) ^ (lane & 7)) << 4);
                mbar_wait(fullb + (it & 1) * 64, (it >> 1) & 1);
                float acc[2][2][4] = {};
#pragma unroll
                for (int ks = 0; ks < 8; ks++)
#pragma unroll
                    for (int m = 0; m < 2; m++) {
                        uint32_t a[4];
                        ldsm4(a, (ab ^ ((ks & 3) << 5)) + (ks >> 2) * 4096 + m * 2048);
                        mma(acc[m][ks & 1], a[0], a[1], a[2], a[3], (ks & 1) ? q1[ks - 1] : q0[ks], (ks & 1) ? q1[ks] : q0[ks + 1]);
                    }
                __syncwarp();
                if (lane == 0) mbar_arrive(fullb + (it & 1) * 64 + (BAR_EMPTY - BAR_FULL) * 8);
#pragma unroll
                for (int m = 0; m < 2; m++) {
                    const float s = sel4(acc[m][0], t4) + sel4(acc[m][1], t4);
                    sts16(sp + m * 32, (uint16_t)pack2(rbf(s) * 0.08838834764831845f, 0.f));
                }
                if (pacer && it >= 2) pace(it * 8 + warp, GAIN_KV);
                __syncwarp();
            }
        }
        __syncwarp();
        if (warp == 7) TSL(6);
        const uint32_t pa = pw + (lane >> 4) * P_PITCH + (lane & 15) * 32;
        const uint32_t sa = sm + OFF_SM + (lane >> 4) * 64;
        const uint4 v0 = lds128(pa), v1 = lds128(pa + 16);
        const uint32_t sv[8] = {v0.x, v0.y, v0.z, v0.w, v1.x, v1.y, v1.z, v1.w};
        float e[16];
        float m = -INFINITY;
#pragma unroll
        for (int i = 0; i < 8; i++) {
            e[2 * i] = blo(sv[i]);
            e[2 * i + 1] = bhi(sv[i]);
            m = fmaxf(m, fmaxf(e[2 * i], e[2 * i + 1]));
        }
#pragma unroll
        for (int o = 8; o; o >>= 1) m = fmaxf(m, __shfl_xor_sync(0xffffffffu, m, o));
        float l = 0.f;
#pragma unroll
        for (int i = 0; i < 16; i++) {
            e[i] = ex2((e[i] - m) * LOG2E);
            l += e[i];
        }
#pragma unroll
        for (int o = 8; o; o >>= 1) l += __shfl_xor_sync(0xffffffffu, l, o);
        if ((lane & 15) == 0) sts64(sa + warp * 8, __float_as_uint(m), __float_as_uint(l));
        bar_sync(2, NCW * 32);
        const float2 v = lds64f(sa + (lane & 7) * 8);
        float M = v.x;
#pragma unroll
        for (int o = 4; o; o >>= 1) M = fmaxf(M, __shfl_xor_sync(0xffffffffu, M, o));
        float L = v.y * ex2((v.x - M) * LOG2E);
#pragma unroll
        for (int o = 4; o; o >>= 1) L += __shfl_xor_sync(0xffffffffu, L, o);
        const float sc = ex2((m - M) * LOG2E) * rcp(L);
        sts128(pa, pack2(e[0] * sc, e[1] * sc), pack2(e[2] * sc, e[3] * sc), pack2(e[4] * sc, e[5] * sc), pack2(e[6] * sc, e[7] * sc));
        sts128(pa + 16, pack2(e[8] * sc, e[9] * sc), pack2(e[10] * sc, e[11] * sc), pack2(e[12] * sc, e[13] * sc), pack2(e[14] * sc, e[15] * sc));
        __syncwarp();
    } else {
        bar_sync(2, NCW * 32);
    }

    const bool reducer = cta < 72 && warp < 4;
    const int rbat = 2 * t4 + (g & 1);
    uint32_t sh[8] = {}, op[8] = {}, rx = 0, rg[2] = {};
    {
        const uint32_t* const src_m = gs + G_M + (72 + warp * 8) * 32 + lane;
        fetch<8, 1>(src_m + 72 * 32, 32, op);
        if (reducer) {
            rx = __ldg(reinterpret_cast<const uint32_t*>(P.x) + rbat * (DM / 2) + 4 * cta + warp);
            get<2, 1>(gs + G_M + cta * 32 + rbat * 4 + warp, 216 * 32, rg);
        }
        get<8, 1>(src_m, 32, sh);
        get<8, 1>(src_m + 72 * 32, 32, op);
    }
    const int side = lds32(sm + OFF_WIN + 8), set = (epoch & 1) * G_SET, rr = (lane >> 4) * 8 + (lane & 7);
    const uint32_t dst_o = pin(4 * (set + dual(D_O + cta * 128) + (tid & 0x70) + (tid & 3) * 4 + ((tid >> 2) & 3)));
    const uint32_t src_o = pin(4 * (set + near(D_O + grp * 1024, side) + g * 128 + warp * 16 + t4 * 4));
    const uint32_t dst_p = pin(4 * (dual(d_part(warp < 8 ? 8 * sub + warp : 64 + sub)) + grp * 64 + lane * 2));
    const uint32_t src_p = pin(4 * (near(d_part(cta), side) + (lane >> 3) * 256 + 16 * warp + (lane & 7) * 2));
    const uint32_t dst_x = pin(4 * (set + dual(D_X1 + cta * 32) + (lane >> 3) * 1024 + warp * 8 + (lane & 7)));
    const uint32_t src_x = pin(4 * (set + near(D_X1 + warp * 256, side) + t4 * 8 + (g & 1) * 4 + (g >> 1)));
    const uint32_t dst_a = pin(4 * (set + dual(D_ACT + (grp * 36 + (warp < 4 ? 4 * sub + warp : 32 + sub)) * 32) + lane));
    const uint32_t src_a = pin(4 * (set + near(D_ACT + (grp * 36 + 4 * warp) * 32, side) + lane));
    const uint32_t dst_out = pin(4 * (rbat * (DM / 2) + 4 * cta + warp));
    const uint32_t rowoff = pin((warp * 32 + rr) * 128 + ((((lane >> 3) & 1) ^ (lane & 7)) << 4));
    const uint32_t reds = pin((tid * 8) | (warp * 2304 + lane * 8) << 16);
    const uint32_t ored = pin((warp * 1088 + (t4 & 1) * 576 + ((t4 >> 1) * 8 + g) * 4) | ((tid >> 6) * 64 + tid * 8) << 16);

    if (warp < 8) {
        float acc[8][4] = {};
        uint32_t pp = pw + (lane & 1) * P_PITCH + (lane >> 3) * 16;
#pragma unroll 1
        for (int it = 0; it < 8; it++, pp += 64) {
            const uint32_t ab = tile + (it & 1) * (8 * TILE_BYTES) + ((lane & 7) + (lane >> 4) * 8) * 128 + ((((lane >> 3) & 1) ^ (lane & 7)) << 4);
            uint32_t pb[4];
            ldsm4(pb, pp);
            mbar_wait(fullb + (it & 1) * 64, (it >> 1) & 1);
#pragma unroll
            for (int ks = 0; ks < 2; ks++)
#pragma unroll
                for (int m = 0; m < 8; m++) {
                    uint32_t a[4];
                    ldsm4t(a, (ab ^ ((m & 3) << 5)) + (m >> 2) * 4096 + ks * 2048);
                    mma(acc[m], a[0], a[1], a[2], a[3], pb[2 * ks], pb[2 * ks + 1]);
                }
            __syncwarp();
            if (lane == 0) mbar_arrive(fullb + (it & 1) * 64 + (BAR_EMPTY - BAR_FULL) * 8);
            if (pacer && it * 8 + warp < NT - 4) pace(NT + it * 8 + warp, GAIN_KV);
            __syncwarp();
        }
        if (warp == 7) TSL(7);
        const uint32_t ra = sm + OFF_ORED + (ored & 0xffff);
#pragma unroll
        for (int m = 0; m < 8; m++) sts32(ra + m * 64, __float_as_uint(sel4(acc[m], t4)));
    }
    bar_sync(5, NCW * 32);
    if (warp < 4) {
        float s[2][2] = {};
#pragma unroll
        for (int w = 0; w < 8; w++) {
            const float2 v = lds64f(sm + OFF_ORED + w * 1088 + (ored >> 16));
            s[w & 1][0] += v.x;
            s[w & 1][1] += v.y;
        }
        put1d(at(g0, dst_o), pack2(s[0][0] + s[1][0], s[0][1] + s[1][1]));
        if (warp == 0) TSL(8);
    }

    project<0>(sm, at(g0, src_o), at(g0, dst_p), rowoff, reds, warp, lane);
    if (warp == 0) TSL(9);
    if (reducer) {
        rx = badd2(rx, bmul2(rg[0], reduce16<0>(at(g0, src_p), lane)));
        if (lane < 16) st1(at(g0, dst_x), nz(rx));
        if (warp == 0) TSL(10);
    }

    const uint32_t gbar = bars + (BAR_GU + warp) * 8;
    const int pl = ((lane >> 3) & 1) ^ P.zg;
    const uint32_t ab = sm + OFF_GU + warp * 8192 + pl * 4096 + rr * 64 + ((lane & 6) << 3);
    const uint32_t ax = sm + OFF_GX + warp * 2048 + pl * 1024 + rr * 16;
    uint32_t a[20][4] = {}, h[8] = {};
    auto load_gu = [&]() {
#pragma unroll
        for (int i = 0; i < 20; i++) ldsm4t(a[i], i % 5 < 4 ? (ab ^ ((i % 5) << 4)) + (i / 5) * 1024 : ax + (i / 5) * 256);
    };
    bool gpre = false;
    {
        int it = 0;
        do {
            if (!gpre && __all_sync(0xffffffffu, mbar_test(gbar, 0))) gpre = true, load_gu();
            fetch<8, 1>(at(g0, src_x), 32, h);
        } while (missing(h) & (++it < SPIN_LIMIT));
    }
    if (warp == 0) TSL(11);
    ln_partial(h, sm + OFF_ST + g * 80 + warp * 8, t4 == 0);
    bar_sync(3, 288);
    {
        uint32_t mean2;
        float inv;
        ln_combine(sm + OFF_ST + g * 80, mean2, inv);
#pragma unroll
        for (int i = 0; i < 8; i++) h[i] = modulate2(h[i], mean2, inv, sh[i], op[i]);
    }
    if (warp == 0) TSL(12);
    if (!gpre) {
        mbar_wait(gbar, 0);
        load_gu();
    }
    if (warp == 8) TSL(17);
    {
        float acc[5][4] = {};
#pragma unroll
        for (int i = 0; i < 20; i++) mma(acc[i % 5], a[i][0], a[i][1], a[i][2], a[i][3], h[2 * (i / 5)], h[2 * (i / 5) + 1]);
#pragma unroll
        for (int m = 0; m < 5; m++) sts128f(sm + OFF_RED + m * 4608 + 2 * (reds & 0xffff), acc[m]);
    }
    bar_sync(3, 288);
    if (warp < 5) {
        float c[4] = {};
        sum_frags<9>(c, sm + OFF_RED + 2 * (reds >> 16), 512);
        const uint32_t w = movm(bmul2(silu2(pack2(c[0], c[1])), pack2(c[2], c[3])));
        if (warp < 4 || sub < 4) put1d(at(g0, dst_a), w);
        if (warp == 1) TSL(13);
    }
    if (cta < 72) {
        float r = 0.f;
#pragma unroll
        for (int i = 0; i < 8; i++) {
            const uint32_t wr = lds32(sm + OFF_WR + (warp * 32 + i * 4 + t4) * 4);
            r = fmaf(blo(h[i]), blo(wr), fmaf(bhi(h[i]), bhi(wr), r));
            if (warp * 8 + i == cta) sts32(sm + OFF_HU + lane * 4, h[i]);
        }
        r = quad_sum(r);
        if (t4 == 0) sts32(sm + OFF_RT + g * 48 + warp * 4, __float_as_uint(r));
    }

    project<1>(sm, at(g0, src_a), at(g0, dst_p), rowoff, reds, warp, lane);
    if (warp == 0) TSL(14);
    if (reducer) {
        const uint4 r0 = lds128(sm + OFF_RT + rbat * 48), r1 = lds128(sm + OFF_RT + rbat * 48 + 16);
        float r = __uint_as_float(lds32(sm + OFF_RT + rbat * 48 + 32));
        r += ((__uint_as_float(r0.x) + __uint_as_float(r0.y)) + (__uint_as_float(r0.z) + __uint_as_float(r0.w))) +
             ((__uint_as_float(r1.x) + __uint_as_float(r1.y)) + (__uint_as_float(r1.z) + __uint_as_float(r1.w)));
        r = sigmoid_f(rbf(r));
        const uint32_t rh = lds32(sm + OFF_HU + (rbat * 4 + warp) * 4);
        const uint32_t y = badd2(rh, bmul2(reduce16<1>(at(g0, src_p), lane), pack2(r, r)));
        if (lane < 8) *at(reinterpret_cast<uint32_t*>(P.out), dst_out) = badd2(rx, bmul2(rg[1], y));
        if (cta == 0 && tid == 0) g0[G_EPOCH] = epoch + 1;
        if (warp == 0) TSL(15);
    }
}

typedef CUresult (*EncodeFn)(CUtensorMap*, CUtensorMapDataType, cuuint32_t, void*, const cuuint64_t*, const cuuint64_t*,
                             const cuuint32_t*, const cuuint32_t*, CUtensorMapInterleave, CUtensorMapSwizzle,
                             CUtensorMapL2promotion, CUtensorMapFloatOOBfill);

void make_map(EncodeFn enc, CUtensorMap* m, void* p, int cols, int rows, int pitch, int bc, int br, int bp, int planes, size_t pstride,
              CUtensorMapSwizzle sw, int promo) {
    cuuint64_t dims[3] = {(cuuint64_t)cols, (cuuint64_t)rows, (cuuint64_t)planes};
    cuuint64_t strides[2] = {(cuuint64_t)pitch * 2, (cuuint64_t)pstride};
    cuuint32_t box[3] = {(cuuint32_t)bc, (cuuint32_t)br, (cuuint32_t)bp};
    cuuint32_t es[3] = {1, 1, 1};
    enc(m, CU_TENSOR_MAP_DATA_TYPE_BFLOAT16, 3, p, dims, strides, box, es, CU_TENSOR_MAP_INTERLEAVE_NONE, sw,
        (CUtensorMapL2promotion)promo, CU_TENSOR_MAP_FLOAT_OOB_FILL_NONE);
}

}

extern "C" void kernel_launch(void* const* d_in, const int* in_sizes, int n_in, void* d_out, int out_size) {
    static EncodeFn enc = nullptr;
    static uint32_t* scratch = nullptr;
    if (!enc) {
        void* fn = nullptr;
        cudaDriverEntryPointQueryResult st;
        cudaGetDriverEntryPoint("cuTensorMapEncodeTiled", &fn, cudaEnableDefault, &st);
        enc = (EncodeFn)fn;
        cudaGetSymbolAddress(&fn, g_scratch);
        scratch = (uint32_t*)(((uintptr_t)fn + 8 * G_SET - 1) & ~(uintptr_t)(8 * G_SET - 1));
        cudaFuncSetAttribute(fused_kernel, cudaFuncAttributeMaxDynamicSharedMemorySize, SMEM_BYTES);
    }
    Params P;
    const CUtensorMapSwizzle none = CU_TENSOR_MAP_SWIZZLE_NONE;
    make_map(enc, &P.m[M_K], d_in[1], 64, NB * HKV * SK, DH, 64, 32, 2, 2, 128, CU_TENSOR_MAP_SWIZZLE_128B, PROMO_KV);
    make_map(enc, &P.m[M_V], d_in[2], 64, NB * HKV * SK, DH, 64, 32, 2, 2, 128, CU_TENSOR_MAP_SWIZZLE_128B, PROMO_KV);
    make_map(enc, &P.m[M_WQ], d_in[3], HQ * DH, DM, HQ * DH, 32, 192, 1, 1, 16, CU_TENSOR_MAP_SWIZZLE_64B, PROMO_W);
    make_map(enc, &P.m[M_WM], d_in[11], 6 * DM, DM, 6 * DM, 32, 192, 1, 1, 16, CU_TENSOR_MAP_SWIZZLE_64B, PROMO_W);
    make_map(enc, &P.m[M_WA], d_in[11], DM, DM, 6 * DM, 16, 192, 2, 2, DM * 2, CU_TENSOR_MAP_SWIZZLE_32B, PROMO_W);
    char *wg = (char*)d_in[7], *wu = (char*)d_in[8], *wo = (char*)d_in[4], *wd = (char*)d_in[9];
    P.zg = wg > wu;
    P.zo = wo > wd;
    const size_t sg = P.zg ? wg - wu : wu - wg, so = P.zo ? wo - wd : wd - wo;
    make_map(enc, &P.m[M_GU], P.zg ? wu : wg, FF, DM, FF, 32, 64, 2, 2, sg, CU_TENSOR_MAP_SWIZZLE_64B, PROMO_GU);
    make_map(enc, &P.m[M_GX], P.zg ? wu : wg, FF, DM, FF, 8, 64, 2, 2, sg, none, PROMO_GX);
    make_map(enc, &P.m[M_OD], P.zo ? wd : wo, DM, FF, DM, 64, 64, 1, 2, so, CU_TENSOR_MAP_SWIZZLE_128B, PROMO_W);
    make_map(enc, &P.m[M_OX], P.zo ? wd : wo, DM, FF, DM, 8, 64, 1, 2, so, none, PROMO_OX);
    P.x = (const __nv_bfloat16*)d_in[0];
    P.wr = (const __nv_bfloat16*)d_in[6];
    P.c = (const __nv_bfloat16*)d_in[10];
    P.out = (__nv_bfloat16*)d_out;
    P.scratch = scratch;
    fused_kernel<<<NCTA, NTHREADS, SMEM_BYTES>>>(P);
}
```

```cpp
#include <cuda_runtime.h>
#include <cuda_bf16.h>
#include <cuda.h>
#include <stdint.h>

typedef unsigned long long u64;

#define W_KV 20
#define W_WO 19
#define W_GU 19
#define W_GU2 W_GU
#define W_WD 13
#define W_MIN -8
#define W_MAX 8
#define GAIN_KV 2
#define GAIN_TAIL 3
#define NK0 2
#define T_CLEAR 116
#define B_CAP 8
#define WD_ROT 3
#define NPING0 4
#define NPING1 16
#define PROMO_W CU_TENSOR_MAP_L2_PROMOTION_L2_128B
#define PROMO_GX 2
#define PROMO_OX 2
#define PROMO_GU 2
#define PROMO_KV CU_TENSOR_MAP_L2_PROMOTION_L2_256B

namespace {

constexpr int NB = 8, DM = 576, HQ = 32, HKV = 16, SK = 8192, WIN = 2048, DH = 128, FF = 4608;
constexpr int NCTA = 128;
constexpr int NCW = 10;
constexpr int NTHREADS = (NCW + 2) * 32;
constexpr int TILE_BYTES = 8192, NSLOT = 16, NT = 64;
constexpr int SPIN_LIMIT = 1 << 22;

constexpr int OFF_RING = 0;
constexpr int OFF_WM = 121856;
constexpr int OFF_WQ = OFF_WM + 36864;
constexpr int OFF_GU = 0;
constexpr int OFF_WD = 73728;
constexpr int OFF_OX = 131072;
constexpr int OFF_DX = OFF_OX + 4096;
constexpr int OFF_GX = OFF_DX + 4608;
constexpr int OFF_WO = OFF_WQ;
constexpr int OFF_P = OFF_WQ + 36864;
constexpr int P_PITCH = 528;
constexpr int OFF_RED = OFF_P + 16 * P_PITCH;
constexpr int OFF_ORED = OFF_RED + 5 * 4608 - 8704;
constexpr int OFF_ST = OFF_RED + 5 * 4608;
constexpr int OFF_SM = OFF_ST + 640;
constexpr int OFF_RT = OFF_SM + 128;
constexpr int OFF_HU = OFF_RT + 384;
constexpr int OFF_QS = OFF_HU + 128;
constexpr int OFF_WR = OFF_QS + 512;
constexpr int OFF_WIN = OFF_WR + 1152;
constexpr int OFF_BAR = OFF_WIN + 16;
constexpr int BAR_FULL = 6, BAR_WO = 22, BAR_GU = 26, BAR_WD = 35, BAR_EMPTY = 40, BAR_SYNC = 56, BAR_WMF = 59, NBAR = 70;
constexpr int SMEM_BYTES = OFF_BAR + NBAR * 8;

constexpr int D_X1 = 0;
constexpr int D_O = 3072;
constexpr int D_ACT = D_O + 512 * 32;
constexpr int D_H = D_ACT + 576 * 32;
constexpr int D_Q = D_H + 3072;
constexpr int G_M = 2 * (D_Q + NB * HQ * 64);
constexpr int G_CNT = G_M + 288 * 32;
constexpr int G_SET = 1 << 18;
__device__ __forceinline__ int d_part(int unit) { return (64 + unit + (unit & 64)) * 1024; }
constexpr int D_PING = 200 * 1024;
constexpr int G_EPOCH = 201 * 2048;
static_assert(G_CNT < 64 * 2048, "scratch layout");
__device__ uint32_t g_scratch[4 * G_SET];
__device__ __forceinline__ int dual(int w) { return w + (w & ~1023); }
__device__ __forceinline__ int near(int w, int side) { return dual(w) + (((__popc(w & 0x16400) ^ side) & 1) << 10); }

#define TI(i)
#define TS(i)
#define TSL(i)

enum { M_K, M_V, M_GU, M_GX, M_OD, M_OX, M_WQ, M_WM, M_WA, NMAP };
struct Params {
    const __nv_bfloat16 *c, *x, *wr;
    __nv_bfloat16* out;
    uint32_t* scratch;
    int zg, zo;
};
struct Maps {
    CUtensorMap m[NMAP];
};

__device__ __forceinline__ void mbar_init(uint32_t bar, int cnt) {
    asm volatile("mbarrier.init.shared::cta.b64 [%0], %1;" ::"r"(bar), "r"(cnt));
}
__device__ __forceinline__ void mbar_expect(uint32_t bar, uint32_t bytes) {
    asm volatile("mbarrier.arrive.expect_tx.shared::cta.b64 _, [%0], %1;" ::"r"(bar), "r"(bytes) : "memory");
}
__device__ __forceinline__ void mbar_arrive(uint32_t bar) {
    asm volatile("mbarrier.arrive.shared::cta.b64 _, [%0];" ::"r"(bar) : "memory");
}
__device__ __forceinline__ void mbar_wait(uint32_t bar, uint32_t parity) {
    asm volatile("{\n.reg .pred p;\n.reg .u32 c;\n"
                 "mbarrier.try_wait.parity.shared::cta.b64 p, [%0], %1;\n@p bra DONE;\nmov.u32 c, %2;\n"
                 "AGAIN:\nmbarrier.try_wait.parity.shared::cta.b64 p, [%0], %1;\nsub.u32 c, c, 1;\n"
                 "setp.eq.or.u32 p, c, 0, p;\n@!p bra AGAIN;\nDONE:\n}"
                 ::"r"(bar), "r"(parity), "n"(SPIN_LIMIT) : "memory");
}
__device__ __forceinline__ bool mbar_test(uint32_t bar, uint32_t parity) {
    uint32_t ok;
    asm volatile("{\n.reg .pred p;\nmbarrier.test_wait.parity.shared::cta.b64 p, [%1], %2;\nselp.u32 %0, 1, 0, p;\n}"
                 : "=r"(ok) : "r"(bar), "r"(parity) : "memory");
    return ok;
}
__device__ __forceinline__ void mbar_wait_lanes(uint32_t bar) {
    mbar_wait(bar, 0);
    __syncwarp();
}
__device__ __forceinline__ void tma3d_hint(uint32_t dst, const CUtensorMap* m, int x, int y, int z, uint32_t bar, u64 pol) {
    asm volatile("cp.async.bulk.tensor.3d.shared::cluster.global.mbarrier::complete_tx::bytes.L2::cache_hint"
                 " [%0], [%1, {%2, %3, %4}], [%5], %6;"
                 ::"r"(dst), "l"(m), "r"(x), "r"(y), "r"(z), "r"(bar), "l"(pol) : "memory");
}
__device__ __forceinline__ void tma3d(uint32_t dst, const CUtensorMap* m, int x, int y, int z, uint32_t bar) {
    asm volatile("cp.async.bulk.tensor.3d.shared::cluster.global.mbarrier::complete_tx::bytes [%0], [%1, {%2, %3, %4}], [%5];"
                 ::"r"(dst), "l"(m), "r"(x), "r"(y), "r"(z), "r"(bar) : "memory");
}
__device__ __forceinline__ void bar_sync(int id, int n) { asm volatile("bar.sync %0, %1;" ::"r"(id), "r"(n) : "memory"); }
__device__ __forceinline__ void bar_arrive(int id, int n) { asm volatile("bar.arrive %0, %1;" ::"r"(id), "r"(n) : "memory"); }
__device__ __forceinline__ void ldsm4(uint32_t (&r)[4], uint32_t a) {
    asm volatile("ldmatrix.sync.aligned.m8n8.x4.shared.b16 {%0,%1,%2,%3}, [%4];"
                 : "=r"(r[0]), "=r"(r[1]), "=r"(r[2]), "=r"(r[3]) : "r"(a) : "memory");
}
__device__ __forceinline__ void ldsm4t(uint32_t (&r)[4], uint32_t a) {
    asm volatile("ldmatrix.sync.aligned.m8n8.x4.trans.shared.b16 {%0,%1,%2,%3}, [%4];"
                 : "=r"(r[0]), "=r"(r[1]), "=r"(r[2]), "=r"(r[3]) : "r"(a) : "memory");
}
__device__ __forceinline__ void mma(float (&c)[4], uint32_t a0, uint32_t a1, uint32_t a2, uint32_t a3, uint32_t b0, uint32_t b1) {
    asm volatile("mma.sync.aligned.m16n8k16.row.col.f32.bf16.bf16.f32 {%0,%1,%2,%3}, {%4,%5,%6,%7}, {%8,%9}, {%0,%1,%2,%3};"
                 : "+f"(c[0]), "+f"(c[1]), "+f"(c[2]), "+f"(c[3])
                 : "r"(a0), "r"(a1), "r"(a2), "r"(a3), "r"(b0), "r"(b1));
}
__device__ __forceinline__ uint32_t movm(uint32_t a) {
    uint32_t d;
    asm volatile("movmatrix.sync.aligned.m8n8.trans.b16 %0, %1;" : "=r"(d) : "r"(a));
    return d;
}
__device__ __forceinline__ uint32_t lds32(uint32_t a) { uint32_t v; asm volatile("ld.shared.b32 %0, [%1];" : "=r"(v) : "r"(a) : "memory"); return v; }
__device__ __forceinline__ float2 lds64f(uint32_t a) { float2 v; asm volatile("ld.shared.v2.f32 {%0,%1}, [%2];" : "=f"(v.x), "=f"(v.y) : "r"(a) : "memory"); return v; }
__device__ __forceinline__ uint4 lds128(uint32_t a) { uint4 v; asm volatile("ld.shared.v4.b32 {%0,%1,%2,%3}, [%4];" : "=r"(v.x), "=r"(v.y), "=r"(v.z), "=r"(v.w) : "r"(a) : "memory"); return v; }
__device__ __forceinline__ void sts32(uint32_t a, uint32_t v) { asm volatile("st.shared.b32 [%0], %1;" ::"r"(a), "r"(v) : "memory"); }
__device__ __forceinline__ void sts16(uint32_t a, uint16_t v) { asm volatile("st.shared.b16 [%0], %1;" ::"r"(a), "h"(v) : "memory"); }
__device__ __forceinline__ void sts64(uint32_t a, uint32_t x, uint32_t y) { asm volatile("st.shared.v2.b32 [%0], {%1,%2};" ::"r"(a), "r"(x), "r"(y) : "memory"); }
__device__ __forceinline__ void sts128(uint32_t a, uint32_t x, uint32_t y, uint32_t z, uint32_t w) {
    asm volatile("st.shared.v4.b32 [%0], {%1,%2,%3,%4};" ::"r"(a), "r"(x), "r"(y), "r"(z), "r"(w) : "memory");
}
__device__ __forceinline__ void sts128f(uint32_t a, const float (&c)[4]) {
    sts128(a, __float_as_uint(c[0]), __float_as_uint(c[1]), __float_as_uint(c[2]), __float_as_uint(c[3]));
}

__device__ __forceinline__ float sel4(const float (&c)[4], int t) { return (t & 2) ? ((t & 1) ? c[3] : c[2]) : ((t & 1) ? c[1] : c[0]); }

template <int LUT>
__device__ __forceinline__ uint32_t lop3(uint32_t a, uint32_t b, uint32_t c) {
    uint32_t d;
    asm("lop3.b32 %0, %1, %2, %3, %4;" : "=r"(d) : "r"(a), "r"(b), "r"(c), "n"(LUT));
    return d;
}
__device__ __forceinline__ uint32_t pin(uint32_t v) { return __shfl_xor_sync(0xffffffffu, v, 0); }
template <typename T>
__device__ __forceinline__ T* at(T* base, uint32_t bytes) { return reinterpret_cast<T*>(reinterpret_cast<char*>(base) + bytes); }

__device__ __forceinline__ uint32_t clock32(uint32_t dep) {
    uint32_t t;
    asm volatile("{\n.reg .pred p;\nsetp.eq.u32 p, %1, 0x9e3779b9;\n@p nanosleep.u32 1;\nmov.u32 %0, %clock;\n}" : "=r"(t) : "r"(dep) : "memory");
    return t;
}

__device__ __forceinline__ uint32_t nz(uint32_t v) { return v ? v : 0x80000000u; }
__device__ __forceinline__ void st1(uint32_t* p, uint32_t a) { asm volatile("st.relaxed.gpu.global.b32 [%0], %1;" ::"l"(p), "r"(a) : "memory"); }
__device__ __forceinline__ void st2(uint32_t* p, uint32_t a, uint32_t b) {
    asm volatile("st.relaxed.gpu.global.v2.b32 [%0], {%1,%2};" ::"l"(p), "r"(a), "r"(b) : "memory");
}
__device__ __forceinline__ void zero4(uint32_t* p) { asm volatile("st.relaxed.gpu.global.v4.b32 [%0], {%1,%1,%1,%1};" ::"l"(p), "r"(0) : "memory"); }
__device__ __forceinline__ void put1d(uint32_t* p, uint32_t a) { a = nz(a), st1(p, a), st1(p + 1024, a); }
__device__ __forceinline__ void put2d(uint32_t* p, uint32_t a, uint32_t b) { a = nz(a), b = nz(b), st2(p, a, b), st2(p + 1024, a, b); }
__device__ __forceinline__ uint32_t ld1(const uint32_t* p) {
    uint32_t v;
    asm volatile("ld.relaxed.gpu.global.b32 %0, [%1];" : "=r"(v) : "l"(p) : "memory");
    return v;
}
template <int N, int V>
__device__ __forceinline__ void fetch(const uint32_t* p, int stride, uint32_t (&a)[N * V]) {
#pragma unroll
    for (int i = 0; i < N; i++) {
        if (V == 1)
            asm volatile("{\n.reg .pred p;\nsetp.eq.u32 p, %0, 0;\n@p ld.relaxed.gpu.global.b32 %0, [%1];\n}"
                         : "+r"(a[i]) : "l"(p + i * stride) : "memory");
        if (V == 4)
            asm volatile("{\n.reg .pred p;\nsetp.eq.u32 p, %4, 0;\n@p ld.relaxed.gpu.global.v4.b32 {%0,%1,%2,%3}, [%5];\n}"
                         : "+r"(a[V * i]), "+r"(a[V * i + V / 4]), "+r"(a[V * i + V / 2]), "+r"(a[V * i + V - 1])
                         : "r"(min(min(a[V * i], a[V * i + V / 4]), min(a[V * i + V / 2], a[V * i + V - 1]))), "l"(p + i * stride) : "memory");
    }
}
template <int N>
__device__ __forceinline__ bool missing(const uint32_t (&a)[N]) {
    uint32_t lo = a[0];
#pragma unroll
    for (int i = 1; i < N; i++) lo = min(lo, a[i]);
    return __any_sync(0xffffffffu, lo == 0);
}
template <int N, int V>
__device__ __forceinline__ void get(const uint32_t* p, int stride, uint32_t (&a)[N * V]) {
    int it = 0;
    do fetch<N, V>(p, stride, a);
    while (missing(a) & (++it < SPIN_LIMIT));
}
__device__ __forceinline__ void cp16(uint32_t dst, const void* src) {
    asm volatile("cp.async.cg.shared.global [%0], [%1], 16;" ::"r"(dst), "l"(src) : "memory");
}

__device__ __forceinline__ uint32_t pack2(float lo, float hi) {
    uint32_t r;
    asm("cvt.rn.bf16x2.f32 %0, %1, %2;" : "=r"(r) : "f"(hi), "f"(lo));
    return r;
}
__device__ __forceinline__ float rbf(float x) { return __uint_as_float(pack2(0.f, x)); }
__device__ __forceinline__ float blo(uint32_t v) { return __uint_as_float(v << 16); }
__device__ __forceinline__ float bhi(uint32_t v) { return __uint_as_float(v & 0xffff0000u); }
__device__ __forceinline__ uint32_t badd2(uint32_t a, uint32_t b) { uint32_t r; asm("add.rn.bf16x2 %0, %1, %2;" : "=r"(r) : "r"(a), "r"(b)); return r; }
__device__ __forceinline__ uint32_t bsub2(uint32_t a, uint32_t b) { uint32_t r; asm("sub.rn.bf16x2 %0, %1, %2;" : "=r"(r) : "r"(a), "r"(b)); return r; }
__device__ __forceinline__ uint32_t bmul2(uint32_t a, uint32_t b) { uint32_t r; asm("mul.rn.bf16x2 %0, %1, %2;" : "=r"(r) : "r"(a), "r"(b)); return r; }
__device__ __forceinline__ float ex2(float x) { float r; asm("ex2.approx.ftz.f32 %0, %1;" : "=f"(r) : "f"(x)); return r; }
__device__ __forceinline__ float rcp(float x) { float r; asm("rcp.approx.ftz.f32 %0, %1;" : "=f"(r) : "f"(x)); return r; }
__device__ __forceinline__ float sqrt_f(float x) { float r; asm("sqrt.approx.ftz.f32 %0, %1;" : "=f"(r) : "f"(x)); return r; }
constexpr float LOG2E = 1.4426950408889634f;
constexpr uint32_t ONE2 = 0x3f803f80u;
__device__ __forceinline__ float sigmoid_f(float x) { return rcp(1.0f + ex2(-LOG2E * x)); }
__device__ __forceinline__ uint32_t silu2(uint32_t v) {
    const float a = blo(v), b = bhi(v);
    return pack2(a * sigmoid_f(a), b * sigmoid_f(b));
}
__device__ __forceinline__ float quad_sum(float v) {
    v += __shfl_xor_sync(0xffffffffu, v, 1);
    return v + __shfl_xor_sync(0xffffffffu, v, 2);
}
__device__ __forceinline__ void ln_partial(const uint32_t (&v)[8], uint32_t dst, bool writer) {
    float s0 = 0.f, s1 = 0.f;
#pragma unroll
    for (int i = 0; i < 8; i++) {
        s0 += blo(v[i]);
        s1 += bhi(v[i]);
    }
    const float mean = quad_sum(s0 + s1) * (1.0f / 64);
    s0 = s1 = 0.f;
#pragma unroll
    for (int i = 0; i < 8; i++) {
        const float a = blo(v[i]) - mean, b = bhi(v[i]) - mean;
        s0 = fmaf(a, a, s0);
        s1 = fmaf(b, b, s1);
    }
    s0 = quad_sum(s0 + s1);
    if (writer) sts64(dst, __float_as_uint(mean), __float_as_uint(s0));
}
__device__ __forceinline__ void ln_combine(uint32_t src, uint32_t& mean2, float& inv) {
    float m[10], q0 = 0.f, q1 = 0.f, s = 0.f;
#pragma unroll
    for (int i = 0; i < 5; i++) {
        const uint4 v = lds128(src + i * 16);
        m[2 * i] = __uint_as_float(v.x);
        m[2 * i + 1] = __uint_as_float(v.z);
        q0 += __uint_as_float(v.y);
        if (i < 4) q1 += __uint_as_float(v.w);
    }
    const float mean = (((m[0] + m[1]) + (m[2] + m[3])) + ((m[4] + m[5]) + (m[6] + m[7])) + m[8]) * (1.0f / 9);
#pragma unroll
    for (int i = 0; i < 9; i++) s = fmaf(m[i] - mean, m[i] - mean, s);
    const float var = fmaf(s, 64.f, q0 + q1) * (1.0f / DM);
    mean2 = pack2(mean, mean);
    inv = rcp(rbf(sqrt_f(rbf(rbf(var) + 1e-5f))));
}
__device__ __forceinline__ uint32_t modulate2(uint32_t x, uint32_t mean2, float inv, uint32_t shift, uint32_t onep) {
    const uint32_t d = bsub2(x, mean2);
    return badd2(bmul2(pack2(blo(d) * inv, bhi(d) * inv), onep), shift);
}
template <int N>
__device__ __forceinline__ void sum_frags(float (&c)[4], uint32_t addr, int stride) {
#pragma unroll
    for (int w = 0; w < N; w++) {
        const uint4 v = lds128(addr + w * stride);
        c[0] += __uint_as_float(v.x); c[1] += __uint_as_float(v.y);
        c[2] += __uint_as_float(v.z); c[3] += __uint_as_float(v.w);
    }
}

template <int ST>
__device__ __forceinline__ void project(uint32_t sm, const uint32_t* src, uint32_t* dst, uint32_t rowoff, uint32_t reds, int warp, int lane) {
    constexpr int NW = ST ? 9 : 8;
    const uint32_t red = sm + (ST ? OFF_WO : OFF_P);
    if (warp < NW) {
        const uint32_t wbar = sm + OFF_BAR + (ST ? BAR_WD + (warp < 8 ? ((warp >> 1) - WD_ROT) & 3 : 4) : BAR_WO + (warp >> 1)) * 8;
        const uint32_t ab = sm + (ST ? OFF_WD : OFF_WO) + rowoff;
        const uint32_t ax = sm + (ST ? OFF_DX : OFF_OX) + ((rowoff >> 7) << 4);
        uint32_t a[10][4] = {}, b[4] = {};
        bool have_w = false, need_b = true;
        int it = 0;
        do {
            if (!need_b) mbar_wait(wbar, 0);
            if (!need_b || (!have_w && __all_sync(0xffffffffu, mbar_test(wbar, 0)))) {
                have_w = true;
#pragma unroll
                for (int i = 0; i < 10; i++) ldsm4t(a[i], i % 5 < 4 ? (ab ^ ((i % 5) << 5)) + (i / 5) * 2048 : ax + (i / 5) * 256);
                if (!need_b) break;
            }
            if (ST) fetch<4, 1>(src, 32, b);
            else fetch<1, 4>(src, 0, b);
            need_b = missing(b) & (++it < SPIN_LIMIT);
        } while (need_b | !have_w);
        if (warp == 0) TSL(ST ? 24 : 21);
        float acc[5][4] = {};
#pragma unroll
        for (int i = 0; i < 10; i++) mma(acc[i % 5], a[i][0], a[i][1], a[i][2], a[i][3], b[2 * (i / 5)], b[2 * (i / 5) + 1]);
#pragma unroll
        for (int u = 0; u < 9; u++)
            sts64(red + u * 2304 + (reds & 0xffff), __float_as_uint(acc[u >> 1][2 * (u & 1)]), __float_as_uint(acc[u >> 1][2 * (u & 1) + 1]));
    }
    bar_sync(3, 288);
    float s[2][2] = {};
#pragma unroll
    for (int w = 0; w < NW; w++) {
        const float2 v = lds64f(red + (reds >> 16) + w * 256);
        s[w & 1][0] += v.x;
        s[w & 1][1] += v.y;
    }
    const uint32_t p0 = (__float_as_uint(s[0][0] + s[1][0]) | 1) ^ ST, p1 = (__float_as_uint(s[0][1] + s[1][1]) | 1) ^ ST;
    st2(dst, p0, p1), st2(dst + 1024, p0, p1);
}

template <int ST>
__device__ __forceinline__ uint32_t reduce16(const uint32_t* src, int lane) {
    uint32_t a[8] = {}, bad[4] = {1, 1, 1, 1};
    int it = 0;
    do {
#pragma unroll
        for (int i = 0; i < 4; i++)
            asm volatile("{\n.reg .pred p;\nsetp.ne.u32 p, %2, 0;\n@p ld.relaxed.gpu.global.v2.b32 {%0,%1}, [%3];\n}"
                         : "+r"(a[2 * i]), "+r"(a[2 * i + 1]) : "r"(bad[i]), "l"(src + i * 64) : "memory");
#pragma unroll
        for (int i = 0; i < 4; i++) bad[i] = lop3<ST ? 0xa8 : 0x2a>(a[2 * i], a[2 * i + 1], 1);
    } while (__any_sync(0xffffffffu, (lop3<0xfe>(bad[0], bad[1], bad[2]) | bad[3]) != 0) & (++it < SPIN_LIMIT));
    float s0 = (__uint_as_float(a[0]) + __uint_as_float(a[2])) + (__uint_as_float(a[4]) + __uint_as_float(a[6]));
    float s1 = (__uint_as_float(a[1]) + __uint_as_float(a[3])) + (__uint_as_float(a[5]) + __uint_as_float(a[7]));
#pragma unroll
    for (int o = 8; o < 32; o <<= 1) {
        s0 += __shfl_xor_sync(0xffffffffu, s0, o);
        s1 += __shfl_xor_sync(0xffffffffu, s1, o);
    }
    const uint32_t y = pack2(s0, s1);
    return __byte_perm(y, __shfl_xor_sync(0xffffffffu, y, 4), (lane & 4) ? 0x3276 : 0x5410);
}

__global__ void __launch_bounds__(NTHREADS, 1) fused_kernel(const Params P, const __grid_constant__ Maps T) {
    extern __shared__ __align__(1024) char smem_raw[];
    constexpr uint32_t sm = 1024;
    const int tid = threadIdx.x, lane = tid & 31;
    const int cta = blockIdx.x, grp = cta >> 3, sub = cta & 7;
    const uint32_t bars = sm + OFF_BAR;
    const int row0 = (sub * HKV + grp) * SK + (SK - WIN);
    u64 pol;
    asm volatile("createpolicy.fractional.L2::evict_first.b64 %0, 1.0;" : "=l"(pol));
    if (tid == NCW * 32) {
        TS(0);
        const int n0 = cta < 108 ? 0 : 3;
#pragma unroll
        for (int i = 0; i < 6; i++) mbar_init(bars + i * 8, 1);
        asm volatile("fence.mbarrier_init.release.cluster;" ::: "memory");
#pragma unroll
        for (int i = 0; i < 3; i++) {
            mbar_expect(bars + (n0 + i) * 8, 12288);
            tma3d(sm + OFF_WM + (n0 + i) * 12288, &T.m[cta < 36 ? M_WA : cta < 108 ? M_WM : M_WQ], cta < 36 ? 16 * cta : 32 * cta,
                  i * 192, 0, bars + (n0 + i) * 8);
            TI(n0 + i);
        }
        TS(26);
    }
    if (tid == NCW * 32 + 32) {
#pragma unroll
        for (int i = 0; i < 4; i++) mbar_init(bars + (BAR_FULL + i) * 8, 1);
        asm volatile("fence.mbarrier_init.release.cluster;" ::: "memory");
#pragma unroll
        for (int t = 0; t < NK0; t++) {
            mbar_expect(bars + (BAR_FULL + t) * 8, TILE_BYTES);
            tma3d_hint(sm + OFF_RING + t * TILE_BYTES, &T.m[M_K], 0, row0 + t * 32, 0, bars + (BAR_FULL + t) * 8, pol);
            TI(6 + t);
        }
    }
    if (tid < 288 && cta < 108) {
#pragma unroll
        for (int i = 0; i < 2; i++) {
            const int row = (lane >> 3) + 4 * i, so = row * DM + (tid >> 5) * 64 + (lane & 7) * 8;
            const uint32_t d = sm + OFF_RED + (tid >> 5) * 2048 + row * 128 + (((lane & 7) ^ row) << 4);
            cp16(d, P.c + so);
            if (cta < 36) cp16(d + 1024, P.x + so);
        }
    }
    uint32_t* const g0 = P.scratch;
    const uint32_t epoch = ld1(g0 + G_EPOCH);
    const int warp = __shfl_sync(0xffffffffu, tid >> 5, 0);
    auto pace = [&](int t, int gain) {
        const int d = (int)atomicAdd(g0 + (epoch & 1) * G_SET + G_CNT, 1u) - 32 * (t - 16) - 16;
        sts32(sm + OFF_WIN, min(max((d * gain + 32) >> 6, W_MIN), W_MAX));
    };

    if (warp >= NCW) {
        const int pw = warp - NCW;
        bar_arrive(1, (NCW + 1) * 32);
        if (pw && lane < M_WQ) asm volatile("prefetch.tensormap [%0];" ::"l"(&T.m[M_WQ - lane]) : "memory");
        if (tid == NCW * 32) sts32(sm + OFF_WIN, 0);
        __syncwarp();
        bar_sync(15, NTHREADS);
        if (lane == 0) {
            if (pw == 0 && cta < 108) {
#pragma unroll 1
                for (int n = 3; n < 6; n++) {
                    mbar_expect(bars + n * 8, 12288);
                    mbar_wait(bars + (n - 3) * 8, 0);
                    tma3d(sm + OFF_WM + n * 12288, &T.m[M_WQ], 32 * cta, (n - 3) * 192, 0, bars + n * 8);
                    TI(n);
                }
            }
#pragma unroll 1
            for (int t = (2 - pw) * NK0; t < 2 * NK0 + 3 * (1 - pw); t++) {
                mbar_expect(bars + (BAR_FULL + t) * 8, TILE_BYTES);
                mbar_wait(bars + (t + (pw ? BAR_FULL - NK0 : 3 - 2 * NK0)) * 8, 0);
                tma3d_hint(sm + OFF_RING + t * TILE_BYTES, &T.m[M_K], 0, row0 + t * 32, 0, bars + (BAR_FULL + t) * 8, pol);
                TI(6 + t);
            }
            if (pw == 0) {
#pragma unroll 1
                for (int t = 2 * NK0 + 3; t < 2 * NT; t++) {
                    if (t == 14 && cta < 108) mbar_wait(bars + BAR_WMF * 8, 0);
                    if (t == 15) TS(30);
                    const int m = t - ((W_KV + (int)lds32(sm + OFF_WIN) + ((0xd8 >> (2 * t & 6)) & 3)) >> 2);
                    const uint32_t fb = bars + (BAR_FULL + (t & 15)) * 8;
                    mbar_wait(fb + (BAR_EMPTY - BAR_FULL) * 8, (~t >> 4) & 1);
                    mbar_expect(fb, TILE_BYTES);
                    mbar_wait(bars + (BAR_FULL + (m & 15)) * 8, (m >> 4) & 1);
                    tma3d_hint(sm + OFF_RING + (t & 15) * TILE_BYTES, &T.m[t >> 6], 0, row0 + (t & (NT - 1)) * 32, 0, fb, pol);
                    TI(6 + t);
                    if (t == T_CLEAR) mbar_arrive(bars + (BAR_SYNC + 1) * 8);
                }
                mbar_arrive(bars + (BAR_SYNC + 2) * 8);
                mbar_wait(bars + BAR_SYNC * 8, 0);
                auto window = [&](int b, int w) {
                    b -= max((w + (int)lds32(sm + OFF_WIN) + ((0xd8 >> (2 * b & 6)) & 3)) >> 2, 1);
                    b = min(b, BAR_GU + B_CAP);
                    mbar_wait(bars + b * 8, b < BAR_WO);
                };
#pragma unroll 1
                for (int i = 0; i < 4; i++) {
                    window(BAR_WO + i, W_WO);
                    tma3d(sm + OFF_WO + i * 8192, &T.m[M_OD], 64 * sub, grp * 256 + i * 64, P.zo, bars + (BAR_WO + i) * 8);
                    tma3d(sm + OFF_OX + i * 1024, &T.m[M_OX], 512 + 8 * sub, grp * 256 + i * 64, P.zo, bars + (BAR_WO + i) * 8);
                    TI(134 + i);
                }
                TS(28);
#pragma unroll 1
                for (int i = 0; i < 9; i++) {
                    mbar_wait(bars + (BAR_EMPTY + i) * 8, 1);
                    window(BAR_GU + i, sub < 4 ? W_GU : W_GU2);
                    tma3d(sm + OFF_GU + i * 8192, &T.m[M_GU], grp * 288 + 32 * sub, i * 64, 0, bars + (BAR_GU + i) * 8);
                    if (sub < 4) tma3d(sm + OFF_GX + i * 2048, &T.m[M_GX], grp * 288 + 256 + 8 * sub, i * 64, 0, bars + (BAR_GU + i) * 8);
                    TI(138 + i);
                }
                TS(29);
#pragma unroll 1
                for (int i = 0; i < 5; i++) {
                    const int blk = i < 4 ? (i + WD_ROT) & 3 : 4, r = min(blk * 64, 224);
                    mbar_wait(bars + (BAR_EMPTY + 9 + blk) * 8, 1);
                    window(BAR_WD + i, W_WD);
                    tma3d(sm + OFF_WD + r * 128, &T.m[M_OD], 64 * sub, grp * 288 + r, P.zo ^ 1, bars + (BAR_WD + i) * 8);
                    tma3d(sm + OFF_DX + r * 16, &T.m[M_OX], 512 + 8 * sub, grp * 288 + r, P.zo ^ 1, bars + (BAR_WD + i) * 8);
                    TI(147 + i);
                }
            } else {
#pragma unroll 1
                for (int i = BAR_WO; i < BAR_WD + 5; i++) mbar_expect(bars + i * 8, i < BAR_GU || i >= BAR_WD ? 9216 : sub < 4 ? 10240 : 8192);
                mbar_arrive(bars + BAR_SYNC * 8);
                mbar_wait(bars + (BAR_SYNC + 2) * 8, 0);
#pragma unroll 1
                for (int t = 124 + (cta & 3); t < 144; t += 4) {
                    mbar_wait(bars + (BAR_FULL - 112 + t) * 8, t < 128);
                    pace(t, GAIN_TAIL);
                }
            }
        }
        return;
    }

    if (lane == 0) {
#pragma unroll
        for (int i = 0; i < 6; i++) mbar_init(bars + (10 + warp * 6 + i) * 8, 1);
        asm volatile("fence.mbarrier_init.release.cluster;" ::: "memory");
    }
    __syncwarp();
    if (warp < 9) bar_arrive(15, NTHREADS);
    const int g = lane >> 2, t4 = lane & 3;
    uint32_t* const gs = g0 + (epoch & 1) * G_SET;

    if (warp < 9) {
        const int off_h = (cta < 36 ? dual(D_H + 2 * cta * 32) : G_M + 4 * (cta - 36) * 32) + tid;
        const int off_h2 = off_h + (cta < 36 ? 1024 : 64);
        const int off_q = dual(D_Q + g * (HQ * 64) + cta * 16) + warp * 8 + t4 * 2;
        uint32_t bf[8] = {}, xp = 0, mean2 = 0;
        float inv = 0.f;
        if (cta < 36) xp = __ldg(reinterpret_cast<const uint32_t*>(P.x) + g * (DM / 2) + 8 * cta + 4 * (warp & 1) + t4);
        if (warp < 2) {
            st2(gs + off_q, 0, 0), st2(gs + off_q + 1024, 0, 0);
            if (cta < 36) st1(gs + off_h, 0), st1(gs + off_h2, 0);
        }
        if (cta < 108) {
            asm volatile("cp.async.wait_all;" ::: "memory");
            __syncwarp();
            const uint32_t fa = sm + OFF_RED + warp * 2048 + (lane & 7) * 128 + (((lane >> 3) ^ (lane & 7)) << 4);
            ldsm4(reinterpret_cast<uint32_t(&)[4]>(bf[0]), fa);
            ldsm4(reinterpret_cast<uint32_t(&)[4]>(bf[4]), fa ^ 64);
            if (cta < 36) {
                uint32_t xv[8];
                ldsm4(reinterpret_cast<uint32_t(&)[4]>(xv[0]), fa + 1024);
                ldsm4(reinterpret_cast<uint32_t(&)[4]>(xv[4]), (fa ^ 64) + 1024);
                ln_partial(xv, sm + OFF_ST + g * 80 + warp * 8, t4 == 0);
            }
#pragma unroll
            for (int i = 0; i < 8; i++) bf[i] = silu2(bf[i]);
        }
        if (warp == 0) TSL(18);
        bar_sync(1, (NCW + 1) * 32);
        if (cta < 36 && warp < 2) ln_combine(sm + OFF_ST + g * 80, mean2, inv);
        const int r = warp * 64 + (lane >> 4) * 8 + (lane & 7), hi8 = (lane >> 3) & 1, box = warp / 3;
#pragma unroll 1
        for (int pass = cta < 108 ? 0 : 1; pass < 2; pass++) {
            const bool pa = pass == 0 && cta < 36;
            const uint32_t ab = sm + OFF_WM + pass * 36864 +
                                (pa ? (box + hi8) * 6144 + r * 32 + ((lane & 4) << 2) : r * 64 + (((2 * hi8) ^ ((r >> 1) & 3)) << 4));
            const uint32_t as = pa ? 512 : 1024, red = sm + OFF_RED + pass * 9216;
            mbar_wait(bars + (pass * 3 + box) * 8, 0);
            if (warp == 8) TSL(pass ? 31 : 19);
            uint32_t a[4][2][4];
#pragma unroll
            for (int i = 0; i < 4; i++) {
                ldsm4t(a[i][0], ab + i * as);
                ldsm4t(a[i][1], (ab ^ 16) + i * as);
            }
            if (pass) {
                bar_sync(8, NCW * 32);
#pragma unroll
                for (int i = 0; i < 8; i++) bf[i] = 0;
                get<8, 1>(gs + near(D_H + warp * 256, lds32(sm + OFF_WIN + 4)) + lane, 32, bf);
                if (warp == 0) TSL(3);
            }
            float acc[2][4] = {};
#pragma unroll
            for (int i = 0; i < 4; i++)
#pragma unroll
                for (int m = 0; m < 2; m++) mma(acc[m], a[i][m][0], a[i][m][1], a[i][m][2], a[i][m][3], bf[2 * i], bf[2 * i + 1]);
            sts128f(red + tid * 16, acc[0]);
            sts128f(red + 4608 + tid * 16, acc[1]);
            bar_sync(3, 288);
            if (warp < 2) {
                float c[4] = {};
                sum_frags<9>(c, red + warp * 4608 + lane * 16, 512);
                uint32_t lo = movm(pack2(c[0], c[1])), hi = movm(pack2(c[2], c[3]));
                if (pass) {
                    put2d(gs + off_q, lo, hi);
                    if (warp == 0) TSL(4);
                } else {
                    const uint32_t hi1 = badd2(hi, ONE2);
                    if (pa) hi = lo = modulate2(xp, mean2, inv, lo, hi1);
                    if (cta >= 72 && cta < 90) lo = badd2(lo, ONE2), hi = hi1;
                    st1(gs + off_h, nz(lo));
                    st1(gs + off_h2, nz(hi));
                    if (warp == 0 && pa) TSL(2);
                }
            } else if (tid == 64 && pass == 0) {
                mbar_arrive(bars + BAR_WMF * 8);
            }
        }
    } else {
        if ((uint32_t)__cvta_generic_to_shared(smem_raw) != sm) __trap();
        uint32_t* const ping = g0 + dual(D_PING) + cta * 8;
        if (lane < 16) st1(ping + (lane >> 3) * 1024 + (lane & 7), 0);
        bar_sync(15, NTHREADS);
        uint32_t best[2] = {~0u, ~0u}, v = 0;
#pragma unroll 1
        for (int part = 0; part < 2; part++) {
            if (lane == 0) {
#pragma unroll 1
                for (int r = part ? NPING1 : NPING0; r > 0; r--) {
#pragma unroll
                    for (int k = 0; k < 2; k++) {
                        const uint32_t t0 = clock32(v);
                        v = atomicExch(ping + k * 1024, t0);
                        best[k] = min(best[k], clock32(v) - t0);
                    }
                }
                sts32(sm + OFF_WIN + 4 + 4 * part, ((best[1] < best[0]) ^ __popc(D_PING & 0x16400)) & 1);
            }
            __syncwarp();
            if (part) break;
            TSL(20);
            bar_arrive(8, NCW * 32);
            mbar_wait(bars + 5 * 8, 0);
            uint32_t a[4] = {};
            get<1, 4>(gs + near(D_Q + (sub * HQ + 2 * grp) * 64, lds32(sm + OFF_WIN + 4)) + lane * 4, 0, a);
            sts128(sm + OFF_QS + lane * 16, a[0], a[1], a[2], a[3]);
            __syncwarp();
            TSL(5);
            bar_arrive(4, 288);
        }
#pragma unroll
        for (int i = lane; i < 72; i += 32) cp16(sm + OFF_WR + i * 16, P.wr + i * 8);
        asm volatile("cp.async.wait_all;" ::: "memory");
        __syncwarp();
        bar_arrive(2, NCW * 32);
        if (cta == 0 && lane == 0) st1(g0 + (~epoch & 1) * G_SET + G_CNT, 0);
        mbar_wait(bars + (BAR_SYNC + 1) * 8, 0);
#pragma unroll 1
        for (int c = 0; c < 4; c++) {
            uint32_t* const pg = g0 + (c >> 1) * G_SET + (c & 1) * 1024;
            zero4(pg + dual(D_O + cta * 128) + lane * 4);
            zero4(pg + dual(D_ACT + (grp * 36 + 4 * sub) * 32) + lane * 4);
            if (lane < 8 ? sub < 4 : lane < 16 && cta < 72)
                zero4(pg + dual(lane < 8 ? D_ACT + (grp * 36 + 32 + sub) * 32 : D_X1 + cta * 32) + (lane & 7) * 4);
        }
#pragma unroll 1
        for (int u = 0; u < 9; u++) zero4(g0 + dual(d_part(u < 8 ? 8 * sub + u : 64 + sub)) + (lane >> 4) * 1024 + grp * 64 + (lane & 15) * 4);
        __syncwarp();
        bar_arrive(5, NCW * 32);
        {
            uint32_t* const nx = g0 + (~epoch & 1) * G_SET;
            uint32_t* const q = nx + dual(D_Q + g * (HQ * 64) + cta * 16) + t4 * 4;
            zero4(q), zero4(q + 1024);
            if (cta < 108) zero4(nx + (cta < 36 ? dual(D_H + 2 * cta * 32) + (lane >> 4) * (1024 - 64) : G_M + 4 * (cta - 36) * 32) + lane * 4);
        }
        return;
    }

    const uint32_t tile = sm + OFF_RING + warp * TILE_BYTES;
    const uint32_t fullb = bars + (BAR_FULL + warp) * 8;
    const uint32_t pw = sm + OFF_P + warp * (2 * P_PITCH);
    const bool pacer = (tid & 127) == (cta & 3) * 32;
    if (warp < 8) {
        {
            uint32_t q0[8], q1[8];
            bar_sync(4, 288);
#pragma unroll
            for (int i = 0; i < 8; i++) {
                const float2 v = lds64f(sm + OFF_QS + (g & 1) * 256 + i * 32 + t4 * 8);
                q0[i] = __float_as_uint(v.x), q1[i] = __float_as_uint(v.y);
            }
            uint32_t sp = pw + (t4 & 1) * P_PITCH + ((t4 >> 1) * 8 + g) * 2;
#pragma unroll 1
            for (int it = 0; it < 8; it++, sp += 64) {
                const uint32_t ab = tile + (it & 1) * (8 * TILE_BYTES) + (lane & 15) * 128 + (((lane >> 4) ^ (lane & 7)) << 4);
                mbar_wait(fullb + (it & 1) * 64, (it >> 1) & 1);
                float acc[2][2][4] = {};
#pragma unroll
                for (int ks = 0; ks < 8; ks++)
#pragma unroll
                    for (int m = 0; m < 2; m++) {
                        uint32_t a[4];
                        ldsm4(a, (ab ^ ((ks & 3) << 5)) + (ks >> 2) * 4096 + m * 2048);
                        mma(acc[m][ks & 1], a[0], a[1], a[2], a[3], (ks & 1) ? q1[ks - 1] : q0[ks], (ks & 1) ? q1[ks] : q0[ks + 1]);
                    }
                __syncwarp();
                if (lane == 0) mbar_arrive(fullb + (it & 1) * 64 + (BAR_EMPTY - BAR_FULL) * 8);
#pragma unroll
                for (int m = 0; m < 2; m++) {
                    const float s = sel4(acc[m][0], t4) + sel4(acc[m][1], t4);
                    sts16(sp + m * 32, (uint16_t)pack2(rbf(s) * 0.08838834764831845f, 0.f));
                }
                if (pacer && it >= 2) pace(it * 8 + warp, GAIN_KV);
                __syncwarp();
            }
        }
        __syncwarp();
        if (warp == 7) TSL(6);
        const uint32_t pa = pw + (lane >> 4) * P_PITCH + (lane & 15) * 32;
        const uint32_t sa = sm + OFF_SM + (lane >> 4) * 64;
        const uint4 v0 = lds128(pa), v1 = lds128(pa + 16);
        const uint32_t sv[8] = {v0.x, v0.y, v0.z, v0.w, v1.x, v1.y, v1.z, v1.w};
        float e[16];
        float m = -INFINITY;
#pragma unroll
        for (int i = 0; i < 8; i++) {
            e[2 * i] = blo(sv[i]);
            e[2 * i + 1] = bhi(sv[i]);
            m = fmaxf(m, fmaxf(e[2 * i], e[2 * i + 1]));
        }
#pragma unroll
        for (int o = 8; o; o >>= 1) m = fmaxf(m, __shfl_xor_sync(0xffffffffu, m, o));
        float l = 0.f;
#pragma unroll
        for (int i = 0; i < 16; i++) {
            e[i] = ex2((e[i] - m) * LOG2E);
            l += e[i];
        }
#pragma unroll
        for (int o = 8; o; o >>= 1) l += __shfl_xor_sync(0xffffffffu, l, o);
        if ((lane & 15) == 0) sts64(sa + warp * 8, __float_as_uint(m), __float_as_uint(l));
        bar_sync(2, NCW * 32);
        const float2 v = lds64f(sa + (lane & 7) * 8);
        float M = v.x;
#pragma unroll
        for (int o = 4; o; o >>= 1) M = fmaxf(M, __shfl_xor_sync(0xffffffffu, M, o));
        float L = v.y * ex2((v.x - M) * LOG2E);
#pragma unroll
        for (int o = 4; o; o >>= 1) L += __shfl_xor_sync(0xffffffffu, L, o);
        const float sc = ex2((m - M) * LOG2E) * rcp(L);
        sts128(pa, pack2(e[0] * sc, e[1] * sc), pack2(e[2] * sc, e[3] * sc), pack2(e[4] * sc, e[5] * sc), pack2(e[6] * sc, e[7] * sc));
        sts128(pa + 16, pack2(e[8] * sc, e[9] * sc), pack2(e[10] * sc, e[11] * sc), pack2(e[12] * sc, e[13] * sc), pack2(e[14] * sc, e[15] * sc));
        __syncwarp();
    } else {
        bar_sync(2, NCW * 32);
    }

    const bool reducer = cta < 72 && warp < 4;
    const int rbat = 2 * t4 + (g & 1);
    uint32_t sh[8] = {}, op[8] = {}, rx = 0, rg[2] = {};
    {
        const uint32_t* const src_m = gs + G_M + (72 + warp * 8) * 32 + lane;
        fetch<8, 1>(src_m + 72 * 32, 32, op);
        if (reducer) {
            rx = __ldg(reinterpret_cast<const uint32_t*>(P.x) + rbat * (DM / 2) + 4 * cta + warp);
            get<2, 1>(gs + G_M + cta * 32 + rbat * 4 + warp, 216 * 32, rg);
        }
        get<8, 1>(src_m, 32, sh);
        get<8, 1>(src_m + 72 * 32, 32, op);
    }
    const int side = lds32(sm + OFF_WIN + 8), set = (epoch & 1) * G_SET, rr = (lane >> 4) * 8 + (lane & 7);
    const uint32_t dst_o = pin(4 * (set + dual(D_O + cta * 128) + (tid & 0x70) + (tid & 3) * 4 + ((tid >> 2) & 3)));
    const uint32_t src_o = pin(4 * (set + near(D_O + grp * 1024, side) + g * 128 + warp * 16 + t4 * 4));
    const uint32_t dst_p = pin(4 * (dual(d_part(warp < 8 ? 8 * sub + warp : 64 + sub)) + grp * 64 + lane * 2));
    const uint32_t src_p = pin(4 * (near(d_part(cta), side) + (lane >> 3) * 256 + 16 * warp + (lane & 7) * 2));
    const uint32_t dst_x = pin(4 * (set + dual(D_X1 + cta * 32) + (lane >> 3) * 1024 + warp * 8 + (lane & 7)));
    const uint32_t src_x = pin(4 * (set + near(D_X1 + warp * 256, side) + t4 * 8 + (g & 1) * 4 + (g >> 1)));
    const uint32_t dst_a = pin(4 * (set + dual(D_ACT + (grp * 36 + (warp < 4 ? 4 * sub + warp : 32 + sub)) * 32) + lane));
    const uint32_t src_a = pin(4 * (set + near(D_ACT + (grp * 36 + 4 * warp) * 32, side) + lane));
    const uint32_t dst_out = pin(4 * (rbat * (DM / 2) + 4 * cta + warp));
    const uint32_t rowoff = pin((warp * 32 + rr) * 128 + ((((lane >> 3) & 1) ^ (lane & 7)) << 4));
    const uint32_t reds = pin((tid * 8) | (warp * 2304 + lane * 8) << 16);
    const uint32_t ored = pin((warp * 1088 + (t4 & 1) * 576 + ((t4 >> 1) * 8 + g) * 4) | ((tid >> 6) * 64 + tid * 8) << 16);

    if (warp < 8) {
        float acc[8][4] = {};
        uint32_t pp = pw + (lane & 1) * P_PITCH + (lane >> 3) * 16;
#pragma unroll 1
        for (int it = 0; it < 8; it++, pp += 64) {
            const uint32_t ab = tile + (it & 1) * (8 * TILE_BYTES) + ((lane & 7) + (lane >> 4) * 8) * 128 + ((((lane >> 3) & 1) ^ (lane & 7)) << 4);
            uint32_t pb[4];
            ldsm4(pb, pp);
            mbar_wait(fullb + (it & 1) * 64, (it >> 1) & 1);
#pragma unroll
            for (int ks = 0; ks < 2; ks++)
#pragma unroll
                for (int m = 0; m < 8; m++) {
                    uint32_t a[4];
                    ldsm4t(a, (ab ^ ((m & 3) << 5)) + (m >> 2) * 4096 + ks * 2048);
                    mma(acc[m], a[0], a[1], a[2], a[3], pb[2 * ks], pb[2 * ks + 1]);
                }
            __syncwarp();
            if (lane == 0) mbar_arrive(fullb + (it & 1) * 64 + (BAR_EMPTY - BAR_FULL) * 8);
            if (pacer && it * 8 + warp < NT - 4) pace(NT + it * 8 + warp, GAIN_KV);
            __syncwarp();
        }
        if (warp == 7) TSL(7);
        const uint32_t ra = sm + OFF_ORED + (ored & 0xffff);
#pragma unroll
        for (int m = 0; m < 8; m++) sts32(ra + m * 64, __float_as_uint(sel4(acc[m], t4)));
    }
    bar_sync(5, NCW * 32);
    if (warp < 4) {
        float s[2][2] = {};
#pragma unroll
        for (int w = 0; w < 8; w++) {
            const float2 v = lds64f(sm + OFF_ORED + w * 1088 + (ored >> 16));
            s[w & 1][0] += v.x;
            s[w & 1][1] += v.y;
        }
        put1d(at(g0, dst_o), pack2(s[0][0] + s[1][0], s[0][1] + s[1][1]));
        if (warp == 0) TSL(8);
    }

    project<0>(sm, at(g0, src_o), at(g0, dst_p), rowoff, reds, warp, lane);
    if (warp == 0) TSL(9);
    if (reducer) {
        rx = badd2(rx, bmul2(rg[0], reduce16<0>(at(g0, src_p), lane)));
        if (lane < 16) st1(at(g0, dst_x), nz(rx));
        if (warp == 0) TSL(10);
    }

    const uint32_t gbar = bars + (BAR_GU + warp) * 8;
    const int pl = ((lane >> 3) & 1) ^ P.zg;
    const uint32_t ab = sm + OFF_GU + warp * 8192 + pl * 4096 + rr * 64 + ((lane & 6) << 3);
    const uint32_t ax = sm + OFF_GX + warp * 2048 + pl * 1024 + rr * 16;
    uint32_t a[20][4] = {}, h[8] = {};
    auto load_gu = [&]() {
#pragma unroll
        for (int i = 0; i < 20; i++) ldsm4t(a[i], i % 5 < 4 ? (ab ^ ((i % 5) << 4)) + (i / 5) * 1024 : ax + (i / 5) * 256);
    };
    bool gpre = false;
    {
        int it = 0;
        do {
            if (!gpre && __all_sync(0xffffffffu, mbar_test(gbar, 0))) gpre = true, load_gu();
            fetch<8, 1>(at(g0, src_x), 32, h);
        } while (missing(h) & (++it < SPIN_LIMIT));
    }
    if (warp == 0) TSL(11);
    ln_partial(h, sm + OFF_ST + g * 80 + warp * 8, t4 == 0);
    bar_sync(3, 288);
    {
        uint32_t mean2;
        float inv;
        ln_combine(sm + OFF_ST + g * 80, mean2, inv);
#pragma unroll
        for (int i = 0; i < 8; i++) h[i] = modulate2(h[i], mean2, inv, sh[i], op[i]);
    }
    if (warp == 0) TSL(12);
    if (!gpre) {
        mbar_wait(gbar, 0);
        load_gu();
    }
    if (warp == 8) TSL(17);
    {
        float acc[5][4] = {};
#pragma unroll
        for (int i = 0; i < 20; i++) mma(acc[i % 5], a[i][0], a[i][1], a[i][2], a[i][3], h[2 * (i / 5)], h[2 * (i / 5) + 1]);
#pragma unroll
        for (int m = 0; m < 5; m++) sts128f(sm + OFF_RED + m * 4608 + 2 * (reds & 0xffff), acc[m]);
    }
    bar_sync(3, 288);
    if (warp < 5) {
        float c[4] = {};
        sum_frags<9>(c, sm + OFF_RED + 2 * (reds >> 16), 512);
        const uint32_t w = movm(bmul2(silu2(pack2(c[0], c[1])), pack2(c[2], c[3])));
        if (warp < 4 || sub < 4) put1d(at(g0, dst_a), w);
        if (warp == 1) TSL(13);
    }
    if (cta < 72) {
        float r = 0.f;
#pragma unroll
        for (int i = 0; i < 8; i++) {
            const uint32_t wr = lds32(sm + OFF_WR + (warp * 32 + i * 4 + t4) * 4);
            r = fmaf(blo(h[i]), blo(wr), fmaf(bhi(h[i]), bhi(wr), r));
            if (warp * 8 + i == cta) sts32(sm + OFF_HU + lane * 4, h[i]);
        }
        r = quad_sum(r);
        if (t4 == 0) sts32(sm + OFF_RT + g * 48 + warp * 4, __float_as_uint(r));
    }

    project<1>(sm, at(g0, src_a), at(g0, dst_p), rowoff, reds, warp, lane);
    if (warp == 0) TSL(14);
    if (reducer) {
        const uint4 r0 = lds128(sm + OFF_RT + rbat * 48), r1 = lds128(sm + OFF_RT + rbat * 48 + 16);
        float r = __uint_as_float(lds32(sm + OFF_RT + rbat * 48 + 32));
        r += ((__uint_as_float(r0.x) + __uint_as_float(r0.y)) + (__uint_as_float(r0.z) + __uint_as_float(r0.w))) +
             ((__uint_as_float(r1.x) + __uint_as_float(r1.y)) + (__uint_as_float(r1.z) + __uint_as_float(r1.w)));
        r = sigmoid_f(rbf(r));
        const uint32_t rh = lds32(sm + OFF_HU + (rbat * 4 + warp) * 4);
        const uint32_t y = badd2(rh, bmul2(reduce16<1>(at(g0, src_p), lane), pack2(r, r)));
        if (lane < 8) *at(reinterpret_cast<uint32_t*>(P.out), dst_out) = badd2(rx, bmul2(rg[1], y));
        if (cta == 0 && tid == 0) g0[G_EPOCH] = epoch + 1;
        if (warp == 0) TSL(15);
    }
}

typedef CUresult (*EncodeFn)(CUtensorMap*, CUtensorMapDataType, cuuint32_t, void*, const cuuint64_t*, const cuuint64_t*,
                             const cuuint32_t*, const cuuint32_t*, CUtensorMapInterleave, CUtensorMapSwizzle,
                             CUtensorMapL2promotion, CUtensorMapFloatOOBfill);

void make_map(EncodeFn enc, CUtensorMap* m, void* p, int cols, int rows, int pitch, int bc, int br, int bp, int planes, size_t pstride,
              CUtensorMapSwizzle sw, int promo) {
    cuuint64_t dims[3] = {(cuuint64_t)cols, (cuuint64_t)rows, (cuuint64_t)planes};
    cuuint64_t strides[2] = {(cuuint64_t)pitch * 2, (cuuint64_t)pstride};
    cuuint32_t box[3] = {(cuuint32_t)bc, (cuuint32_t)br, (cuuint32_t)bp};
    cuuint32_t es[3] = {1, 1, 1};
    enc(m, CU_TENSOR_MAP_DATA_TYPE_BFLOAT16, 3, p, dims, strides, box, es, CU_TENSOR_MAP_INTERLEAVE_NONE, sw,
        (CUtensorMapL2promotion)promo, CU_TENSOR_MAP_FLOAT_OOB_FILL_NONE);
}

}

extern "C" void kernel_launch(void* const* d_in, const int* in_sizes, int n_in, void* d_out, int out_size) {
    static EncodeFn enc = nullptr;
    static uint32_t* scratch = nullptr;
    if (!enc) {
        void* fn = nullptr;
        cudaDriverEntryPointQueryResult st;
        cudaGetDriverEntryPoint("cuTensorMapEncodeTiled", &fn, cudaEnableDefault, &st);
        enc = (EncodeFn)fn;
        cudaGetSymbolAddress(&fn, g_scratch);
        scratch = (uint32_t*)(((uintptr_t)fn + 8 * G_SET - 1) & ~(uintptr_t)(8 * G_SET - 1));
        cudaFuncSetAttribute(fused_kernel, cudaFuncAttributeMaxDynamicSharedMemorySize, SMEM_BYTES);
    }
    Params P;
    Maps T;
    const CUtensorMapSwizzle none = CU_TENSOR_MAP_SWIZZLE_NONE;
    make_map(enc, &T.m[M_K], d_in[1], 64, NB * HKV * SK, DH, 64, 32, 2, 2, 128, CU_TENSOR_MAP_SWIZZLE_128B, PROMO_KV);
    make_map(enc, &T.m[M_V], d_in[2], 64, NB * HKV * SK, DH, 64, 32, 2, 2, 128, CU_TENSOR_MAP_SWIZZLE_128B, PROMO_KV);
    make_map(enc, &T.m[M_WQ], d_in[3], HQ * DH, DM, HQ * DH, 32, 192, 1, 1, 16, CU_TENSOR_MAP_SWIZZLE_64B, PROMO_W);
    make_map(enc, &T.m[M_WM], d_in[11], 6 * DM, DM, 6 * DM, 32, 192, 1, 1, 16, CU_TENSOR_MAP_SWIZZLE_64B, PROMO_W);
    make_map(enc, &T.m[M_WA], d_in[11], DM, DM, 6 * DM, 16, 192, 2, 2, DM * 2, CU_TENSOR_MAP_SWIZZLE_32B, PROMO_W);
    char *wg = (char*)d_in[7], *wu = (char*)d_in[8], *wo = (char*)d_in[4], *wd = (char*)d_in[9];
    P.zg = wg > wu;
    P.zo = wo > wd;
    const size_t sg = P.zg ? wg - wu : wu - wg, so = P.zo ? wo - wd : wd - wo;
    make_map(enc, &T.m[M_GU], P.zg ? wu : wg, FF, DM, FF, 32, 64, 2, 2, sg, CU_TENSOR_MAP_SWIZZLE_64B, PROMO_GU);
    make_map(enc, &T.m[M_GX], P.zg ? wu : wg, FF, DM, FF, 8, 64, 2, 2, sg, none, PROMO_GX);
    make_map(enc, &T.m[M_OD], P.zo ? wd : wo, DM, FF, DM, 64, 64, 1, 2, so, CU_TENSOR_MAP_SWIZZLE_128B, PROMO_W);
    make_map(enc, &T.m[M_OX], P.zo ? wd : wo, DM, FF, DM, 8, 64, 1, 2, so, none, PROMO_OX);
    P.x = (const __nv_bfloat16*)d_in[0];
    P.wr = (const __nv_bfloat16*)d_in[6];
    P.c = (const __nv_bfloat16*)d_in[10];
    P.out = (__nv_bfloat16*)d_out;
    P.scratch = scratch;
    fused_kernel<<<NCTA, NTHREADS, SMEM_BYTES>>>(P, T);
}
```

```cpp
#include <cuda_runtime.h>
#include <cuda_bf16.h>
#include <cuda.h>
#include <stdint.h>

typedef unsigned long long u64;

#define W_KV 20
#define W_WO 19
#define W_GU 19
#define W_GU2 W_GU
#define W_WD 13
#define W_MIN -8
#define W_MAX 8
#define GAIN_KV 2
#define GAIN_TAIL 3
#define NK0 2
#define T_CLEAR 116
#define B_CAP 8
#define WD_ROT 3
#define NPING0 4
#define NPING1 16
#define PROMO_W CU_TENSOR_MAP_L2_PROMOTION_L2_128B
#define PROMO_GX 2
#define PROMO_OX 2
#define PROMO_GU 2
#define PROMO_KV CU_TENSOR_MAP_L2_PROMOTION_L2_256B

namespace {

constexpr int NB = 8, DM = 576, HQ = 32, HKV = 16, SK = 8192, WIN = 2048, DH = 128, FF = 4608;
constexpr int NCTA = 128;
constexpr int NCW = 10;
constexpr int NTHREADS = (NCW + 2) * 32;
constexpr int TILE_BYTES = 8192, NSLOT = 16, NT = 64;
constexpr int SPIN_LIMIT = 1 << 22;

constexpr int OFF_RING = 0;
constexpr int OFF_WM = 121856;
constexpr int OFF_WQ = OFF_WM + 36864;
constexpr int OFF_GU = 0;
constexpr int OFF_WD = 73728;
constexpr int OFF_OX = 131072;
constexpr int OFF_DX = OFF_OX + 4096;
constexpr int OFF_GX = OFF_DX + 4608;
constexpr int OFF_WO = OFF_WQ;
constexpr int OFF_P = OFF_WQ + 36864;
constexpr int P_PITCH = 528;
constexpr int OFF_RED = OFF_P + 16 * P_PITCH;
constexpr int OFF_ORED = OFF_RED + 5 * 4608 - 8704;
constexpr int OFF_ST = OFF_RED + 5 * 4608;
constexpr int OFF_SM = OFF_ST + 640;
constexpr int OFF_RT = OFF_SM + 128;
constexpr int OFF_HU = OFF_RT + 384;
constexpr int OFF_QS = OFF_HU + 128;
constexpr int OFF_WR = OFF_QS + 512;
constexpr int OFF_WIN = OFF_WR + 1152;
constexpr int OFF_BAR = OFF_WIN + 16;
constexpr int BAR_FULL = 6, BAR_WO = 22, BAR_GU = 26, BAR_WD = 35, BAR_EMPTY = 40, BAR_SYNC = 56, BAR_WMF = 59, NBAR = 70;
constexpr int SMEM_BYTES = OFF_BAR + NBAR * 8;

constexpr int D_X1 = 0;
constexpr int D_O = 3072;
constexpr int D_ACT = D_O + 512 * 32;
constexpr int D_H = D_ACT + 576 * 32;
constexpr int D_Q = D_H + 3072;
constexpr int G_M = 2 * (D_Q + NB * HQ * 64);
constexpr int G_CNT = G_M + 288 * 32;
constexpr int G_SET = 1 << 18;
__device__ __forceinline__ int d_part(int unit) { return (64 + unit + (unit & 64)) * 1024; }
constexpr int D_PING = 200 * 1024;
constexpr int G_EPOCH = 201 * 2048;
static_assert(G_CNT < 64 * 2048, "scratch layout");
__device__ uint32_t g_scratch[4 * G_SET];
__device__ __forceinline__ int dual(int w) { return w + (w & ~1023); }
__device__ __forceinline__ int near(int w, int side) { return dual(w) + (((__popc(w & 0x16400) ^ side) & 1) << 10); }

#define TI(i)
#define TS(i)
#define TSL(i)

enum { M_K, M_V, M_GU, M_GX, M_OD, M_OX, M_WQ, M_WM, M_WA, NMAP };
struct Params {
    const __nv_bfloat16 *c, *x, *wr;
    __nv_bfloat16* out;
    uint32_t* scratch;
    int zg, zo;
};
struct Maps {
    CUtensorMap m[NMAP];
};

__device__ __forceinline__ void mbar_init(uint32_t bar, int cnt) {
    asm volatile("mbarrier.init.shared::cta.b64 [%0], %1;" ::"r"(bar), "r"(cnt));
}
__device__ __forceinline__ void mbar_expect(uint32_t bar, uint32_t bytes) {
    asm volatile("mbarrier.arrive.expect_tx.shared::cta.b64 _, [%0], %1;" ::"r"(bar), "r"(bytes) : "memory");
}
__device__ __forceinline__ void mbar_arrive(uint32_t bar) {
    asm volatile("mbarrier.arrive.shared::cta.b64 _, [%0];" ::"r"(bar) : "memory");
}
__device__ __forceinline__ void mbar_wait(uint32_t bar, uint32_t parity) {
    asm volatile("{\n.reg .pred p;\n.reg .u32 c;\n"
                 "mbarrier.try_wait.parity.shared::cta.b64 p, [%0], %1;\n@p bra DONE;\nmov.u32 c, %2;\n"
                 "AGAIN:\nmbarrier.try_wait.parity.shared::cta.b64 p, [%0], %1;\nsub.u32 c, c, 1;\n"
                 "setp.eq.or.u32 p, c, 0, p;\n@!p bra AGAIN;\nDONE:\n}"
                 ::"r"(bar), "r"(parity), "n"(SPIN_LIMIT) : "memory");
}
__device__ __forceinline__ bool mbar_test(uint32_t bar, uint32_t parity) {
    uint32_t ok;
    asm volatile("{\n.reg .pred p;\nmbarrier.test_wait.parity.shared::cta.b64 p, [%1], %2;\nselp.u32 %0, 1, 0, p;\n}"
                 : "=r"(ok) : "r"(bar), "r"(parity) : "memory");
    return ok;
}
__device__ __forceinline__ void mbar_wait_lanes(uint32_t bar) {
    mbar_wait(bar, 0);
    __syncwarp();
}
__device__ __forceinline__ void tma3d_hint(uint32_t dst, const CUtensorMap* m, int x, int y, int z, uint32_t bar, u64 pol) {
    asm volatile("cp.async.bulk.tensor.3d.shared::cluster.global.mbarrier::complete_tx::bytes.L2::cache_hint"
                 " [%0], [%1, {%2, %3, %4}], [%5], %6;"
                 ::"r"(dst), "l"(m), "r"(x), "r"(y), "r"(z), "r"(bar), "l"(pol) : "memory");
}
__device__ __forceinline__ void tma3d(uint32_t dst, const CUtensorMap* m, int x, int y, int z, uint32_t bar) {
    asm volatile("cp.async.bulk.tensor.3d.shared::cluster.global.mbarrier::complete_tx::bytes [%0], [%1, {%2, %3, %4}], [%5];"
                 ::"r"(dst), "l"(m), "r"(x), "r"(y), "r"(z), "r"(bar) : "memory");
}
__device__ __forceinline__ void bar_sync(int id, int n) { asm volatile("bar.sync %0, %1;" ::"r"(id), "r"(n) : "memory"); }
__device__ __forceinline__ void bar_arrive(int id, int n) { asm volatile("bar.arrive %0, %1;" ::"r"(id), "r"(n) : "memory"); }
__device__ __forceinline__ void ldsm4(uint32_t (&r)[4], uint32_t a) {
    asm volatile("ldmatrix.sync.aligned.m8n8.x4.shared.b16 {%0,%1,%2,%3}, [%4];"
                 : "=r"(r[0]), "=r"(r[1]), "=r"(r[2]), "=r"(r[3]) : "r"(a) : "memory");
}
__device__ __forceinline__ void ldsm4t(uint32_t (&r)[4], uint32_t a) {
    asm volatile("ldmatrix.sync.aligned.m8n8.x4.trans.shared.b16 {%0,%1,%2,%3}, [%4];"
                 : "=r"(r[0]), "=r"(r[1]), "=r"(r[2]), "=r"(r[3]) : "r"(a) : "memory");
}
__device__ __forceinline__ void mma(float (&c)[4], uint32_t a0, uint32_t a1, uint32_t a2, uint32_t a3, uint32_t b0, uint32_t b1) {
    asm volatile("mma.sync.aligned.m16n8k16.row.col.f32.bf16.bf16.f32 {%0,%1,%2,%3}, {%4,%5,%6,%7}, {%8,%9}, {%0,%1,%2,%3};"
                 : "+f"(c[0]), "+f"(c[1]), "+f"(c[2]), "+f"(c[3])
                 : "r"(a0), "r"(a1), "r"(a2), "r"(a3), "r"(b0), "r"(b1));
}
__device__ __forceinline__ uint32_t movm(uint32_t a) {
    uint32_t d;
    asm volatile("movmatrix.sync.aligned.m8n8.trans.b16 %0, %1;" : "=r"(d) : "r"(a));
    return d;
}
__device__ __forceinline__ uint32_t lds32(uint32_t a) { uint32_t v; asm volatile("ld.shared.b32 %0, [%1];" : "=r"(v) : "r"(a) : "memory"); return v; }
__device__ __forceinline__ float2 lds64f(uint32_t a) { float2 v; asm volatile("ld.shared.v2.f32 {%0,%1}, [%2];" : "=f"(v.x), "=f"(v.y) : "r"(a) : "memory"); return v; }
__device__ __forceinline__ uint4 lds128(uint32_t a) { uint4 v; asm volatile("ld.shared.v4.b32 {%0,%1,%2,%3}, [%4];" : "=r"(v.x), "=r"(v.y), "=r"(v.z), "=r"(v.w) : "r"(a) : "memory"); return v; }
__device__ __forceinline__ void sts32(uint32_t a, uint32_t v) { asm volatile("st.shared.b32 [%0], %1;" ::"r"(a), "r"(v) : "memory"); }
__device__ __forceinline__ void sts16(uint32_t a, uint16_t v) { asm volatile("st.shared.b16 [%0], %1;" ::"r"(a), "h"(v) : "memory"); }
__device__ __forceinline__ void sts64(uint32_t a, uint32_t x, uint32_t y) { asm volatile("st.shared.v2.b32 [%0], {%1,%2};" ::"r"(a), "r"(x), "r"(y) : "memory"); }
__device__ __forceinline__ void sts128(uint32_t a, uint32_t x, uint32_t y, uint32_t z, uint32_t w) {
    asm volatile("st.shared.v4.b32 [%0], {%1,%2,%3,%4};" ::"r"(a), "r"(x), "r"(y), "r"(z), "r"(w) : "memory");
}
__device__ __forceinline__ void sts128f(uint32_t a, const float (&c)[4]) {
    sts128(a, __float_as_uint(c[0]), __float_as_uint(c[1]), __float_as_uint(c[2]), __float_as_uint(c[3]));
}

__device__ __forceinline__ float sel4(const float (&c)[4], int t) { return (t & 2) ? ((t & 1) ? c[3] : c[2]) : ((t & 1) ? c[1] : c[0]); }

template <int LUT>
__device__ __forceinline__ uint32_t lop3(uint32_t a, uint32_t b, uint32_t c) {
    uint32_t d;
    asm("lop3.b32 %0, %1, %2, %3, %4;" : "=r"(d) : "r"(a), "r"(b), "r"(c), "n"(LUT));
    return d;
}
__device__ __forceinline__ uint32_t pin(uint32_t v) { return __shfl_xor_sync(0xffffffffu, v, 0); }
template <typename T>
__device__ __forceinline__ T* at(T* base, uint32_t bytes) { return (T*)((const char*)base + bytes); }

__device__ __forceinline__ uint32_t clock32(uint32_t dep) {
    uint32_t t;
    asm volatile("{\n.reg .pred p;\nsetp.eq.u32 p, %1, 0x9e3779b9;\n@p nanosleep.u32 1;\nmov.u32 %0, %clock;\n}" : "=r"(t) : "r"(dep) : "memory");
    return t;
}

__device__ __forceinline__ uint32_t nz(uint32_t v) { return v ? v : 0x80000000u; }
__device__ __forceinline__ void st1(uint32_t* p, uint32_t a) { asm volatile("st.relaxed.gpu.global.b32 [%0], %1;" ::"l"(p), "r"(a) : "memory"); }
__device__ __forceinline__ void st2(uint32_t* p, uint32_t a, uint32_t b) {
    asm volatile("st.relaxed.gpu.global.v2.b32 [%0], {%1,%2};" ::"l"(p), "r"(a), "r"(b) : "memory");
}
__device__ __forceinline__ void zero4(uint32_t* p) { asm volatile("st.relaxed.gpu.global.v4.b32 [%0], {%1,%1,%1,%1};" ::"l"(p), "r"(0) : "memory"); }
__device__ __forceinline__ void put1d(uint32_t* p, uint32_t a) { a = nz(a), st1(p, a), st1(p + 1024, a); }
__device__ __forceinline__ void put2d(uint32_t* p, uint32_t a, uint32_t b) { a = nz(a), b = nz(b), st2(p, a, b), st2(p + 1024, a, b); }
__device__ __forceinline__ uint32_t ld1(const uint32_t* p) {
    uint32_t v;
    asm volatile("ld.relaxed.gpu.global.b32 %0, [%1];" : "=r"(v) : "l"(p) : "memory");
    return v;
}
template <int N, int V>
__device__ __forceinline__ void fetch(const uint32_t* p, int stride, uint32_t (&a)[N * V]) {
#pragma unroll
    for (int i = 0; i < N; i++) {
        if (V == 1)
            asm volatile("{\n.reg .pred p;\nsetp.eq.u32 p, %0, 0;\n@p ld.relaxed.gpu.global.b32 %0, [%1];\n}"
                         : "+r"(a[i]) : "l"(p + i * stride) : "memory");
        if (V == 4)
            asm volatile("{\n.reg .pred p;\nsetp.eq.u32 p, %4, 0;\n@p ld.relaxed.gpu.global.v4.b32 {%0,%1,%2,%3}, [%5];\n}"
                         : "+r"(a[V * i]), "+r"(a[V * i + V / 4]), "+r"(a[V * i + V / 2]), "+r"(a[V * i + V - 1])
                         : "r"(min(min(a[V * i], a[V * i + V / 4]), min(a[V * i + V / 2], a[V * i + V - 1]))), "l"(p + i * stride) : "memory");
    }
}
template <int N>
__device__ __forceinline__ bool missing(const uint32_t (&a)[N]) {
    uint32_t lo = a[0];
#pragma unroll
    for (int i = 1; i < N; i++) lo = min(lo, a[i]);
    return __any_sync(0xffffffffu, lo == 0);
}
template <int N, int V>
__device__ __forceinline__ void get(const uint32_t* p, int stride, uint32_t (&a)[N * V]) {
    int it = 0;
    do fetch<N, V>(p, stride, a);
    while (missing(a) & (++it < SPIN_LIMIT));
}
__device__ __forceinline__ void cp16(uint32_t dst, const void* src) {
    asm volatile("cp.async.cg.shared.global [%0], [%1], 16;" ::"r"(dst), "l"(src) : "memory");
}

__device__ __forceinline__ uint32_t pack2(float lo, float hi) {
    uint32_t r;
    asm("cvt.rn.bf16x2.f32 %0, %1, %2;" : "=r"(r) : "f"(hi), "f"(lo));
    return r;
}
__device__ __forceinline__ float rbf(float x) { return __uint_as_float(pack2(0.f, x)); }
__device__ __forceinline__ float blo(uint32_t v) { return __uint_as_float(v << 16); }
__device__ __forceinline__ float bhi(uint32_t v) { return __uint_as_float(v & 0xffff0000u); }
__device__ __forceinline__ uint32_t badd2(uint32_t a, uint32_t b) { uint32_t r; asm("add.rn.bf16x2 %0, %1, %2;" : "=r"(r) : "r"(a), "r"(b)); return r; }
__device__ __forceinline__ uint32_t bsub2(uint32_t a, uint32_t b) { uint32_t r; asm("sub.rn.bf16x2 %0, %1, %2;" : "=r"(r) : "r"(a), "r"(b)); return r; }
__device__ __forceinline__ uint32_t bmul2(uint32_t a, uint32_t b) { uint32_t r; asm("mul.rn.bf16x2 %0, %1, %2;" : "=r"(r) : "r"(a), "r"(b)); return r; }
__device__ __forceinline__ float ex2(float x) { float r; asm("ex2.approx.ftz.f32 %0, %1;" : "=f"(r) : "f"(x)); return r; }
__device__ __forceinline__ float rcp(float x) { float r; asm("rcp.approx.ftz.f32 %0, %1;" : "=f"(r) : "f"(x)); return r; }
__device__ __forceinline__ float sqrt_f(float x) { float r; asm("sqrt.approx.ftz.f32 %0, %1;" : "=f"(r) : "f"(x)); return r; }
constexpr float LOG2E = 1.4426950408889634f;
constexpr uint32_t ONE2 = 0x3f803f80u;
__device__ __forceinline__ float sigmoid_f(float x) { return rcp(1.0f + ex2(-LOG2E * x)); }
__device__ __forceinline__ uint32_t silu2(uint32_t v) {
    const float a = blo(v), b = bhi(v);
    return pack2(a * sigmoid_f(a), b * sigmoid_f(b));
}
__device__ __forceinline__ float quad_sum(float v) {
    v += __shfl_xor_sync(0xffffffffu, v, 1);
    return v + __shfl_xor_sync(0xffffffffu, v, 2);
}
__device__ __forceinline__ void ln_partial(const uint32_t (&v)[8], uint32_t dst, bool writer) {
    float s0 = 0.f, s1 = 0.f;
#pragma unroll
    for (int i = 0; i < 8; i++) {
        s0 += blo(v[i]);
        s1 += bhi(v[i]);
    }
    const float mean = quad_sum(s0 + s1) * (1.0f / 64);
    s0 = s1 = 0.f;
#pragma unroll
    for (int i = 0; i < 8; i++) {
        const float a = blo(v[i]) - mean, b = bhi(v[i]) - mean;
        s0 = fmaf(a, a, s0);
        s1 = fmaf(b, b, s1);
    }
    s0 = quad_sum(s0 + s1);
    if (writer) sts64(dst, __float_as_uint(mean), __float_as_uint(s0));
}
__device__ __forceinline__ void ln_combine(uint32_t src, uint32_t& mean2, float& inv) {
    float m[10], q0 = 0.f, q1 = 0.f, s = 0.f;
#pragma unroll
    for (int i = 0; i < 5; i++) {
        const uint4 v = lds128(src + i * 16);
        m[2 * i] = __uint_as_float(v.x);
        m[2 * i + 1] = __uint_as_float(v.z);
        q0 += __uint_as_float(v.y);
        if (i < 4) q1 += __uint_as_float(v.w);
    }
    const float mean = (((m[0] + m[1]) + (m[2] + m[3])) + ((m[4] + m[5]) + (m[6] + m[7])) + m[8]) * (1.0f / 9);
#pragma unroll
    for (int i = 0; i < 9; i++) s = fmaf(m[i] - mean, m[i] - mean, s);
    const float var = fmaf(s, 64.f, q0 + q1) * (1.0f / DM);
    mean2 = pack2(mean, mean);
    inv = rcp(rbf(sqrt_f(rbf(rbf(var) + 1e-5f))));
}
__device__ __forceinline__ uint32_t modulate2(uint32_t x, uint32_t mean2, float inv, uint32_t shift, uint32_t onep) {
    const uint32_t d = bsub2(x, mean2);
    return badd2(bmul2(pack2(blo(d) * inv, bhi(d) * inv), onep), shift);
}
template <int N>
__device__ __forceinline__ void sum_frags(float (&c)[4], uint32_t addr, int stride) {
#pragma unroll
    for (int w = 0; w < N; w++) {
        const uint4 v = lds128(addr + w * stride);
        c[0] += __uint_as_float(v.x); c[1] += __uint_as_float(v.y);
        c[2] += __uint_as_float(v.z); c[3] += __uint_as_float(v.w);
    }
}

template <int ST>
__device__ __forceinline__ void project(uint32_t sm, const uint32_t* src, uint32_t* dst, uint32_t rowoff, uint32_t reds, int nsync, int warp, int lane) {
    constexpr int NW = ST ? 9 : 8;
    const uint32_t red = sm + (ST ? OFF_WO : OFF_P);
    if (warp < NW) {
        const uint32_t wbar = sm + OFF_BAR + (ST ? BAR_WD + (warp < 8 ? ((warp >> 1) - WD_ROT) & 3 : 4) : BAR_WO + (warp >> 1)) * 8;
        const uint32_t ab = sm + (ST ? OFF_WD : OFF_WO) + rowoff;
        const uint32_t ax = sm + (ST ? OFF_DX : OFF_OX) + ((rowoff >> 7) << 4);
        uint32_t a[10][4] = {}, b[4] = {};
        bool have_w = false, need_b = true;
        int it = 0;
        do {
            if (!need_b) mbar_wait(wbar, 0);
            if (!need_b || (!have_w && __all_sync(0xffffffffu, mbar_test(wbar, 0)))) {
                have_w = true;
#pragma unroll
                for (int i = 0; i < 10; i++) ldsm4t(a[i], i % 5 < 4 ? (ab ^ ((i % 5) << 5)) + (i / 5) * 2048 : ax + (i / 5) * 256);
                if (!need_b) break;
            }
            if (ST) fetch<4, 1>(src, 32, b);
            else fetch<1, 4>(src, 0, b);
            need_b = missing(b) & (++it < SPIN_LIMIT);
        } while (need_b | !have_w);
        if (warp == 0) TSL(ST ? 24 : 21);
        float acc[5][4] = {};
#pragma unroll
        for (int i = 0; i < 10; i++) mma(acc[i % 5], a[i][0], a[i][1], a[i][2], a[i][3], b[2 * (i / 5)], b[2 * (i / 5) + 1]);
#pragma unroll
        for (int u = 0; u < 9; u++)
            sts64(red + u * 2304 + (reds & 0xffff), __float_as_uint(acc[u >> 1][2 * (u & 1)]), __float_as_uint(acc[u >> 1][2 * (u & 1) + 1]));
    }
    bar_sync(ST ? 6 : 3, nsync);
    float s[2][2] = {};
#pragma unroll
    for (int w = 0; w < NW; w++) {
        const float2 v = lds64f(red + (reds >> 16) + w * 256);
        s[w & 1][0] += v.x;
        s[w & 1][1] += v.y;
    }
    const uint32_t p0 = (__float_as_uint(s[0][0] + s[1][0]) | 1) ^ ST, p1 = (__float_as_uint(s[0][1] + s[1][1]) | 1) ^ ST;
    st2(dst, p0, p1), st2(dst + 1024, p0, p1);
}

template <int ST>
__device__ __forceinline__ uint32_t reduce16(const uint32_t* src) {
    uint32_t a[32] = {}, bad[16], any;
    int it = 0;
#pragma unroll
    for (int i = 0; i < 16; i++) bad[i] = 1;
    do {
#pragma unroll
        for (int i = 0; i < 16; i++)
            asm volatile("{\n.reg .pred p;\nsetp.ne.u32 p, %2, 0;\n@p ld.relaxed.gpu.global.v2.b32 {%0,%1}, [%3];\n}"
                         : "+r"(a[2 * i]), "+r"(a[2 * i + 1]) : "r"(bad[i]), "l"(src + i * 64) : "memory");
#pragma unroll
        for (int i = 0; i < 16; i++) bad[i] = lop3<ST ? 0xa8 : 0x2a>(a[2 * i], a[2 * i + 1], 1);
        any = lop3<0xfe>(lop3<0xfe>(lop3<0xfe>(bad[0], bad[1], bad[2]), lop3<0xfe>(bad[3], bad[4], bad[5]), lop3<0xfe>(bad[6], bad[7], bad[8])),
                         lop3<0xfe>(lop3<0xfe>(bad[9], bad[10], bad[11]), lop3<0xfe>(bad[12], bad[13], bad[14]), bad[15]), 0);
    } while (__any_sync(0xffffffffu, any != 0) & (++it < SPIN_LIMIT));
    float f[8];
#pragma unroll
    for (int i = 0; i < 8; i++)
        f[i] = (__uint_as_float(a[i]) + __uint_as_float(a[i + 8])) + (__uint_as_float(a[i + 16]) + __uint_as_float(a[i + 24]));
    f[0] = (f[0] + f[2]) + (f[4] + f[6]);
    f[1] = (f[1] + f[3]) + (f[5] + f[7]);
    return movm(pack2(f[0], f[1]));
}

__global__ void __launch_bounds__(NTHREADS, 1) fused_kernel(const Params P, const __grid_constant__ Maps T) {
    extern __shared__ __align__(1024) char smem_raw[];
    constexpr uint32_t sm = 1024;
    const int tid = threadIdx.x, lane = tid & 31;
    const int cta = blockIdx.x, grp = cta >> 3, sub = cta & 7;
    const uint32_t bars = sm + OFF_BAR;
    const int row0 = (sub * HKV + grp) * SK + (SK - WIN);
    u64 pol;
    asm volatile("createpolicy.fractional.L2::evict_first.b64 %0, 1.0;" : "=l"(pol));
    if (tid == NCW * 32) {
        TS(0);
        const int n0 = cta < 108 ? 0 : 3;
#pragma unroll
        for (int i = 0; i < 6; i++) mbar_init(bars + i * 8, 1);
        asm volatile("fence.mbarrier_init.release.cluster;" ::: "memory");
#pragma unroll
        for (int i = 0; i < 3; i++) {
            mbar_expect(bars + (n0 + i) * 8, 12288);
            tma3d(sm + OFF_WM + (n0 + i) * 12288, &T.m[cta < 36 ? M_WA : cta < 108 ? M_WM : M_WQ], cta < 36 ? 16 * cta : 32 * cta,
                  i * 192, 0, bars + (n0 + i) * 8);
            TI(n0 + i);
        }
        TS(26);
    }
    if (tid == NCW * 32 + 32) {
#pragma unroll
        for (int i = 0; i < 4; i++) mbar_init(bars + (BAR_FULL + i) * 8, 1);
        asm volatile("fence.mbarrier_init.release.cluster;" ::: "memory");
#pragma unroll
        for (int t = 0; t < NK0; t++) {
            mbar_expect(bars + (BAR_FULL + t) * 8, TILE_BYTES);
            tma3d_hint(sm + OFF_RING + t * TILE_BYTES, &T.m[M_K], 0, row0 + t * 32, 0, bars + (BAR_FULL + t) * 8, pol);
            TI(6 + t);
        }
    }
    if (tid < 288 && cta < 108) {
#pragma unroll
        for (int i = 0; i < 2; i++) {
            const int row = (lane >> 3) + 4 * i, so = row * DM + (tid >> 5) * 64 + (lane & 7) * 8;
            const uint32_t d = sm + OFF_RED + (tid >> 5) * 2048 + row * 128 + (((lane & 7) ^ row) << 4);
            cp16(d, P.c + so);
            if (cta < 36) cp16(d + 1024, P.x + so);
        }
    }
    uint32_t* const g0 = P.scratch;
    const uint32_t epoch = ld1(g0 + G_EPOCH);
    const int warp = __shfl_sync(0xffffffffu, tid >> 5, 0);
    auto pace = [&](int t, int gain) {
        const int d = (int)atomicAdd(g0 + (epoch & 1) * G_SET + G_CNT, 1u) - 32 * (t - 16) - 16;
        sts32(sm + OFF_WIN, min(max((d * gain + 32) >> 6, W_MIN), W_MAX));
    };

    if (warp >= NCW) {
        const int pw = warp - NCW;
        bar_arrive(1, (NCW + 1) * 32);
        if (pw && lane < M_WQ) asm volatile("prefetch.tensormap [%0];" ::"l"(&T.m[M_WQ - lane]) : "memory");
        if (tid == NCW * 32) sts32(sm + OFF_WIN, 0);
        __syncwarp();
        bar_sync(15, NTHREADS);
        if (lane == 0) {
            if (pw == 0 && cta < 108) {
#pragma unroll 1
                for (int n = 3; n < 6; n++) {
                    mbar_expect(bars + n * 8, 12288);
                    mbar_wait(bars + (n - 3) * 8, 0);
                    tma3d(sm + OFF_WM + n * 12288, &T.m[M_WQ], 32 * cta, (n - 3) * 192, 0, bars + n * 8);
                    TI(n);
                }
            }
#pragma unroll 1
            for (int t = (2 - pw) * NK0; t < 2 * NK0 + 3 * (1 - pw); t++) {
                mbar_expect(bars + (BAR_FULL + t) * 8, TILE_BYTES);
                mbar_wait(bars + (t + (pw ? BAR_FULL - NK0 : 3 - 2 * NK0)) * 8, 0);
                tma3d_hint(sm + OFF_RING + t * TILE_BYTES, &T.m[M_K], 0, row0 + t * 32, 0, bars + (BAR_FULL + t) * 8, pol);
                TI(6 + t);
            }
            if (pw == 0) {
#pragma unroll 1
                for (int t = 2 * NK0 + 3; t < 2 * NT; t++) {
                    if (t == 14 && cta < 108) mbar_wait(bars + BAR_WMF * 8, 0);
                    if (t == 15) TS(30);
                    const int m = t - ((W_KV + (int)lds32(sm + OFF_WIN) + ((0xd8 >> (2 * t & 6)) & 3)) >> 2);
                    const uint32_t fb = bars + (BAR_FULL + (t & 15)) * 8;
                    mbar_wait(fb + (BAR_EMPTY - BAR_FULL) * 8, (~t >> 4) & 1);
                    mbar_expect(fb, TILE_BYTES);
                    mbar_wait(bars + (BAR_FULL + (m & 15)) * 8, (m >> 4) & 1);
                    tma3d_hint(sm + OFF_RING + (t & 15) * TILE_BYTES, &T.m[t >> 6], 0, row0 + (t & (NT - 1)) * 32, 0, fb, pol);
                    TI(6 + t);
                    if (t == T_CLEAR) mbar_arrive(bars + (BAR_SYNC + 1) * 8);
                }
                mbar_arrive(bars + (BAR_SYNC + 2) * 8);
                mbar_wait(bars + BAR_SYNC * 8, 0);
                auto window = [&](int b, int w) {
                    b -= max((w + (int)lds32(sm + OFF_WIN) + ((0xd8 >> (2 * b & 6)) & 3)) >> 2, 1);
                    b = min(b, BAR_GU + B_CAP);
                    mbar_wait(bars + b * 8, b < BAR_WO);
                };
#pragma unroll 1
                for (int i = 0; i < 4; i++) {
                    window(BAR_WO + i, W_WO);
                    tma3d(sm + OFF_WO + i * 8192, &T.m[M_OD], 64 * sub, grp * 256 + i * 64, P.zo, bars + (BAR_WO + i) * 8);
                    tma3d(sm + OFF_OX + i * 1024, &T.m[M_OX], 512 + 8 * sub, grp * 256 + i * 64, P.zo, bars + (BAR_WO + i) * 8);
                    TI(134 + i);
                }
                TS(28);
#pragma unroll 1
                for (int i = 0; i < 9; i++) {
                    mbar_wait(bars + (BAR_EMPTY + i) * 8, 1);
                    window(BAR_GU + i, sub < 4 ? W_GU : W_GU2);
                    tma3d(sm + OFF_GU + i * 8192, &T.m[M_GU], grp * 288 + 32 * sub, i * 64, 0, bars + (BAR_GU + i) * 8);
                    if (sub < 4) tma3d(sm + OFF_GX + i * 2048, &T.m[M_GX], grp * 288 + 256 + 8 * sub, i * 64, 0, bars + (BAR_GU + i) * 8);
                    TI(138 + i);
                }
                TS(29);
#pragma unroll 1
                for (int i = 0; i < 5; i++) {
                    const int blk = i < 4 ? (i + WD_ROT) & 3 : 4, r = min(blk * 64, 224);
                    mbar_wait(bars + (BAR_EMPTY + 9 + blk) * 8, 1);
                    window(BAR_WD + i, W_WD);
                    tma3d(sm + OFF_WD + r * 128, &T.m[M_OD], 64 * sub, grp * 288 + r, P.zo ^ 1, bars + (BAR_WD + i) * 8);
                    tma3d(sm + OFF_DX + r * 16, &T.m[M_OX], 512 + 8 * sub, grp * 288 + r, P.zo ^ 1, bars + (BAR_WD + i) * 8);
                    TI(147 + i);
                }
            } else {
#pragma unroll 1
                for (int i = BAR_WO; i < BAR_WD + 5; i++) mbar_expect(bars + i * 8, i < BAR_GU || i >= BAR_WD ? 9216 : sub < 4 ? 10240 : 8192);
                mbar_arrive(bars + BAR_SYNC * 8);
                mbar_wait(bars + (BAR_SYNC + 2) * 8, 0);
#pragma unroll 1
                for (int t = 124 + (cta & 3); t < 144; t += 4) {
                    mbar_wait(bars + (BAR_FULL - 112 + t) * 8, t < 128);
                    pace(t, GAIN_TAIL);
                }
            }
        }
        return;
    }

    if (lane == 0) {
#pragma unroll
        for (int i = 0; i < 6; i++) mbar_init(bars + (10 + warp * 6 + i) * 8, 1);
        asm volatile("fence.mbarrier_init.release.cluster;" ::: "memory");
    }
    __syncwarp();
    if (warp < 9) bar_arrive(15, NTHREADS);
    const int g = lane >> 2, t4 = lane & 3;
    uint32_t* const gs = g0 + (epoch & 1) * G_SET;

    if (warp < 9) {
        const int off_h = (cta < 36 ? dual(D_H + 2 * cta * 32) : G_M + 4 * (cta - 36) * 32) + tid;
        const int off_h2 = off_h + (cta < 36 ? 1024 : 64);
        const int off_q = dual(D_Q + g * (HQ * 64) + cta * 16) + warp * 8 + t4 * 2;
        uint32_t bf[8] = {}, xp = 0, mean2 = 0;
        float inv = 0.f;
        if (cta < 36) xp = __ldg(reinterpret_cast<const uint32_t*>(P.x) + g * (DM / 2) + 8 * cta + 4 * (warp & 1) + t4);
        if (warp < 2) {
            st2(gs + off_q, 0, 0), st2(gs + off_q + 1024, 0, 0);
            if (cta < 36) st1(gs + off_h, 0), st1(gs + off_h2, 0);
        }
        if (cta < 108) {
            asm volatile("cp.async.wait_all;" ::: "memory");
            __syncwarp();
            const uint32_t fa = sm + OFF_RED + warp * 2048 + (lane & 7) * 128 + (((lane >> 3) ^ (lane & 7)) << 4);
            ldsm4(reinterpret_cast<uint32_t(&)[4]>(bf[0]), fa);
            ldsm4(reinterpret_cast<uint32_t(&)[4]>(bf[4]), fa ^ 64);
            if (cta < 36) {
                uint32_t xv[8];
                ldsm4(reinterpret_cast<uint32_t(&)[4]>(xv[0]), fa + 1024);
                ldsm4(reinterpret_cast<uint32_t(&)[4]>(xv[4]), (fa ^ 64) + 1024);
                ln_partial(xv, sm + OFF_ST + g * 80 + warp * 8, t4 == 0);
            }
#pragma unroll
            for (int i = 0; i < 8; i++) bf[i] = silu2(bf[i]);
        }
        if (warp == 0) TSL(18);
        bar_sync(1, (NCW + 1) * 32);
        if (cta < 36 && warp < 2) ln_combine(sm + OFF_ST + g * 80, mean2, inv);
        const int r = warp * 64 + (lane >> 4) * 8 + (lane & 7), hi8 = (lane >> 3) & 1, box = warp / 3;
#pragma unroll 1
        for (int pass = cta < 108 ? 0 : 1; pass < 2; pass++) {
            const bool pa = pass == 0 && cta < 36;
            const uint32_t ab = sm + OFF_WM + pass * 36864 +
                                (pa ? (box + hi8) * 6144 + r * 32 + ((lane & 4) << 2) : r * 64 + (((2 * hi8) ^ ((r >> 1) & 3)) << 4));
            const uint32_t as = pa ? 512 : 1024, red = sm + OFF_RED + pass * 9216;
            mbar_wait(bars + (pass * 3 + box) * 8, 0);
            if (warp == 8) TSL(pass ? 31 : 19);
            uint32_t a[4][2][4];
#pragma unroll
            for (int i = 0; i < 4; i++) {
                ldsm4t(a[i][0], ab + i * as);
                ldsm4t(a[i][1], (ab ^ 16) + i * as);
            }
            if (pass) {
                bar_sync(8, NCW * 32);
#pragma unroll
                for (int i = 0; i < 8; i++) bf[i] = 0;
                get<8, 1>(gs + near(D_H + warp * 256, lds32(sm + OFF_WIN + 4)) + lane, 32, bf);
                if (warp == 0) TSL(3);
            }
            float acc[2][4] = {};
#pragma unroll
            for (int i = 0; i < 4; i++)
#pragma unroll
                for (int m = 0; m < 2; m++) mma(acc[m], a[i][m][0], a[i][m][1], a[i][m][2], a[i][m][3], bf[2 * i], bf[2 * i + 1]);
            sts128f(red + tid * 16, acc[0]);
            sts128f(red + 4608 + tid * 16, acc[1]);
            bar_sync(3, 288);
            if (warp < 2) {
                float c[4] = {};
                sum_frags<9>(c, red + warp * 4608 + lane * 16, 512);
                uint32_t lo = movm(pack2(c[0], c[1])), hi = movm(pack2(c[2], c[3]));
                if (pass) {
                    put2d(gs + off_q, lo, hi);
                    if (warp == 0) TSL(4);
                } else {
                    const uint32_t hi1 = badd2(hi, ONE2);
                    if (pa) hi = lo = modulate2(xp, mean2, inv, lo, hi1);
                    if (cta >= 72 && cta < 90) lo = badd2(lo, ONE2), hi = hi1;
                    st1(gs + off_h, nz(lo));
                    st1(gs + off_h2, nz(hi));
                    if (warp == 0 && pa) TSL(2);
                }
            } else if (tid == 64 && pass == 0) {
                mbar_arrive(bars + BAR_WMF * 8);
            }
        }
    } else {
        if ((uint32_t)__cvta_generic_to_shared(smem_raw) != sm) __trap();
        uint32_t* const ping = g0 + dual(D_PING) + cta * 8;
        if (lane < 16) st1(ping + (lane >> 3) * 1024 + (lane & 7), 0);
        bar_sync(15, NTHREADS);
        uint32_t best[2] = {~0u, ~0u}, v = 0;
#pragma unroll 1
        for (int part = 0; part < 2; part++) {
            if (lane == 0) {
#pragma unroll 1
                for (int r = part ? NPING1 : NPING0; r > 0; r--) {
#pragma unroll
                    for (int k = 0; k < 2; k++) {
                        const uint32_t t0 = clock32(v);
                        v = atomicExch(ping + k * 1024, t0);
                        best[k] = min(best[k], clock32(v) - t0);
                    }
                }
                sts32(sm + OFF_WIN + 4 + 4 * part, ((best[1] < best[0]) ^ __popc(D_PING & 0x16400)) & 1);
            }
            __syncwarp();
            if (part) break;
            TSL(20);
            bar_arrive(8, NCW * 32);
            mbar_wait(bars + 5 * 8, 0);
            uint32_t a[4] = {};
            get<1, 4>(gs + near(D_Q + (sub * HQ + 2 * grp) * 64, lds32(sm + OFF_WIN + 4)) + lane * 4, 0, a);
            sts128(sm + OFF_QS + lane * 16, a[0], a[1], a[2], a[3]);
            __syncwarp();
            TSL(5);
            bar_arrive(4, 288);
        }
#pragma unroll
        for (int i = lane; i < 72; i += 32) cp16(sm + OFF_WR + i * 16, P.wr + i * 8);
        asm volatile("cp.async.wait_all;" ::: "memory");
        __syncwarp();
        bar_arrive(2, NCW * 32);
        if (cta == 0 && lane == 0) st1(g0 + (~epoch & 1) * G_SET + G_CNT, 0);
        mbar_wait(bars + (BAR_SYNC + 1) * 8, 0);
#pragma unroll 1
        for (int c = 0; c < 4; c++) {
            uint32_t* const pg = g0 + (c >> 1) * G_SET + (c & 1) * 1024;
            zero4(pg + dual(D_O + cta * 128) + lane * 4);
            zero4(pg + dual(D_ACT + (grp * 36 + 4 * sub) * 32) + lane * 4);
            if (lane < 8 ? sub < 4 : lane < 16 && cta < 72)
                zero4(pg + dual(lane < 8 ? D_ACT + (grp * 36 + 32 + sub) * 32 : D_X1 + cta * 32) + (lane & 7) * 4);
        }
#pragma unroll 1
        for (int u = 0; u < 9; u++) zero4(g0 + dual(d_part(u < 8 ? 8 * sub + u : 64 + sub)) + (lane >> 4) * 1024 + grp * 64 + (lane & 15) * 4);
        {
            uint32_t* const nx = g0 + (~epoch & 1) * G_SET;
            uint32_t* const q = nx + dual(D_Q + g * (HQ * 64) + cta * 16) + t4 * 4;
            zero4(q), zero4(q + 1024);
            if (cta < 108) zero4(nx + (cta < 36 ? dual(D_H + 2 * cta * 32) + (lane >> 4) * (1024 - 64) : G_M + 4 * (cta - 36) * 32) + lane * 4);
        }
        if (cta >= 72) {
            bar_arrive(5, NCW * 32);
            return;
        }
        const uint32_t io = pin(4 * (g * (DM / 2) + 4 * cta + t4));
        uint32_t x = __ldg(at(reinterpret_cast<const uint32_t*>(P.x), io)), gab[2] = {};
        get<2, 1>(gs + G_M + cta * 32 + lane, 216 * 32, gab);
        const uint32_t src_p = pin(4 * (near(d_part(cta), lds32(sm + OFF_WIN + 8)) + lane * 2));
        const uint32_t dst_x = pin(4 * ((epoch & 1) * G_SET + dual(D_X1 + cta * 32) + lane));
        bar_sync(5, NCW * 32);
        x = badd2(x, bmul2(gab[0], reduce16<0>(at(g0, src_p))));
        put1d(at(g0, dst_x), x);
        TSL(10);
        bar_sync(6, NCW * 32);
        const uint4 r0 = lds128(sm + OFF_RT + g * 48), r1 = lds128(sm + OFF_RT + g * 48 + 16);
        float r = __uint_as_float(lds32(sm + OFF_RT + g * 48 + 32));
        r += ((__uint_as_float(r0.x) + __uint_as_float(r0.y)) + (__uint_as_float(r0.z) + __uint_as_float(r0.w))) +
             ((__uint_as_float(r1.x) + __uint_as_float(r1.y)) + (__uint_as_float(r1.z) + __uint_as_float(r1.w)));
        r = sigmoid_f(rbf(r));
        const uint32_t h = lds32(sm + OFF_HU + lane * 4), rs = pack2(r, r);
        *at(reinterpret_cast<uint32_t*>(P.out), io) = badd2(x, bmul2(gab[1], badd2(h, bmul2(reduce16<1>(at(g0, src_p)), rs))));
        if (cta == 0 && lane == 0) g0[G_EPOCH] = epoch + 1;
        TSL(15);
        return;
    }

    const uint32_t tile = sm + OFF_RING + warp * TILE_BYTES;
    const uint32_t fullb = bars + (BAR_FULL + warp) * 8;
    const uint32_t pw = sm + OFF_P + warp * (2 * P_PITCH);
    const bool pacer = (tid & 127) == (cta & 3) * 32;
    if (warp < 8) {
        {
            uint32_t q0[8], q1[8];
            bar_sync(4, 288);
#pragma unroll
            for (int i = 0; i < 8; i++) {
                const float2 v = lds64f(sm + OFF_QS + (g & 1) * 256 + i * 32 + t4 * 8);
                q0[i] = __float_as_uint(v.x), q1[i] = __float_as_uint(v.y);
            }
            uint32_t sp = pw + (t4 & 1) * P_PITCH + ((t4 >> 1) * 8 + g) * 2;
#pragma unroll 1
            for (int it = 0; it < 8; it++, sp += 64) {
                const uint32_t ab = tile + (it & 1) * (8 * TILE_BYTES) + (lane & 15) * 128 + (((lane >> 4) ^ (lane & 7)) << 4);
                mbar_wait(fullb + (it & 1) * 64, (it >> 1) & 1);
                float acc[2][2][4] = {};
#pragma unroll
                for (int ks = 0; ks < 8; ks++)
#pragma unroll
                    for (int m = 0; m < 2; m++) {
                        uint32_t a[4];
                        ldsm4(a, (ab ^ ((ks & 3) << 5)) + (ks >> 2) * 4096 + m * 2048);
                        mma(acc[m][ks & 1], a[0], a[1], a[2], a[3], (ks & 1) ? q1[ks - 1] : q0[ks], (ks & 1) ? q1[ks] : q0[ks + 1]);
                    }
                __syncwarp();
                if (lane == 0) mbar_arrive(fullb + (it & 1) * 64 + (BAR_EMPTY - BAR_FULL) * 8);
#pragma unroll
                for (int m = 0; m < 2; m++) {
                    const float s = sel4(acc[m][0], t4) + sel4(acc[m][1], t4);
                    sts16(sp + m * 32, (uint16_t)pack2(rbf(s) * 0.08838834764831845f, 0.f));
                }
                if (pacer && it >= 2) pace(it * 8 + warp, GAIN_KV);
                __syncwarp();
            }
        }
        __syncwarp();
        if (warp == 7) TSL(6);
        const uint32_t pa = pw + (lane >> 4) * P_PITCH + (lane & 15) * 32;
        const uint32_t sa = sm + OFF_SM + (lane >> 4) * 64;
        const uint4 v0 = lds128(pa), v1 = lds128(pa + 16);
        const uint32_t sv[8] = {v0.x, v0.y, v0.z, v0.w, v1.x, v1.y, v1.z, v1.w};
        float e[16];
        float m = -INFINITY;
#pragma unroll
        for (int i = 0; i < 8; i++) {
            e[2 * i] = blo(sv[i]);
            e[2 * i + 1] = bhi(sv[i]);
            m = fmaxf(m, fmaxf(e[2 * i], e[2 * i + 1]));
        }
#pragma unroll
        for (int o = 8; o; o >>= 1) m = fmaxf(m, __shfl_xor_sync(0xffffffffu, m, o));
        float l = 0.f;
#pragma unroll
        for (int i = 0; i < 16; i++) {
            e[i] = ex2((e[i] - m) * LOG2E);
            l += e[i];
        }
#pragma unroll
        for (int o = 8; o; o >>= 1) l += __shfl_xor_sync(0xffffffffu, l, o);
        if ((lane & 15) == 0) sts64(sa + warp * 8, __float_as_uint(m), __float_as_uint(l));
        bar_sync(2, NCW * 32);
        const float2 v = lds64f(sa + (lane & 7) * 8);
        float M = v.x;
#pragma unroll
        for (int o = 4; o; o >>= 1) M = fmaxf(M, __shfl_xor_sync(0xffffffffu, M, o));
        float L = v.y * ex2((v.x - M) * LOG2E);
#pragma unroll
        for (int o = 4; o; o >>= 1) L += __shfl_xor_sync(0xffffffffu, L, o);
        const float sc = ex2((m - M) * LOG2E) * rcp(L);
        sts128(pa, pack2(e[0] * sc, e[1] * sc), pack2(e[2] * sc, e[3] * sc), pack2(e[4] * sc, e[5] * sc), pack2(e[6] * sc, e[7] * sc));
        sts128(pa + 16, pack2(e[8] * sc, e[9] * sc), pack2(e[10] * sc, e[11] * sc), pack2(e[12] * sc, e[13] * sc), pack2(e[14] * sc, e[15] * sc));
        __syncwarp();
    } else {
        bar_sync(2, NCW * 32);
    }

    uint32_t sh[8] = {}, op[8] = {};
    {
        const uint32_t* const src_m = gs + G_M + (72 + warp * 8) * 32 + lane;
        fetch<8, 1>(src_m + 72 * 32, 32, op);
        get<8, 1>(src_m, 32, sh);
        get<8, 1>(src_m + 72 * 32, 32, op);
    }
    const int side = lds32(sm + OFF_WIN + 8), set = (epoch & 1) * G_SET, rr = (lane >> 4) * 8 + (lane & 7);
    const uint32_t dst_o = pin(4 * (set + dual(D_O + cta * 128) + (tid & 0x70) + (tid & 3) * 4 + ((tid >> 2) & 3)));
    const uint32_t src_o = pin(4 * (set + near(D_O + grp * 1024, side) + g * 128 + warp * 16 + t4 * 4));
    const uint32_t dst_p = pin(4 * (dual(d_part(warp < 8 ? 8 * sub + warp : 64 + sub)) + grp * 64 + lane * 2));
    const uint32_t src_x = pin(4 * (set + near(D_X1 + warp * 256, side) + lane));
    const uint32_t dst_a = pin(4 * (set + dual(D_ACT + (grp * 36 + (warp < 4 ? 4 * sub + warp : 32 + sub)) * 32) + lane));
    const uint32_t src_a = pin(4 * (set + near(D_ACT + (grp * 36 + 4 * warp) * 32, side) + lane));
    const uint32_t rowoff = pin((warp * 32 + rr) * 128 + ((((lane >> 3) & 1) ^ (lane & 7)) << 4));
    const uint32_t reds = pin((tid * 8) | (warp * 2304 + lane * 8) << 16);
    const uint32_t ored = pin((warp * 1088 + (t4 & 1) * 576 + ((t4 >> 1) * 8 + g) * 4) | ((tid >> 6) * 64 + tid * 8) << 16);

    if (warp < 8) {
        float acc[8][4] = {};
        uint32_t pp = pw + (lane & 1) * P_PITCH + (lane >> 3) * 16;
#pragma unroll 1
        for (int it = 0; it < 8; it++, pp += 64) {
            const uint32_t ab = tile + (it & 1) * (8 * TILE_BYTES) + ((lane & 7) + (lane >> 4) * 8) * 128 + ((((lane >> 3) & 1) ^ (lane & 7)) << 4);
            uint32_t pb[4];
            ldsm4(pb, pp);
            mbar_wait(fullb + (it & 1) * 64, (it >> 1) & 1);
#pragma unroll
            for (int ks = 0; ks < 2; ks++)
#pragma unroll
                for (int m = 0; m < 8; m++) {
                    uint32_t a[4];
                    ldsm4t(a, (ab ^ ((m & 3) << 5)) + (m >> 2) * 4096 + ks * 2048);
                    mma(acc[m], a[0], a[1], a[2], a[3], pb[2 * ks], pb[2 * ks + 1]);
                }
            __syncwarp();
            if (lane == 0) mbar_arrive(fullb + (it & 1) * 64 + (BAR_EMPTY - BAR_FULL) * 8);
            if (pacer && it * 8 + warp < NT - 4) pace(NT + it * 8 + warp, GAIN_KV);
            __syncwarp();
        }
        if (warp == 7) TSL(7);
        const uint32_t ra = sm + OFF_ORED + (ored & 0xffff);
#pragma unroll
        for (int m = 0; m < 8; m++) sts32(ra + m * 64, __float_as_uint(sel4(acc[m], t4)));
    }
    bar_sync(5, NCW * 32);
    if (warp < 4) {
        float s[2][2] = {};
#pragma unroll
        for (int w = 0; w < 8; w++) {
            const float2 v = lds64f(sm + OFF_ORED + w * 1088 + (ored >> 16));
            s[w & 1][0] += v.x;
            s[w & 1][1] += v.y;
        }
        put1d(at(g0, dst_o), pack2(s[0][0] + s[1][0], s[0][1] + s[1][1]));
        if (warp == 0) TSL(8);
    }

    project<0>(sm, at(g0, src_o), at(g0, dst_p), rowoff, reds, 288, warp, lane);
    if (warp == 0) TSL(9);

    const uint32_t gbar = bars + (BAR_GU + warp) * 8;
    const int pl = ((lane >> 3) & 1) ^ P.zg;
    const uint32_t ab = sm + OFF_GU + warp * 8192 + pl * 4096 + rr * 64 + ((lane & 6) << 3);
    const uint32_t ax = sm + OFF_GX + warp * 2048 + pl * 1024 + rr * 16;
    uint32_t a[20][4] = {}, h[8] = {};
    auto load_gu = [&]() {
#pragma unroll
        for (int i = 0; i < 20; i++) ldsm4t(a[i], i % 5 < 4 ? (ab ^ ((i % 5) << 4)) + (i / 5) * 1024 : ax + (i / 5) * 256);
    };
    bool gpre = false;
    {
        int it = 0;
        do {
            if (!gpre && __all_sync(0xffffffffu, mbar_test(gbar, 0))) gpre = true, load_gu();
            fetch<8, 1>(at(g0, src_x), 32, h);
        } while (missing(h) & (++it < SPIN_LIMIT));
    }
    if (warp == 0) TSL(11);
    ln_partial(h, sm + OFF_ST + g * 80 + warp * 8, t4 == 0);
    bar_sync(3, 288);
    {
        uint32_t mean2;
        float inv;
        ln_combine(sm + OFF_ST + g * 80, mean2, inv);
#pragma unroll
        for (int i = 0; i < 8; i++) h[i] = modulate2(h[i], mean2, inv, sh[i], op[i]);
    }
    if (warp == 0) TSL(12);
    if (!gpre) {
        mbar_wait(gbar, 0);
        load_gu();
    }
    if (warp == 8) TSL(17);
    {
        float acc[5][4] = {};
#pragma unroll
        for (int i = 0; i < 20; i++) mma(acc[i % 5], a[i][0], a[i][1], a[i][2], a[i][3], h[2 * (i / 5)], h[2 * (i / 5) + 1]);
#pragma unroll
        for (int m = 0; m < 5; m++) sts128f(sm + OFF_RED + m * 4608 + 2 * (reds & 0xffff), acc[m]);
    }
    bar_sync(3, 288);
    if (warp < 5) {
        float c[4] = {};
        sum_frags<9>(c, sm + OFF_RED + 2 * (reds >> 16), 512);
        const uint32_t w = movm(bmul2(silu2(pack2(c[0], c[1])), pack2(c[2], c[3])));
        if (warp < 4 || sub < 4) put1d(at(g0, dst_a), w);
        if (warp == 1) TSL(13);
    }
    if (cta < 72) {
        float r = 0.f;
#pragma unroll
        for (int i = 0; i < 8; i++) {
            const uint32_t wr = lds32(sm + OFF_WR + (warp * 32 + i * 4 + t4) * 4);
            r = fmaf(blo(h[i]), blo(wr), fmaf(bhi(h[i]), bhi(wr), r));
            if (warp * 8 + i == cta) sts32(sm + OFF_HU + lane * 4, h[i]);
        }
        r = quad_sum(r);
        if (t4 == 0) sts32(sm + OFF_RT + g * 48 + warp * 4, __float_as_uint(r));
    }

    project<1>(sm, at(g0, src_a), at(g0, dst_p), rowoff, reds, cta < 72 ? 320 : 288, warp, lane);
    if (warp == 0) TSL(14);
}

typedef CUresult (*EncodeFn)(CUtensorMap*, CUtensorMapDataType, cuuint32_t, void*, const cuuint64_t*, const cuuint64_t*,
                             const cuuint32_t*, const cuuint32_t*, CUtensorMapInterleave, CUtensorMapSwizzle,
                             CUtensorMapL2promotion, CUtensorMapFloatOOBfill);

void make_map(EncodeFn enc, CUtensorMap* m, void* p, int cols, int rows, int pitch, int bc, int br, int bp, int planes, size_t pstride,
              CUtensorMapSwizzle sw, int promo) {
    cuuint64_t dims[3] = {(cuuint64_t)cols, (cuuint64_t)rows, (cuuint64_t)planes};
    cuuint64_t strides[2] = {(cuuint64_t)pitch * 2, (cuuint64_t)pstride};
    cuuint32_t box[3] = {(cuuint32_t)bc, (cuuint32_t)br, (cuuint32_t)bp};
    cuuint32_t es[3] = {1, 1, 1};
    enc(m, CU_TENSOR_MAP_DATA_TYPE_BFLOAT16, 3, p, dims, strides, box, es, CU_TENSOR_MAP_INTERLEAVE_NONE, sw,
        (CUtensorMapL2promotion)promo, CU_TENSOR_MAP_FLOAT_OOB_FILL_NONE);
}

}

extern "C" void kernel_launch(void* const* d_in, const int* in_sizes, int n_in, void* d_out, int out_size) {
    static EncodeFn enc = nullptr;
    static uint32_t* scratch = nullptr;
    if (!enc) {
        void* fn = nullptr;
        cudaDriverEntryPointQueryResult st;
        cudaGetDriverEntryPoint("cuTensorMapEncodeTiled", &fn, cudaEnableDefault, &st);
        enc = (EncodeFn)fn;
        cudaGetSymbolAddress(&fn, g_scratch);
        scratch = (uint32_t*)(((uintptr_t)fn + 8 * G_SET - 1) & ~(uintptr_t)(8 * G_SET - 1));
        cudaFuncSetAttribute(fused_kernel, cudaFuncAttributeMaxDynamicSharedMemorySize, SMEM_BYTES);
    }
    Params P;
    Maps T;
    const CUtensorMapSwizzle none = CU_TENSOR_MAP_SWIZZLE_NONE;
    make_map(enc, &T.m[M_K], d_in[1], 64, NB * HKV * SK, DH, 64, 32, 2, 2, 128, CU_TENSOR_MAP_SWIZZLE_128B, PROMO_KV);
    make_map(enc, &T.m[M_V], d_in[2], 64, NB * HKV * SK, DH, 64, 32, 2, 2, 128, CU_TENSOR_MAP_SWIZZLE_128B, PROMO_KV);
    make_map(enc, &T.m[M_WQ], d_in[3], HQ * DH, DM, HQ * DH, 32, 192, 1, 1, 16, CU_TENSOR_MAP_SWIZZLE_64B, PROMO_W);
    make_map(enc, &T.m[M_WM], d_in[11], 6 * DM, DM, 6 * DM, 32, 192, 1, 1, 16, CU_TENSOR_MAP_SWIZZLE_64B, PROMO_W);
    make_map(enc, &T.m[M_WA], d_in[11], DM, DM, 6 * DM, 16, 192, 2, 2, DM * 2, CU_TENSOR_MAP_SWIZZLE_32B, PROMO_W);
    char *wg = (char*)d_in[7], *wu = (char*)d_in[8], *wo = (char*)d_in[4], *wd = (char*)d_in[9];
    P.zg = wg > wu;
    P.zo = wo > wd;
    const size_t sg = P.zg ? wg - wu : wu - wg, so = P.zo ? wo - wd : wd - wo;
    make_map(enc, &T.m[M_GU], P.zg ? wu : wg, FF, DM, FF, 32, 64, 2, 2, sg, CU_TENSOR_MAP_SWIZZLE_64B, PROMO_GU);
    make_map(enc, &T.m[M_GX], P.zg ? wu : wg, FF, DM, FF, 8, 64, 2, 2, sg, none, PROMO_GX);
    make_map(enc, &T.m[M_OD], P.zo ? wd : wo, DM, FF, DM, 64, 64, 1, 2, so, CU_TENSOR_MAP_SWIZZLE_128B, PROMO_W);
    make_map(enc, &T.m[M_OX], P.zo ? wd : wo, DM, FF, DM, 8, 64, 1, 2, so, none, PROMO_OX);
    P.x = (const __nv_bfloat16*)d_in[0];
    P.wr = (const __nv_bfloat16*)d_in[6];
    P.c = (const __nv_bfloat16*)d_in[10];
    P.out = (__nv_bfloat16*)d_out;
    P.scratch = scratch;
    fused_kernel<<<NCTA, NTHREADS, SMEM_BYTES>>>(P, T);
}
```

```cpp
#include <cuda_runtime.h>
#include <cuda_bf16.h>
#include <cuda.h>
#include <stdint.h>

typedef unsigned long long u64;

#define W_KV 21
#define W_WO 19
#define W_GU 19
#define W_GU2 W_GU
#define W_WD 14
#define W_MIN -6
#define W_MAX 8
#define GAIN_KV 2
#define GAIN_TAIL 3
#define NK0 3
#define T_CLEAR 116
#define B_CAP 8
#define GB_AT 2
#define WD_ROT 3
#define NPING0 5
#define NPING1 16
#define PROMO_W CU_TENSOR_MAP_L2_PROMOTION_L2_128B
#define PROMO_GX 2
#define PROMO_OX 2
#define PROMO_GU 2
#define PROMO_KV CU_TENSOR_MAP_L2_PROMOTION_L2_256B

namespace {

constexpr int NB = 8, DM = 576, HQ = 32, HKV = 16, SK = 8192, WIN = 2048, DH = 128, FF = 4608;
constexpr int NCTA = 128;
constexpr int NCW = 10;
constexpr int NTHREADS = (NCW + 2) * 32;
constexpr int TILE_BYTES = 8192, NSLOT = 16, NT = 64;
constexpr int SPIN_LIMIT = 1 << 22;

constexpr int OFF_RING = 0;
constexpr int OFF_WM = 121856;
constexpr int OFF_WQ = OFF_WM + 36864;
constexpr int OFF_GU = 0;
constexpr int OFF_WD = 73728;
constexpr int OFF_GB = 114688;
constexpr int OFF_OX = 131072;
constexpr int OFF_DX = OFF_OX + 4096;
constexpr int OFF_GX = OFF_DX + 4608;
constexpr int OFF_WO = OFF_WQ;
constexpr int OFF_P = OFF_WQ + 36864;
constexpr int P_PITCH = 528;
constexpr int OFF_RED = OFF_P + 16 * P_PITCH;
constexpr int OFF_ORED = OFF_RED + 5 * 4608 - 8704;
constexpr int OFF_ST = OFF_RED + 5 * 4608;
constexpr int OFF_SM = OFF_ST + 640;
constexpr int OFF_RT = OFF_SM + 128;
constexpr int OFF_HU = OFF_RT + 384;
constexpr int OFF_QS = OFF_HU + 128;
constexpr int OFF_WR = OFF_QS + 512;
constexpr int OFF_WIN = OFF_WR + 1152;
constexpr int OFF_BAR = OFF_WIN + 16;
constexpr int BAR_FULL = 6, BAR_WO = 22, BAR_GU = 26, BAR_WD = 35, BAR_EMPTY = 40, BAR_SYNC = 56, BAR_WMF = 59, BAR_GB = 60, NBAR = 70;
constexpr int SMEM_BYTES = OFF_BAR + NBAR * 8;

constexpr int D_X1 = 0;
constexpr int D_O = 3072;
constexpr int D_ACT = D_O + 512 * 32;
constexpr int D_H = D_ACT + 576 * 32;
constexpr int D_Q = D_H + 3072;
constexpr int G_M = 2 * (D_Q + NB * HQ * 64);
constexpr int G_CNT = G_M + 216 * 32;
constexpr int G_SET = 1 << 18;
__device__ __forceinline__ int d_part(int unit) { return (64 + unit + (unit & 64)) * 1024; }
constexpr int D_PING = 200 * 1024;
constexpr int G_EPOCH = 201 * 2048;
static_assert(G_CNT < 64 * 2048, "scratch layout");
__device__ uint32_t g_scratch[4 * G_SET];
__device__ __forceinline__ int dual(int w) { return w + (w & ~1023); }
__device__ __forceinline__ int near(int w, int side) { return dual(w) + (((__popc(w & 0x16400) ^ side) & 1) << 10); }

#define TI(i)
#define TS(i)
#define TSL(i)

enum { M_K, M_V, M_GU, M_GX, M_OD, M_OX, M_WQ, M_WM, M_WA, M_GB, NMAP };
struct Params {
    const __nv_bfloat16 *c, *x, *wr;
    __nv_bfloat16* out;
    uint32_t* scratch;
    int zg, zo;
};
struct Maps {
    CUtensorMap m[NMAP];
};

__device__ __forceinline__ void mbar_init(uint32_t bar, int cnt) {
    asm volatile("mbarrier.init.shared::cta.b64 [%0], %1;" ::"r"(bar), "r"(cnt));
}
__device__ __forceinline__ void mbar_expect(uint32_t bar, uint32_t bytes) {
    asm volatile("mbarrier.arrive.expect_tx.shared::cta.b64 _, [%0], %1;" ::"r"(bar), "r"(bytes) : "memory");
}
__device__ __forceinline__ void mbar_arrive(uint32_t bar) {
    asm volatile("mbarrier.arrive.shared::cta.b64 _, [%0];" ::"r"(bar) : "memory");
}
__device__ __forceinline__ void mbar_wait(uint32_t bar, uint32_t parity) {
    asm volatile("{\n.reg .pred p;\n.reg .u32 c;\n"
                 "mbarrier.try_wait.parity.shared::cta.b64 p, [%0], %1;\n@p bra DONE;\nmov.u32 c, %2;\n"
                 "AGAIN:\nmbarrier.try_wait.parity.shared::cta.b64 p, [%0], %1;\nsub.u32 c, c, 1;\n"
                 "setp.eq.or.u32 p, c, 0, p;\n@!p bra AGAIN;\nDONE:\n}"
                 ::"r"(bar), "r"(parity), "n"(SPIN_LIMIT) : "memory");
}
__device__ __forceinline__ bool mbar_test(uint32_t bar, uint32_t parity) {
    uint32_t ok;
    asm volatile("{\n.reg .pred p;\nmbarrier.test_wait.parity.shared::cta.b64 p, [%1], %2;\nselp.u32 %0, 1, 0, p;\n}"
                 : "=r"(ok) : "r"(bar), "r"(parity) : "memory");
    return ok;
}
__device__ __forceinline__ void mbar_wait_lanes(uint32_t bar) {
    mbar_wait(bar, 0);
    __syncwarp();
}
__device__ __forceinline__ void tma3d_hint(uint32_t dst, const CUtensorMap* m, int x, int y, int z, uint32_t bar, u64 pol) {
    asm volatile("cp.async.bulk.tensor.3d.shared::cluster.global.mbarrier::complete_tx::bytes.L2::cache_hint"
                 " [%0], [%1, {%2, %3, %4}], [%5], %6;"
                 ::"r"(dst), "l"(m), "r"(x), "r"(y), "r"(z), "r"(bar), "l"(pol) : "memory");
}
__device__ __forceinline__ void tma3d(uint32_t dst, const CUtensorMap* m, int x, int y, int z, uint32_t bar) {
    asm volatile("cp.async.bulk.tensor.3d.shared::cluster.global.mbarrier::complete_tx::bytes [%0], [%1, {%2, %3, %4}], [%5];"
                 ::"r"(dst), "l"(m), "r"(x), "r"(y), "r"(z), "r"(bar) : "memory");
}
__device__ __forceinline__ void bar_sync(int id, int n) { asm volatile("bar.sync %0, %1;" ::"r"(id), "r"(n) : "memory"); }
__device__ __forceinline__ void bar_arrive(int id, int n) { asm volatile("bar.arrive %0, %1;" ::"r"(id), "r"(n) : "memory"); }
__device__ __forceinline__ void ldsm4(uint32_t (&r)[4], uint32_t a) {
    asm volatile("ldmatrix.sync.aligned.m8n8.x4.shared.b16 {%0,%1,%2,%3}, [%4];"
                 : "=r"(r[0]), "=r"(r[1]), "=r"(r[2]), "=r"(r[3]) : "r"(a) : "memory");
}
__device__ __forceinline__ void ldsm4t(uint32_t (&r)[4], uint32_t a) {
    asm volatile("ldmatrix.sync.aligned.m8n8.x4.trans.shared.b16 {%0,%1,%2,%3}, [%4];"
                 : "=r"(r[0]), "=r"(r[1]), "=r"(r[2]), "=r"(r[3]) : "r"(a) : "memory");
}
__device__ __forceinline__ void mma(float (&c)[4], uint32_t a0, uint32_t a1, uint32_t a2, uint32_t a3, uint32_t b0, uint32_t b1) {
    asm volatile("mma.sync.aligned.m16n8k16.row.col.f32.bf16.bf16.f32 {%0,%1,%2,%3}, {%4,%5,%6,%7}, {%8,%9}, {%0,%1,%2,%3};"
                 : "+f"(c[0]), "+f"(c[1]), "+f"(c[2]), "+f"(c[3])
                 : "r"(a0), "r"(a1), "r"(a2), "r"(a3), "r"(b0), "r"(b1));
}
__device__ __forceinline__ uint32_t movm(uint32_t a) {
    uint32_t d;
    asm volatile("movmatrix.sync.aligned.m8n8.trans.b16 %0, %1;" : "=r"(d) : "r"(a));
    return d;
}
__device__ __forceinline__ uint32_t lds32(uint32_t a) { uint32_t v; asm volatile("ld.shared.b32 %0, [%1];" : "=r"(v) : "r"(a) : "memory"); return v; }
__device__ __forceinline__ float2 lds64f(uint32_t a) { float2 v; asm volatile("ld.shared.v2.f32 {%0,%1}, [%2];" : "=f"(v.x), "=f"(v.y) : "r"(a) : "memory"); return v; }
__device__ __forceinline__ uint4 lds128(uint32_t a) { uint4 v; asm volatile("ld.shared.v4.b32 {%0,%1,%2,%3}, [%4];" : "=r"(v.x), "=r"(v.y), "=r"(v.z), "=r"(v.w) : "r"(a) : "memory"); return v; }
__device__ __forceinline__ void sts32(uint32_t a, uint32_t v) { asm volatile("st.shared.b32 [%0], %1;" ::"r"(a), "r"(v) : "memory"); }
__device__ __forceinline__ void sts16(uint32_t a, uint16_t v) { asm volatile("st.shared.b16 [%0], %1;" ::"r"(a), "h"(v) : "memory"); }
__device__ __forceinline__ void sts64(uint32_t a, uint32_t x, uint32_t y) { asm volatile("st.shared.v2.b32 [%0], {%1,%2};" ::"r"(a), "r"(x), "r"(y) : "memory"); }
__device__ __forceinline__ void sts128(uint32_t a, uint32_t x, uint32_t y, uint32_t z, uint32_t w) {
    asm volatile("st.shared.v4.b32 [%0], {%1,%2,%3,%4};" ::"r"(a), "r"(x), "r"(y), "r"(z), "r"(w) : "memory");
}
__device__ __forceinline__ void sts128f(uint32_t a, const float (&c)[4]) {
    sts128(a, __float_as_uint(c[0]), __float_as_uint(c[1]), __float_as_uint(c[2]), __float_as_uint(c[3]));
}

__device__ __forceinline__ float sel4(const float (&c)[4], int t) { return (t & 2) ? ((t & 1) ? c[3] : c[2]) : ((t & 1) ? c[1] : c[0]); }

template <int LUT>
__device__ __forceinline__ uint32_t lop3(uint32_t a, uint32_t b, uint32_t c) {
    uint32_t d;
    asm("lop3.b32 %0, %1, %2, %3, %4;" : "=r"(d) : "r"(a), "r"(b), "r"(c), "n"(LUT));
    return d;
}
__device__ __forceinline__ uint32_t pin(uint32_t v) { return __shfl_xor_sync(0xffffffffu, v, 0); }
template <typename T>
__device__ __forceinline__ T* at(T* base, uint32_t bytes) { return (T*)((const char*)base + bytes); }

__device__ __forceinline__ uint32_t clock32(uint32_t dep) {
    uint32_t t;
    asm volatile("{\n.reg .pred p;\nsetp.eq.u32 p, %1, 0x9e3779b9;\n@p nanosleep.u32 1;\nmov.u32 %0, %clock;\n}" : "=r"(t) : "r"(dep) : "memory");
    return t;
}

__device__ __forceinline__ uint32_t nz(uint32_t v) { return v ? v : 0x80000000u; }
__device__ __forceinline__ void st1(uint32_t* p, uint32_t a) { asm volatile("st.relaxed.gpu.global.b32 [%0], %1;" ::"l"(p), "r"(a) : "memory"); }
__device__ __forceinline__ void st2(uint32_t* p, uint32_t a, uint32_t b) {
    asm volatile("st.relaxed.gpu.global.v2.b32 [%0], {%1,%2};" ::"l"(p), "r"(a), "r"(b) : "memory");
}
__device__ __forceinline__ void zero4(uint32_t* p) { asm volatile("st.relaxed.gpu.global.v4.b32 [%0], {%1,%1,%1,%1};" ::"l"(p), "r"(0) : "memory"); }
__device__ __forceinline__ void put1d(uint32_t* p, uint32_t a) { a = nz(a), st1(p, a), st1(p + 1024, a); }
__device__ __forceinline__ void put2d(uint32_t* p, uint32_t a, uint32_t b) { a = nz(a), b = nz(b), st2(p, a, b), st2(p + 1024, a, b); }
__device__ __forceinline__ uint32_t ld1(const uint32_t* p) {
    uint32_t v;
    asm volatile("ld.relaxed.gpu.global.b32 %0, [%1];" : "=r"(v) : "l"(p) : "memory");
    return v;
}
template <int N, int V>
__device__ __forceinline__ void fetch(const uint32_t* p, int stride, uint32_t (&a)[N * V]) {
#pragma unroll
    for (int i = 0; i < N; i++) {
        if (V == 1)
            asm volatile("{\n.reg .pred p;\nsetp.eq.u32 p, %0, 0;\n@p ld.relaxed.gpu.global.b32 %0, [%1];\n}"
                         : "+r"(a[i]) : "l"(p + i * stride) : "memory");
        if (V == 4)
            asm volatile("{\n.reg .pred p;\nsetp.eq.u32 p, %4, 0;\n@p ld.relaxed.gpu.global.v4.b32 {%0,%1,%2,%3}, [%5];\n}"
                         : "+r"(a[V * i]), "+r"(a[V * i + V / 4]), "+r"(a[V * i + V / 2]), "+r"(a[V * i + V - 1])
                         : "r"(min(min(a[V * i], a[V * i + V / 4]), min(a[V * i + V / 2], a[V * i + V - 1]))), "l"(p + i * stride) : "memory");
    }
}
template <int N>
__device__ __forceinline__ bool missing(const uint32_t (&a)[N]) {
    uint32_t lo = a[0];
#pragma unroll
    for (int i = 1; i < N; i++) lo = min(lo, a[i]);
    return __any_sync(0xffffffffu, lo == 0);
}
template <int N, int V>
__device__ __forceinline__ void get(const uint32_t* p, int stride, uint32_t (&a)[N * V]) {
    int it = 0;
    do fetch<N, V>(p, stride, a);
    while (missing(a) & (++it < SPIN_LIMIT));
}
__device__ __forceinline__ void cp16(uint32_t dst, const void* src) {
    asm volatile("cp.async.cg.shared.global [%0], [%1], 16;" ::"r"(dst), "l"(src) : "memory");
}

__device__ __forceinline__ uint32_t pack2(float lo, float hi) {
    uint32_t r;
    asm("cvt.rn.bf16x2.f32 %0, %1, %2;" : "=r"(r) : "f"(hi), "f"(lo));
    return r;
}
__device__ __forceinline__ float rbf(float x) { return __uint_as_float(pack2(0.f, x)); }
__device__ __forceinline__ float blo(uint32_t v) { return __uint_as_float(v << 16); }
__device__ __forceinline__ float bhi(uint32_t v) { return __uint_as_float(v & 0xffff0000u); }
__device__ __forceinline__ uint32_t badd2(uint32_t a, uint32_t b) { uint32_t r; asm("add.rn.bf16x2 %0, %1, %2;" : "=r"(r) : "r"(a), "r"(b)); return r; }
__device__ __forceinline__ uint32_t bsub2(uint32_t a, uint32_t b) { uint32_t r; asm("sub.rn.bf16x2 %0, %1, %2;" : "=r"(r) : "r"(a), "r"(b)); return r; }
__device__ __forceinline__ uint32_t bmul2(uint32_t a, uint32_t b) { uint32_t r; asm("mul.rn.bf16x2 %0, %1, %2;" : "=r"(r) : "r"(a), "r"(b)); return r; }
__device__ __forceinline__ float ex2(float x) { float r; asm("ex2.approx.ftz.f32 %0, %1;" : "=f"(r) : "f"(x)); return r; }
__device__ __forceinline__ float rcp(float x) { float r; asm("rcp.approx.ftz.f32 %0, %1;" : "=f"(r) : "f"(x)); return r; }
__device__ __forceinline__ float sqrt_f(float x) { float r; asm("sqrt.approx.ftz.f32 %0, %1;" : "=f"(r) : "f"(x)); return r; }
constexpr float LOG2E = 1.4426950408889634f;
constexpr uint32_t ONE2 = 0x3f803f80u;
__device__ __forceinline__ float sigmoid_f(float x) { return rcp(1.0f + ex2(-LOG2E * x)); }
__device__ __forceinline__ uint32_t silu2(uint32_t v) {
    const float a = blo(v), b = bhi(v);
    return pack2(a * sigmoid_f(a), b * sigmoid_f(b));
}
__device__ __forceinline__ float quad_sum(float v) {
    v += __shfl_xor_sync(0xffffffffu, v, 1);
    return v + __shfl_xor_sync(0xffffffffu, v, 2);
}
__device__ __forceinline__ void ln_partial(const uint32_t (&v)[8], uint32_t dst, bool writer) {
    float s0 = 0.f, s1 = 0.f;
#pragma unroll
    for (int i = 0; i < 8; i++) {
        s0 += blo(v[i]);
        s1 += bhi(v[i]);
    }
    const float mean = quad_sum(s0 + s1) * (1.0f / 64);
    s0 = s1 = 0.f;
#pragma unroll
    for (int i = 0; i < 8; i++) {
        const float a = blo(v[i]) - mean, b = bhi(v[i]) - mean;
        s0 = fmaf(a, a, s0);
        s1 = fmaf(b, b, s1);
    }
    s0 = quad_sum(s0 + s1);
    if (writer) sts64(dst, __float_as_uint(mean), __float_as_uint(s0));
}
__device__ __forceinline__ void ln_combine(uint32_t src, uint32_t& mean2, float& inv) {
    float m[10], q0 = 0.f, q1 = 0.f, s = 0.f;
#pragma unroll
    for (int i = 0; i < 5; i++) {
        const uint4 v = lds128(src + i * 16);
        m[2 * i] = __uint_as_float(v.x);
        m[2 * i + 1] = __uint_as_float(v.z);
        q0 += __uint_as_float(v.y);
        if (i < 4) q1 += __uint_as_float(v.w);
    }
    const float mean = (((m[0] + m[1]) + (m[2] + m[3])) + ((m[4] + m[5]) + (m[6] + m[7])) + m[8]) * (1.0f / 9);
#pragma unroll
    for (int i = 0; i < 9; i++) s = fmaf(m[i] - mean, m[i] - mean, s);
    const float var = fmaf(s, 64.f, q0 + q1) * (1.0f / DM);
    mean2 = pack2(mean, mean);
    inv = rcp(rbf(sqrt_f(rbf(rbf(var) + 1e-5f))));
}
__device__ __forceinline__ uint32_t modulate2(uint32_t x, uint32_t mean2, float inv, uint32_t shift, uint32_t onep) {
    const uint32_t d = bsub2(x, mean2);
    return badd2(bmul2(pack2(blo(d) * inv, bhi(d) * inv), onep), shift);
}
template <int N>
__device__ __forceinline__ void sum_frags(float (&c)[4], uint32_t addr, int stride) {
#pragma unroll
    for (int w = 0; w < N; w++) {
        const uint4 v = lds128(addr + w * stride);
        c[0] += __uint_as_float(v.x); c[1] += __uint_as_float(v.y);
        c[2] += __uint_as_float(v.z); c[3] += __uint_as_float(v.w);
    }
}

template <int ST>
__device__ __forceinline__ void project(uint32_t sm, const uint32_t* src, uint32_t* dst, uint32_t rowoff, uint32_t reds, int nsync, int warp, int lane) {
    constexpr int NW = ST ? 9 : 8;
    const uint32_t red = sm + (ST ? OFF_WO : OFF_P);
    if (warp < NW) {
        const uint32_t wbar = sm + OFF_BAR + (ST ? BAR_WD + (warp < 8 ? ((warp >> 1) - WD_ROT) & 3 : 4) : BAR_WO + (warp >> 1)) * 8;
        const uint32_t ab = sm + (ST ? OFF_WD : OFF_WO) + rowoff;
        const uint32_t ax = sm + (ST ? OFF_DX : OFF_OX) + ((rowoff >> 7) << 4);
        uint32_t a[10][4] = {}, b[4] = {};
        bool have_w = false, need_b = true;
        int it = 0;
        do {
            if (!need_b) mbar_wait(wbar, 0);
            if (!need_b || (!have_w && __all_sync(0xffffffffu, mbar_test(wbar, 0)))) {
                have_w = true;
#pragma unroll
                for (int i = 0; i < 10; i++) ldsm4t(a[i], i % 5 < 4 ? (ab ^ ((i % 5) << 5)) + (i / 5) * 2048 : ax + (i / 5) * 256);
                if (!need_b) break;
            }
            if (ST) fetch<4, 1>(src, 32, b);
            else fetch<1, 4>(src, 0, b);
            need_b = missing(b) & (++it < SPIN_LIMIT);
        } while (need_b | !have_w);
        if (warp == 0) TSL(ST ? 24 : 21);
        float acc[5][4] = {};
#pragma unroll
        for (int i = 0; i < 10; i++) mma(acc[i % 5], a[i][0], a[i][1], a[i][2], a[i][3], b[2 * (i / 5)], b[2 * (i / 5) + 1]);
#pragma unroll
        for (int u = 0; u < 9; u++)
            sts64(red + u * 2304 + (reds & 0xffff), __float_as_uint(acc[u >> 1][2 * (u & 1)]), __float_as_uint(acc[u >> 1][2 * (u & 1) + 1]));
    }
    bar_sync(ST ? 6 : 3, nsync);
    float s[2][2] = {};
#pragma unroll
    for (int w = 0; w < NW; w++) {
        const float2 v = lds64f(red + (reds >> 16) + w * 256);
        s[w & 1][0] += v.x;
        s[w & 1][1] += v.y;
    }
    const uint32_t p0 = (__float_as_uint(s[0][0] + s[1][0]) | 1) ^ ST, p1 = (__float_as_uint(s[0][1] + s[1][1]) | 1) ^ ST;
    st2(dst, p0, p1), st2(dst + 1024, p0, p1);
}

template <int ST, typename F>
__device__ __forceinline__ uint32_t reduce16(const uint32_t* src, F arrived) {
    uint32_t a[32] = {}, bad[16], any;
    int it = 0;
#pragma unroll
    for (int i = 0; i < 16; i++) bad[i] = 1;
    do {
#pragma unroll
        for (int i = 0; i < 16; i++)
            asm volatile("{\n.reg .pred p;\nsetp.ne.u32 p, %2, 0;\n@p ld.relaxed.gpu.global.v2.b32 {%0,%1}, [%3];\n}"
                         : "+r"(a[2 * i]), "+r"(a[2 * i + 1]) : "r"(bad[i]), "l"(src + i * 64) : "memory");
#pragma unroll
        for (int i = 0; i < 16; i++) bad[i] = lop3<ST ? 0xa8 : 0x2a>(a[2 * i], a[2 * i + 1], 1);
        any = lop3<0xfe>(lop3<0xfe>(lop3<0xfe>(bad[0], bad[1], bad[2]), lop3<0xfe>(bad[3], bad[4], bad[5]), lop3<0xfe>(bad[6], bad[7], bad[8])),
                         lop3<0xfe>(lop3<0xfe>(bad[9], bad[10], bad[11]), lop3<0xfe>(bad[12], bad[13], bad[14]), bad[15]), 0);
    } while (__any_sync(0xffffffffu, any != 0) & (++it < SPIN_LIMIT));
    arrived();
    float f[8];
#pragma unroll
    for (int i = 0; i < 8; i++)
        f[i] = (__uint_as_float(a[i]) + __uint_as_float(a[i + 8])) + (__uint_as_float(a[i + 16]) + __uint_as_float(a[i + 24]));
    f[0] = (f[0] + f[2]) + (f[4] + f[6]);
    f[1] = (f[1] + f[3]) + (f[5] + f[7]);
    return movm(pack2(f[0], f[1]));
}

__global__ void __launch_bounds__(NTHREADS, 1) fused_kernel(const Params P, const __grid_constant__ Maps T) {
    extern __shared__ __align__(1024) char smem_raw[];
    constexpr uint32_t sm = 1024;
    const int tid = threadIdx.x, lane = tid & 31;
    const int cta = blockIdx.x, grp = cta >> 3, sub = cta & 7;
    const uint32_t bars = sm + OFF_BAR;
    const int row0 = (sub * HKV + grp) * SK + (SK - WIN);
    u64 pol;
    asm volatile("createpolicy.fractional.L2::evict_first.b64 %0, 1.0;" : "=l"(pol));
    if (tid == NCW * 32) {
        TS(0);
        const int n0 = cta < 90 ? 0 : 3;
#pragma unroll
        for (int i = 0; i < 6; i++) mbar_init(bars + i * 8, 1);
        asm volatile("fence.mbarrier_init.release.cluster;" ::: "memory");
#pragma unroll
        for (int i = 0; i < 3; i++) {
            mbar_expect(bars + (n0 + i) * 8, 12288);
            tma3d(sm + OFF_WM + (n0 + i) * 12288, &T.m[cta < 36 ? M_WA : cta < 90 ? M_WM : M_WQ], cta < 36 ? 16 * cta : 32 * cta,
                  i * 192, 0, bars + (n0 + i) * 8);
            TI(n0 + i);
        }
        TS(26);
    }
    if (tid == NCW * 32 + 32) {
#pragma unroll
        for (int i = 0; i < 4; i++) mbar_init(bars + (BAR_FULL + i) * 8, 1);
        asm volatile("fence.mbarrier_init.release.cluster;" ::: "memory");
#pragma unroll
        for (int t = 0; t < NK0; t++) {
            mbar_expect(bars + (BAR_FULL + t) * 8, TILE_BYTES);
            tma3d_hint(sm + OFF_RING + t * TILE_BYTES, &T.m[M_K], 0, row0 + t * 32, 0, bars + (BAR_FULL + t) * 8, pol);
            TI(6 + t);
        }
    }
    if (tid < 288 && cta < 90) {
#pragma unroll
        for (int i = 0; i < 2; i++) {
            const int row = (lane >> 3) + 4 * i, so = row * DM + (tid >> 5) * 64 + (lane & 7) * 8;
            const uint32_t d = sm + OFF_RED + (tid >> 5) * 2048 + row * 128 + (((lane & 7) ^ row) << 4);
            cp16(d, P.c + so);
            if (cta < 36) cp16(d + 1024, P.x + so);
        }
    }
    uint32_t* const g0 = P.scratch;
    const uint32_t epoch = ld1(g0 + G_EPOCH);
    const int warp = __shfl_sync(0xffffffffu, tid >> 5, 0);
    auto pace = [&](int t, int gain) {
        const int d = (int)atomicAdd(g0 + (epoch & 1) * G_SET + G_CNT, 1u) - 32 * (t - 16) - 16;
        sts32(sm + OFF_WIN, min(max((d * gain + 32) >> 6, W_MIN), W_MAX));
    };

    if (warp >= NCW) {
        const int pw = warp - NCW;
        bar_arrive(1, (NCW + 1) * 32);
        if (pw && lane < M_WQ) asm volatile("prefetch.tensormap [%0];" ::"l"(&T.m[M_WQ - lane]) : "memory");
        if (tid == NCW * 32) sts32(sm + OFF_WIN, 0);
        __syncwarp();
        bar_sync(15, NTHREADS);
        if (lane == 0) {
            if (pw == 0 && cta < 90) {
#pragma unroll 1
                for (int n = 3; n < 6; n++) {
                    mbar_expect(bars + n * 8, 12288);
                    mbar_wait(bars + (n - 3) * 8, 0);
                    tma3d(sm + OFF_WM + n * 12288, &T.m[M_WQ], 32 * cta, (n - 3) * 192, 0, bars + n * 8);
                    TI(n);
                }
            }
#pragma unroll 1
            for (int t = (2 - pw) * NK0; t < 2 * NK0 + 3 * (1 - pw); t++) {
                mbar_expect(bars + (BAR_FULL + t) * 8, TILE_BYTES);
                mbar_wait(bars + (t + (pw ? BAR_FULL - NK0 : 3 - 2 * NK0)) * 8, 0);
                tma3d_hint(sm + OFF_RING + t * TILE_BYTES, &T.m[M_K], 0, row0 + t * 32, 0, bars + (BAR_FULL + t) * 8, pol);
                TI(6 + t);
            }
            if (pw == 0) {
#pragma unroll 1
                for (int t = 2 * NK0 + 3; t < 2 * NT; t++) {
                    if (t == 14 && cta < 90) mbar_wait(bars + BAR_WMF * 8, 0);
                    if (t == 15) TS(30);
                    const int m = t - ((W_KV + (int)lds32(sm + OFF_WIN) + ((0xd8 >> (2 * t & 6)) & 3)) >> 2);
                    const uint32_t fb = bars + (BAR_FULL + (t & 15)) * 8;
                    mbar_wait(fb + (BAR_EMPTY - BAR_FULL) * 8, (~t >> 4) & 1);
                    mbar_expect(fb, TILE_BYTES);
                    mbar_wait(bars + (BAR_FULL + (m & 15)) * 8, (m >> 4) & 1);
                    tma3d_hint(sm + OFF_RING + (t & 15) * TILE_BYTES, &T.m[t >> 6], 0, row0 + (t & (NT - 1)) * 32, 0, fb, pol);
                    TI(6 + t);
                    if (t == T_CLEAR) mbar_arrive(bars + (BAR_SYNC + 1) * 8);
                }
                mbar_arrive(bars + (BAR_SYNC + 2) * 8);
                mbar_wait(bars + BAR_SYNC * 8, 0);
                auto window = [&](int b, int w) {
                    b -= max((w + (int)lds32(sm + OFF_WIN) + ((0xd8 >> (2 * b & 6)) & 3)) >> 2, 1);
                    b = min(b, BAR_GU + B_CAP);
                    mbar_wait(bars + b * 8, b < BAR_WO);
                };
#pragma unroll 1
                for (int i = 0; i < 4; i++) {
                    window(BAR_WO + i, W_WO);
                    tma3d(sm + OFF_WO + i * 8192, &T.m[M_OD], 64 * sub, grp * 256 + i * 64, P.zo, bars + (BAR_WO + i) * 8);
                    tma3d(sm + OFF_OX + i * 1024, &T.m[M_OX], 512 + 8 * sub, grp * 256 + i * 64, P.zo, bars + (BAR_WO + i) * 8);
                    TI(134 + i);
                }
                TS(28);
#pragma unroll 1
                for (int i = 0; i < 9; i++) {
                    mbar_wait(bars + (BAR_EMPTY + i) * 8, 1);
                    window(BAR_GU + i, sub < 4 ? W_GU : W_GU2);
                    tma3d(sm + OFF_GU + i * 8192, &T.m[M_GU], grp * 288 + 32 * sub, i * 64, 0, bars + (BAR_GU + i) * 8);
                    if (sub < 4) tma3d(sm + OFF_GX + i * 2048, &T.m[M_GX], grp * 288 + 256 + 8 * sub, i * 64, 0, bars + (BAR_GU + i) * 8);
                    TI(138 + i);
                }
                TS(29);
#pragma unroll 1
                for (int i = 0; i < 5; i++) {
                    const int blk = i < 4 ? (i + WD_ROT) & 3 : 4, r = min(blk * 64, 224);
                    mbar_wait(bars + (BAR_EMPTY + 9 + blk) * 8, 1);
                    window(BAR_WD + i, W_WD);
                    tma3d(sm + OFF_WD + r * 128, &T.m[M_OD], 64 * sub, grp * 288 + r, P.zo ^ 1, bars + (BAR_WD + i) * 8);
                    tma3d(sm + OFF_DX + r * 16, &T.m[M_OX], 512 + 8 * sub, grp * 288 + r, P.zo ^ 1, bars + (BAR_WD + i) * 8);
                    TI(147 + i);
                }
                if (cta < 72) {
                    mbar_wait(bars + (BAR_EMPTY + 14) * 8, 1);
                    mbar_wait(bars + (BAR_EMPTY + 15) * 8, 1);
                    mbar_expect(bars + BAR_GB * 8, 9216);
                    mbar_wait(bars + (BAR_WD + GB_AT) * 8, 0);
#pragma unroll
                    for (int i = 0; i < 3; i++) tma3d(sm + OFF_GB + i * 3072, &T.m[M_GB], 5 * DM + 8 * cta, i * 192, 0, bars + BAR_GB * 8);
                }
            } else {
#pragma unroll 1
                for (int i = BAR_WO; i < BAR_WD + 5; i++) mbar_expect(bars + i * 8, i < BAR_GU || i >= BAR_WD ? 9216 : sub < 4 ? 10240 : 8192);
                mbar_arrive(bars + BAR_SYNC * 8);
                mbar_wait(bars + (BAR_SYNC + 2) * 8, 0);
#pragma unroll 1
                for (int t = 124 + (cta & 3); t < 144; t += 4) {
                    mbar_wait(bars + (BAR_FULL - 112 + t) * 8, t < 128);
                    pace(t, GAIN_TAIL);
                }
            }
        }
        return;
    }

    if (lane == 0) {
#pragma unroll
        for (int i = 0; i < 6; i++) mbar_init(bars + (10 + warp * 6 + i) * 8, 1);
        asm volatile("fence.mbarrier_init.release.cluster;" ::: "memory");
    }
    __syncwarp();
    if (warp < 9) bar_arrive(15, NTHREADS);
    const int g = lane >> 2, t4 = lane & 3;
    uint32_t* const gs = g0 + (epoch & 1) * G_SET;

    uint32_t sc[8] = {};
    if (warp < 9) {
        const int off_h = (cta < 36 ? dual(D_H + 2 * cta * 32) : G_M + 4 * (cta - 36) * 32) + tid;
        const int off_h2 = off_h + (cta < 36 ? 1024 : 64);
        const int off_q = dual(D_Q + g * (HQ * 64) + cta * 16) + warp * 8 + t4 * 2;
        uint32_t bf[8] = {}, xp = 0, mean2 = 0;
        float inv = 0.f;
        if (cta < 36) xp = __ldg(reinterpret_cast<const uint32_t*>(P.x) + g * (DM / 2) + 8 * cta + 4 * (warp & 1) + t4);
        if (warp < 2) {
            st2(gs + off_q, 0, 0), st2(gs + off_q + 1024, 0, 0);
            if (cta < 36) st1(gs + off_h, 0), st1(gs + off_h2, 0);
        }
        if (cta < 90) {
            asm volatile("cp.async.wait_all;" ::: "memory");
            __syncwarp();
            const uint32_t fa = sm + OFF_RED + warp * 2048 + (lane & 7) * 128 + (((lane >> 3) ^ (lane & 7)) << 4);
            ldsm4(reinterpret_cast<uint32_t(&)[4]>(bf[0]), fa);
            ldsm4(reinterpret_cast<uint32_t(&)[4]>(bf[4]), fa ^ 64);
            if (cta < 36) {
                uint32_t xv[8];
                ldsm4(reinterpret_cast<uint32_t(&)[4]>(xv[0]), fa + 1024);
                ldsm4(reinterpret_cast<uint32_t(&)[4]>(xv[4]), (fa ^ 64) + 1024);
                ln_partial(xv, sm + OFF_ST + g * 80 + warp * 8, t4 == 0);
            }
#pragma unroll
            for (int i = 0; i < 8; i++) sc[i] = bf[i] = silu2(bf[i]);
        }
        if (warp == 0) TSL(18);
        bar_sync(1, (NCW + 1) * 32);
        if (cta < 36 && warp < 2) ln_combine(sm + OFF_ST + g * 80, mean2, inv);
        const int r = warp * 64 + (lane >> 4) * 8 + (lane & 7), hi8 = (lane >> 3) & 1, box = warp / 3;
#pragma unroll 1
        for (int pass = cta < 90 ? 0 : 1; pass < 2; pass++) {
            const bool pa = pass == 0 && cta < 36;
            const uint32_t ab = sm + OFF_WM + pass * 36864 +
                                (pa ? (box + hi8) * 6144 + r * 32 + ((lane & 4) << 2) : r * 64 + (((2 * hi8) ^ ((r >> 1) & 3)) << 4));
            const uint32_t as = pa ? 512 : 1024, red = sm + OFF_RED + pass * 9216;
            mbar_wait(bars + (pass * 3 + box) * 8, 0);
            if (warp == 8) TSL(pass ? 31 : 19);
            uint32_t a[4][2][4];
#pragma unroll
            for (int i = 0; i < 4; i++) {
                ldsm4t(a[i][0], ab + i * as);
                ldsm4t(a[i][1], (ab ^ 16) + i * as);
            }
            if (pass) {
                bar_sync(8, NCW * 32);
#pragma unroll
                for (int i = 0; i < 8; i++) bf[i] = 0;
                get<8, 1>(gs + near(D_H + warp * 256, lds32(sm + OFF_WIN + 4)) + lane, 32, bf);
                if (warp == 0) TSL(3);
            }
            float acc[2][4] = {};
#pragma unroll
            for (int i = 0; i < 4; i++)
#pragma unroll
                for (int m = 0; m < 2; m++) mma(acc[m], a[i][m][0], a[i][m][1], a[i][m][2], a[i][m][3], bf[2 * i], bf[2 * i + 1]);
            sts128f(red + tid * 16, acc[0]);
            sts128f(red + 4608 + tid * 16, acc[1]);
            bar_sync(3, 288);
            if (warp < 2) {
                float c[4] = {};
                sum_frags<9>(c, red + warp * 4608 + lane * 16, 512);
                uint32_t lo = movm(pack2(c[0], c[1])), hi = movm(pack2(c[2], c[3]));
                if (pass) {
                    put2d(gs + off_q, lo, hi);
                    if (warp == 0) TSL(4);
                } else {
                    const uint32_t hi1 = badd2(hi, ONE2);
                    if (pa) hi = lo = modulate2(xp, mean2, inv, lo, hi1);
                    if (cta >= 72) lo = badd2(lo, ONE2), hi = hi1;
                    st1(gs + off_h, nz(lo));
                    st1(gs + off_h2, nz(hi));
                    if (warp == 0 && pa) TSL(2);
                }
            } else if (tid == 64 && pass == 0) {
                mbar_arrive(bars + BAR_WMF * 8);
            }
        }
    } else {
        if ((uint32_t)__cvta_generic_to_shared(smem_raw) != sm) __trap();
        uint32_t* const ping = g0 + dual(D_PING) + cta * 8;
        if (lane < 16) st1(ping + (lane >> 3) * 1024 + (lane & 7), 0);
        bar_sync(15, NTHREADS);
        uint32_t best[2] = {~0u, ~0u}, v = 0;
#pragma unroll 1
        for (int part = 0; part < 2; part++) {
            if (lane == 0) {
#pragma unroll 1
                for (int r = part ? NPING1 : NPING0; r > 0; r--) {
#pragma unroll
                    for (int k = 0; k < 2; k++) {
                        const uint32_t t0 = clock32(v);
                        v = atomicExch(ping + k * 1024, t0);
                        best[k] = min(best[k], clock32(v) - t0);
                    }
                }
                sts32(sm + OFF_WIN + 4 + 4 * part, ((best[1] < best[0]) ^ __popc(D_PING & 0x16400)) & 1);
            }
            __syncwarp();
            if (part) break;
            TSL(20);
            bar_arrive(8, NCW * 32);
            mbar_wait(bars + 5 * 8, 0);
            uint32_t a[4] = {};
            get<1, 4>(gs + near(D_Q + (sub * HQ + 2 * grp) * 64, lds32(sm + OFF_WIN + 4)) + lane * 4, 0, a);
            sts128(sm + OFF_QS + lane * 16, a[0], a[1], a[2], a[3]);
            __syncwarp();
            TSL(5);
            bar_arrive(4, 288);
        }
#pragma unroll
        for (int i = lane; i < 72; i += 32) cp16(sm + OFF_WR + i * 16, P.wr + i * 8);
        asm volatile("cp.async.wait_all;" ::: "memory");
        __syncwarp();
        bar_arrive(2, NCW * 32);
        if (cta == 0 && lane == 0) st1(g0 + (~epoch & 1) * G_SET + G_CNT, 0);
        mbar_wait(bars + (BAR_SYNC + 1) * 8, 0);
#pragma unroll 1
        for (int c = 0; c < 4; c++) {
            uint32_t* const pg = g0 + (c >> 1) * G_SET + (c & 1) * 1024;
            zero4(pg + dual(D_O + cta * 128) + lane * 4);
            zero4(pg + dual(D_ACT + (grp * 36 + 4 * sub) * 32) + lane * 4);
            if (lane < 8 ? sub < 4 : lane < 16 && cta < 72)
                zero4(pg + dual(lane < 8 ? D_ACT + (grp * 36 + 32 + sub) * 32 : D_X1 + cta * 32) + (lane & 7) * 4);
        }
#pragma unroll 1
        for (int u = 0; u < 9; u++) zero4(g0 + dual(d_part(u < 8 ? 8 * sub + u : 64 + sub)) + (lane >> 4) * 1024 + grp * 64 + (lane & 15) * 4);
        {
            uint32_t* const nx = g0 + (~epoch & 1) * G_SET;
            uint32_t* const q = nx + dual(D_Q + g * (HQ * 64) + cta * 16) + t4 * 4;
            zero4(q), zero4(q + 1024);
            if (cta < 90) zero4(nx + (cta < 36 ? dual(D_H + 2 * cta * 32) + (lane >> 4) * (1024 - 64) : G_M + 4 * (cta - 36) * 32) + lane * 4);
        }
        if (cta >= 72) {
            bar_arrive(5, NCW * 32);
            return;
        }
        const uint32_t io = pin(4 * (g * (DM / 2) + 4 * cta + t4));
        uint32_t x = __ldg(at(reinterpret_cast<const uint32_t*>(P.x), io)), ga[1] = {};
        get<1, 1>(gs + G_M + cta * 32 + lane, 0, ga);
        const uint32_t src_p = pin(4 * (near(d_part(cta), lds32(sm + OFF_WIN + 8)) + lane * 2));
        const uint32_t dst_x = pin(4 * ((epoch & 1) * G_SET + dual(D_X1 + cta * 32) + lane));
        bar_sync(5, NCW * 32);
        x = badd2(x, bmul2(ga[0], reduce16<0>(at(g0, src_p), [] {})));
        put1d(at(g0, dst_x), x);
        TSL(10);
        bar_sync(6, NCW * 32);
        const uint4 r0 = lds128(sm + OFF_RT + g * 48), r1 = lds128(sm + OFF_RT + g * 48 + 16);
        float r = __uint_as_float(lds32(sm + OFF_RT + g * 48 + 32));
        r += ((__uint_as_float(r0.x) + __uint_as_float(r0.y)) + (__uint_as_float(r0.z) + __uint_as_float(r0.w))) +
             ((__uint_as_float(r1.x) + __uint_as_float(r1.y)) + (__uint_as_float(r1.z) + __uint_as_float(r1.w)));
        r = sigmoid_f(rbf(r));
        const uint32_t h = lds32(sm + OFF_HU + lane * 4), rs = pack2(r, r);
        uint32_t gb;
        const uint32_t y = reduce16<1>(at(g0, src_p), [&] {
            bar_sync(9, 64);
            gb = lds32(sm + OFF_QS + lane * 4);
        });
        *at(reinterpret_cast<uint32_t*>(P.out), io) = badd2(x, bmul2(gb, badd2(h, bmul2(y, rs))));
        if (cta == 0 && lane == 0) g0[G_EPOCH] = epoch + 1;
        TSL(15);
        return;
    }

    const uint32_t tile = sm + OFF_RING + warp * TILE_BYTES;
    const uint32_t fullb = bars + (BAR_FULL + warp) * 8;
    const uint32_t pw = sm + OFF_P + warp * (2 * P_PITCH);
    const bool pacer = (tid & 127) == (cta & 3) * 32;
    if (warp < 8) {
        {
            uint32_t q0[8], q1[8];
            bar_sync(4, 288);
#pragma unroll
            for (int i = 0; i < 8; i++) {
                const float2 v = lds64f(sm + OFF_QS + (g & 1) * 256 + i * 32 + t4 * 8);
                q0[i] = __float_as_uint(v.x), q1[i] = __float_as_uint(v.y);
            }
            uint32_t sp = pw + (t4 & 1) * P_PITCH + ((t4 >> 1) * 8 + g) * 2;
#pragma unroll 1
            for (int it = 0; it < 8; it++, sp += 64) {
                const uint32_t ab = tile + (it & 1) * (8 * TILE_BYTES) + (lane & 15) * 128 + (((lane >> 4) ^ (lane & 7)) << 4);
                mbar_wait(fullb + (it & 1) * 64, (it >> 1) & 1);
                float acc[2][2][4] = {};
#pragma unroll
                for (int ks = 0; ks < 8; ks++)
#pragma unroll
                    for (int m = 0; m < 2; m++) {
                        uint32_t a[4];
                        ldsm4(a, (ab ^ ((ks & 3) << 5)) + (ks >> 2) * 4096 + m * 2048);
                        mma(acc[m][ks & 1], a[0], a[1], a[2], a[3], (ks & 1) ? q1[ks - 1] : q0[ks], (ks & 1) ? q1[ks] : q0[ks + 1]);
                    }
                __syncwarp();
                if (lane == 0) mbar_arrive(fullb + (it & 1) * 64 + (BAR_EMPTY - BAR_FULL) * 8);
#pragma unroll
                for (int m = 0; m < 2; m++) {
                    const float s = sel4(acc[m][0], t4) + sel4(acc[m][1], t4);
                    sts16(sp + m * 32, (uint16_t)pack2(rbf(s) * 0.08838834764831845f, 0.f));
                }
                if (pacer && it >= 2) pace(it * 8 + warp, GAIN_KV);
                __syncwarp();
            }
        }
        __syncwarp();
        if (warp == 7) TSL(6);
        const uint32_t pa = pw + (lane >> 4) * P_PITCH + (lane & 15) * 32;
        const uint32_t sa = sm + OFF_SM + (lane >> 4) * 64;
        const uint4 v0 = lds128(pa), v1 = lds128(pa + 16);
        const uint32_t sv[8] = {v0.x, v0.y, v0.z, v0.w, v1.x, v1.y, v1.z, v1.w};
        float e[16];
        float m = -INFINITY;
#pragma unroll
        for (int i = 0; i < 8; i++) {
            e[2 * i] = blo(sv[i]);
            e[2 * i + 1] = bhi(sv[i]);
            m = fmaxf(m, fmaxf(e[2 * i], e[2 * i + 1]));
        }
#pragma unroll
        for (int o = 8; o; o >>= 1) m = fmaxf(m, __shfl_xor_sync(0xffffffffu, m, o));
        float l = 0.f;
#pragma unroll
        for (int i = 0; i < 16; i++) {
            e[i] = ex2((e[i] - m) * LOG2E);
            l += e[i];
        }
#pragma unroll
        for (int o = 8; o; o >>= 1) l += __shfl_xor_sync(0xffffffffu, l, o);
        if ((lane & 15) == 0) sts64(sa + warp * 8, __float_as_uint(m), __float_as_uint(l));
        bar_sync(2, NCW * 32);
        const float2 v = lds64f(sa + (lane & 7) * 8);
        float M = v.x;
#pragma unroll
        for (int o = 4; o; o >>= 1) M = fmaxf(M, __shfl_xor_sync(0xffffffffu, M, o));
        float L = v.y * ex2((v.x - M) * LOG2E);
#pragma unroll
        for (int o = 4; o; o >>= 1) L += __shfl_xor_sync(0xffffffffu, L, o);
        const float sc = ex2((m - M) * LOG2E) * rcp(L);
        sts128(pa, pack2(e[0] * sc, e[1] * sc), pack2(e[2] * sc, e[3] * sc), pack2(e[4] * sc, e[5] * sc), pack2(e[6] * sc, e[7] * sc));
        sts128(pa + 16, pack2(e[8] * sc, e[9] * sc), pack2(e[10] * sc, e[11] * sc), pack2(e[12] * sc, e[13] * sc), pack2(e[14] * sc, e[15] * sc));
        __syncwarp();
    } else {
        bar_sync(2, NCW * 32);
    }

    uint32_t sh[8] = {}, op[8] = {};
    {
        const uint32_t* const src_m = gs + G_M + (72 + warp * 8) * 32 + lane;
        fetch<8, 1>(src_m + 72 * 32, 32, op);
        get<8, 1>(src_m, 32, sh);
        get<8, 1>(src_m + 72 * 32, 32, op);
    }
    const int side = lds32(sm + OFF_WIN + 8), set = (epoch & 1) * G_SET, rr = (lane >> 4) * 8 + (lane & 7);
    const uint32_t dst_o = pin(4 * (set + dual(D_O + cta * 128) + (tid & 0x70) + (tid & 3) * 4 + ((tid >> 2) & 3)));
    const uint32_t src_o = pin(4 * (set + near(D_O + grp * 1024, side) + g * 128 + warp * 16 + t4 * 4));
    const uint32_t dst_p = pin(4 * (dual(d_part(warp < 8 ? 8 * sub + warp : 64 + sub)) + grp * 64 + lane * 2));
    const uint32_t src_x = pin(4 * (set + near(D_X1 + warp * 256, side) + lane));
    const uint32_t dst_a = pin(4 * (set + dual(D_ACT + (grp * 36 + (warp < 4 ? 4 * sub + warp : 32 + sub)) * 32) + lane));
    const uint32_t src_a = pin(4 * (set + near(D_ACT + (grp * 36 + 4 * warp) * 32, side) + lane));
    const uint32_t rowoff = pin((warp * 32 + rr) * 128 + ((((lane >> 3) & 1) ^ (lane & 7)) << 4));
    const uint32_t reds = pin((tid * 8) | (warp * 2304 + lane * 8) << 16);
    const uint32_t ored = pin((warp * 1088 + (t4 & 1) * 576 + ((t4 >> 1) * 8 + g) * 4) | ((tid >> 6) * 64 + tid * 8) << 16);

    if (warp < 8) {
        float acc[8][4] = {};
        uint32_t pp = pw + (lane & 1) * P_PITCH + (lane >> 3) * 16;
#pragma unroll 1
        for (int it = 0; it < 8; it++, pp += 64) {
            const uint32_t ab = tile + (it & 1) * (8 * TILE_BYTES) + ((lane & 7) + (lane >> 4) * 8) * 128 + ((((lane >> 3) & 1) ^ (lane & 7)) << 4);
            uint32_t pb[4];
            ldsm4(pb, pp);
            mbar_wait(fullb + (it & 1) * 64, (it >> 1) & 1);
#pragma unroll
            for (int ks = 0; ks < 2; ks++)
#pragma unroll
                for (int m = 0; m < 8; m++) {
                    uint32_t a[4];
                    ldsm4t(a, (ab ^ ((m & 3) << 5)) + (m >> 2) * 4096 + ks * 2048);
                    mma(acc[m], a[0], a[1], a[2], a[3], pb[2 * ks], pb[2 * ks + 1]);
                }
            __syncwarp();
            if (lane == 0) mbar_arrive(fullb + (it & 1) * 64 + (BAR_EMPTY - BAR_FULL) * 8);
            if (pacer && it * 8 + warp < NT - 4) pace(NT + it * 8 + warp, GAIN_KV);
            __syncwarp();
        }
        if (warp == 7) TSL(7);
        const uint32_t ra = sm + OFF_ORED + (ored & 0xffff);
#pragma unroll
        for (int m = 0; m < 8; m++) sts32(ra + m * 64, __float_as_uint(sel4(acc[m], t4)));
    }
    bar_sync(5, NCW * 32);
    if (warp < 4) {
        float s[2][2] = {};
#pragma unroll
        for (int w = 0; w < 8; w++) {
            const float2 v = lds64f(sm + OFF_ORED + w * 1088 + (ored >> 16));
            s[w & 1][0] += v.x;
            s[w & 1][1] += v.y;
        }
        put1d(at(g0, dst_o), pack2(s[0][0] + s[1][0], s[0][1] + s[1][1]));
        if (warp == 0) TSL(8);
    }

    project<0>(sm, at(g0, src_o), at(g0, dst_p), rowoff, reds, 288, warp, lane);
    if (warp == 0) TSL(9);

    const uint32_t gbar = bars + (BAR_GU + warp) * 8;
    const int pl = ((lane >> 3) & 1) ^ P.zg;
    const uint32_t ab = sm + OFF_GU + warp * 8192 + pl * 4096 + rr * 64 + ((lane & 6) << 3);
    const uint32_t ax = sm + OFF_GX + warp * 2048 + pl * 1024 + rr * 16;
    uint32_t a[20][4] = {}, h[8] = {};
    auto load_gu = [&]() {
#pragma unroll
        for (int i = 0; i < 20; i++) ldsm4t(a[i], i % 5 < 4 ? (ab ^ ((i % 5) << 4)) + (i / 5) * 1024 : ax + (i / 5) * 256);
    };
    bool gpre = false;
    {
        int it = 0;
        do {
            if (!gpre && __all_sync(0xffffffffu, mbar_test(gbar, 0))) gpre = true, load_gu();
            fetch<8, 1>(at(g0, src_x), 32, h);
        } while (missing(h) & (++it < SPIN_LIMIT));
    }
    if (warp == 0) TSL(11);
    ln_partial(h, sm + OFF_ST + g * 80 + warp * 8, t4 == 0);
    bar_sync(3, 288);
    {
        uint32_t mean2;
        float inv;
        ln_combine(sm + OFF_ST + g * 80, mean2, inv);
#pragma unroll
        for (int i = 0; i < 8; i++) h[i] = modulate2(h[i], mean2, inv, sh[i], op[i]);
    }
    if (warp == 0) TSL(12);
    if (!gpre) {
        mbar_wait(gbar, 0);
        load_gu();
    }
    if (warp == 8) TSL(17);
    {
        float acc[5][4] = {};
#pragma unroll
        for (int i = 0; i < 20; i++) mma(acc[i % 5], a[i][0], a[i][1], a[i][2], a[i][3], h[2 * (i / 5)], h[2 * (i / 5) + 1]);
#pragma unroll
        for (int m = 0; m < 5; m++) sts128f(sm + OFF_RED + m * 4608 + 2 * (reds & 0xffff), acc[m]);
    }
    bar_sync(3, 288);
    if (warp < 5) {
        float c[4] = {};
        sum_frags<9>(c, sm + OFF_RED + 2 * (reds >> 16), 512);
        const uint32_t w = movm(bmul2(silu2(pack2(c[0], c[1])), pack2(c[2], c[3])));
        if (warp < 4 || sub < 4) put1d(at(g0, dst_a), w);
        if (warp == 1) TSL(13);
    }
    if (cta < 72) {
        float r = 0.f;
#pragma unroll
        for (int i = 0; i < 8; i++) {
            const uint32_t wr = lds32(sm + OFF_WR + (warp * 32 + i * 4 + t4) * 4);
            r = fmaf(blo(h[i]), blo(wr), fmaf(bhi(h[i]), bhi(wr), r));
            if (warp * 8 + i == cta) sts32(sm + OFF_HU + lane * 4, h[i]);
        }
        r = quad_sum(r);
        if (t4 == 0) sts32(sm + OFF_RT + g * 48 + warp * 4, __float_as_uint(r));
    }

    project<1>(sm, at(g0, src_a), at(g0, dst_p), rowoff, reds, cta < 72 ? 320 : 288, warp, lane);
    if (warp == 0) TSL(14);

    if (cta < 72) {
        const uint32_t ga = sm + OFF_GB + warp * 1024 + ((lane >> 3) & 1) * 256 + (lane >> 4) * 128 + (lane & 7) * 16;
        float acc[2][4] = {};
        mbar_wait(bars + BAR_GB * 8, 0);
        if (warp == 0) TSL(22);
#pragma unroll
        for (int i = 0; i < 2; i++) {
            uint32_t w[4];
            ldsm4t(w, ga + i * 512);
            mma(acc[0], w[0], w[1], w[2], w[3], sc[4 * i], sc[4 * i + 1]);
            mma(acc[1], w[0], w[1], w[2], w[3], sc[4 * i + 2], sc[4 * i + 3]);
        }
        sts64(sm + OFF_RED + (reds & 0xffff), __float_as_uint(acc[0][0] + acc[1][2]), __float_as_uint(acc[0][1] + acc[1][3]));
        if (warp) {
            bar_arrive(7, 288);
        } else {
            bar_sync(7, 288);
            float s[2][2] = {};
#pragma unroll
            for (int w = 0; w < 9; w++) {
                const float2 v = lds64f(sm + OFF_RED + (reds & 0xffff) + w * 256);
                s[w & 1][0] += v.x;
                s[w & 1][1] += v.y;
            }
            sts32(sm + OFF_QS + lane * 4, movm(pack2(s[0][0] + s[1][0], s[0][1] + s[1][1])));
            __syncwarp();
            bar_arrive(9, 64);
        }
    }
}

typedef CUresult (*EncodeFn)(CUtensorMap*, CUtensorMapDataType, cuuint32_t, void*, const cuuint64_t*, const cuuint64_t*,
                             const cuuint32_t*, const cuuint32_t*, CUtensorMapInterleave, CUtensorMapSwizzle,
                             CUtensorMapL2promotion, CUtensorMapFloatOOBfill);

void make_map(EncodeFn enc, CUtensorMap* m, void* p, int cols, int rows, int pitch, int bc, int br, int bp, int planes, size_t pstride,
              CUtensorMapSwizzle sw, int promo) {
    cuuint64_t dims[3] = {(cuuint64_t)cols, (cuuint64_t)rows, (cuuint64_t)planes};
    cuuint64_t strides[2] = {(cuuint64_t)pitch * 2, (cuuint64_t)pstride};
    cuuint32_t box[3] = {(cuuint32_t)bc, (cuuint32_t)br, (cuuint32_t)bp};
    cuuint32_t es[3] = {1, 1, 1};
    enc(m, CU_TENSOR_MAP_DATA_TYPE_BFLOAT16, 3, p, dims, strides, box, es, CU_TENSOR_MAP_INTERLEAVE_NONE, sw,
        (CUtensorMapL2promotion)promo, CU_TENSOR_MAP_FLOAT_OOB_FILL_NONE);
}

}

extern "C" void kernel_launch(void* const* d_in, const int* in_sizes, int n_in, void* d_out, int out_size) {
    static EncodeFn enc = nullptr;
    static uint32_t* scratch = nullptr;
    if (!enc) {
        void* fn = nullptr;
        cudaDriverEntryPointQueryResult st;
        cudaGetDriverEntryPoint("cuTensorMapEncodeTiled", &fn, cudaEnableDefault, &st);
        enc = (EncodeFn)fn;
        cudaGetSymbolAddress(&fn, g_scratch);
        scratch = (uint32_t*)(((uintptr_t)fn + 8 * G_SET - 1) & ~(uintptr_t)(8 * G_SET - 1));
        cudaFuncSetAttribute(fused_kernel, cudaFuncAttributeMaxDynamicSharedMemorySize, SMEM_BYTES);
    }
    Params P;
    Maps T;
    const CUtensorMapSwizzle none = CU_TENSOR_MAP_SWIZZLE_NONE;
    make_map(enc, &T.m[M_K], d_in[1], 64, NB * HKV * SK, DH, 64, 32, 2, 2, 128, CU_TENSOR_MAP_SWIZZLE_128B, PROMO_KV);
    make_map(enc, &T.m[M_V], d_in[2], 64, NB * HKV * SK, DH, 64, 32, 2, 2, 128, CU_TENSOR_MAP_SWIZZLE_128B, PROMO_KV);
    make_map(enc, &T.m[M_WQ], d_in[3], HQ * DH, DM, HQ * DH, 32, 192, 1, 1, 16, CU_TENSOR_MAP_SWIZZLE_64B, PROMO_W);
    make_map(enc, &T.m[M_WM], d_in[11], 6 * DM, DM, 6 * DM, 32, 192, 1, 1, 16, CU_TENSOR_MAP_SWIZZLE_64B, PROMO_W);
    make_map(enc, &T.m[M_WA], d_in[11], DM, DM, 6 * DM, 16, 192, 2, 2, DM * 2, CU_TENSOR_MAP_SWIZZLE_32B, PROMO_W);
    make_map(enc, &T.m[M_GB], d_in[11], 6 * DM, DM, 6 * DM, 8, 192, 1, 1, 16, none, PROMO_W);
    char *wg = (char*)d_in[7], *wu = (char*)d_in[8], *wo = (char*)d_in[4], *wd = (char*)d_in[9];
    P.zg = wg > wu;
    P.zo = wo > wd;
    const size_t sg = P.zg ? wg - wu : wu - wg, so = P.zo ? wo - wd : wd - wo;
    make_map(enc, &T.m[M_GU], P.zg ? wu : wg, FF, DM, FF, 32, 64, 2, 2, sg, CU_TENSOR_MAP_SWIZZLE_64B, PROMO_GU);
    make_map(enc, &T.m[M_GX], P.zg ? wu : wg, FF, DM, FF, 8, 64, 2, 2, sg, none, PROMO_GX);
    make_map(enc, &T.m[M_OD], P.zo ? wd : wo, DM, FF, DM, 64, 64, 1, 2, so, CU_TENSOR_MAP_SWIZZLE_128B, PROMO_W);
    make_map(enc, &T.m[M_OX], P.zo ? wd : wo, DM, FF, DM, 8, 64, 1, 2, so, none, PROMO_OX);
    P.x = (const __nv_bfloat16*)d_in[0];
    P.wr = (const __nv_bfloat16*)d_in[6];
    P.c = (const __nv_bfloat16*)d_in[10];
    P.out = (__nv_bfloat16*)d_out;
    P.scratch = scratch;
    fused_kernel<<<NCTA, NTHREADS, SMEM_BYTES>>>(P, T);
}
```

```cpp
#include <cuda_runtime.h>
#include <cuda_bf16.h>
#include <cuda.h>
#include <stdint.h>

typedef unsigned long long u64;

#define W_KV 21
#define W_WO 19
#define W_GU 19
#define W_GU2 W_GU
#define W_WD 14
#define W_MIN -6
#define W_MAX 8
#define GAIN_KV 2
#define GAIN_TAIL 3
#define NK0 3
#define T_CLEAR 116
#define B_CAP 8
#define GB_AT 2
#define PFK 2
#define NK1 2
#define WD_ROT 3
#define NPING0 4
#define NPING1 16
#define PROMO_W CU_TENSOR_MAP_L2_PROMOTION_L2_128B
#define PROMO_GX 2
#define PROMO_OX 2
#define PROMO_GU 2
#define PROMO_KV CU_TENSOR_MAP_L2_PROMOTION_L2_256B

namespace {

constexpr int NB = 8, DM = 576, HQ = 32, HKV = 16, SK = 8192, WIN = 2048, DH = 128, FF = 4608;
constexpr int NCTA = 128;
constexpr int NCW = 10;
constexpr int NTHREADS = (NCW + 2) * 32;
constexpr int TILE_BYTES = 8192, NSLOT = 16, NT = 64;
constexpr int SPIN_LIMIT = 1 << 22;

constexpr int OFF_RING = 0;
constexpr int OFF_WM = 121856;
constexpr int OFF_WQ = OFF_WM + 36864;
constexpr int OFF_GU = 0;
constexpr int OFF_WD = 73728;
constexpr int OFF_GB = 114688;
constexpr int OFF_OX = 131072;
constexpr int OFF_DX = OFF_OX + 4096;
constexpr int OFF_GX = OFF_DX + 4608;
constexpr int OFF_WO = OFF_WQ;
constexpr int OFF_P = OFF_WQ + 36864;
constexpr int P_PITCH = 528;
constexpr int OFF_RED = OFF_P + 16 * P_PITCH;
constexpr int OFF_ORED = OFF_RED + 5 * 4608 - 8704;
constexpr int OFF_ST = OFF_RED + 5 * 4608;
constexpr int OFF_SM = OFF_ST + 640;
constexpr int OFF_RT = OFF_SM + 128;
constexpr int OFF_HU = OFF_RT + 384;
constexpr int OFF_QS = OFF_HU + 128;
constexpr int OFF_WR = OFF_QS + 512;
constexpr int OFF_WIN = OFF_WR + 1152;
constexpr int OFF_BAR = OFF_WIN + 16;
constexpr int BAR_FULL = 6, BAR_WO = 22, BAR_GU = 26, BAR_WD = 35, BAR_EMPTY = 40, BAR_SYNC = 56, BAR_WMF = 59, BAR_GB = 60, NBAR = 70;
constexpr int SMEM_BYTES = OFF_BAR + NBAR * 8;

constexpr int D_X1 = 0;
constexpr int D_O = 3072;
constexpr int D_ACT = D_O + 512 * 32;
constexpr int D_H = D_ACT + 576 * 32;
constexpr int D_Q = D_H + 3072;
constexpr int G_M = 2 * (D_Q + NB * HQ * 64);
constexpr int G_CNT = G_M + 216 * 32;
constexpr int G_SET = 1 << 18;
__device__ __forceinline__ int d_part(int unit) { return (64 + unit + (unit & 64)) * 1024; }
constexpr int D_PING = 200 * 1024;
constexpr int G_EPOCH = 201 * 2048;
static_assert(G_CNT < 64 * 2048, "scratch layout");
__device__ uint32_t g_scratch[4 * G_SET];
__device__ __forceinline__ int dual(int w) { return w + (w & ~1023); }
__device__ __forceinline__ int near(int w, int side) { return dual(w) + (((__popc(w & 0x16400) ^ side) & 1) << 10); }

#define TI(i)
#define TS(i)
#define TSL(i)

enum { M_K, M_V, M_GU, M_GX, M_OD, M_OX, M_WQ, M_WM, M_WA, M_GB, NMAP };
struct Params {
    const __nv_bfloat16 *c, *x, *k;
    __nv_bfloat16* out;
    uint32_t* scratch;
    const __nv_bfloat16* wr;
    int zg, zo;
};
struct Maps {
    CUtensorMap m[NMAP];
};

__device__ __forceinline__ void mbar_init(uint32_t bar, int cnt) {
    asm volatile("mbarrier.init.shared::cta.b64 [%0], %1;" ::"r"(bar), "r"(cnt));
}
__device__ __forceinline__ void mbar_expect(uint32_t bar, uint32_t bytes) {
    asm volatile("mbarrier.arrive.expect_tx.shared::cta.b64 _, [%0], %1;" ::"r"(bar), "r"(bytes) : "memory");
}
__device__ __forceinline__ void mbar_arrive(uint32_t bar) {
    asm volatile("mbarrier.arrive.shared::cta.b64 _, [%0];" ::"r"(bar) : "memory");
}
__device__ __forceinline__ void mbar_wait(uint32_t bar, uint32_t parity) {
    asm volatile("{\n.reg .pred p;\n.reg .u32 c;\n"
                 "mbarrier.try_wait.parity.shared::cta.b64 p, [%0], %1;\n@p bra DONE;\nmov.u32 c, %2;\n"
                 "AGAIN:\nmbarrier.try_wait.parity.shared::cta.b64 p, [%0], %1;\nsub.u32 c, c, 1;\n"
                 "setp.eq.or.u32 p, c, 0, p;\n@!p bra AGAIN;\nDONE:\n}"
                 ::"r"(bar), "r"(parity), "n"(SPIN_LIMIT) : "memory");
}
__device__ __forceinline__ bool mbar_test(uint32_t bar, uint32_t parity) {
    uint32_t ok;
    asm volatile("{\n.reg .pred p;\nmbarrier.test_wait.parity.shared::cta.b64 p, [%1], %2;\nselp.u32 %0, 1, 0, p;\n}"
                 : "=r"(ok) : "r"(bar), "r"(parity) : "memory");
    return ok;
}
__device__ __forceinline__ void mbar_wait_lanes(uint32_t bar) {
    mbar_wait(bar, 0);
    __syncwarp();
}
__device__ __forceinline__ void tma3d_hint(uint32_t dst, const CUtensorMap* m, int x, int y, int z, uint32_t bar, u64 pol) {
    asm volatile("cp.async.bulk.tensor.3d.shared::cluster.global.mbarrier::complete_tx::bytes.L2::cache_hint"
                 " [%0], [%1, {%2, %3, %4}], [%5], %6;"
                 ::"r"(dst), "l"(m), "r"(x), "r"(y), "r"(z), "r"(bar), "l"(pol) : "memory");
}
__device__ __forceinline__ void tma3d(uint32_t dst, const CUtensorMap* m, int x, int y, int z, uint32_t bar) {
    asm volatile("cp.async.bulk.tensor.3d.shared::cluster.global.mbarrier::complete_tx::bytes [%0], [%1, {%2, %3, %4}], [%5];"
                 ::"r"(dst), "l"(m), "r"(x), "r"(y), "r"(z), "r"(bar) : "memory");
}
__device__ __forceinline__ void bar_sync(int id, int n) { asm volatile("bar.sync %0, %1;" ::"r"(id), "r"(n) : "memory"); }
__device__ __forceinline__ void bar_arrive(int id, int n) { asm volatile("bar.arrive %0, %1;" ::"r"(id), "r"(n) : "memory"); }
__device__ __forceinline__ void ldsm4(uint32_t (&r)[4], uint32_t a) {
    asm volatile("ldmatrix.sync.aligned.m8n8.x4.shared.b16 {%0,%1,%2,%3}, [%4];"
                 : "=r"(r[0]), "=r"(r[1]), "=r"(r[2]), "=r"(r[3]) : "r"(a) : "memory");
}
__device__ __forceinline__ void ldsm4t(uint32_t (&r)[4], uint32_t a) {
    asm volatile("ldmatrix.sync.aligned.m8n8.x4.trans.shared.b16 {%0,%1,%2,%3}, [%4];"
                 : "=r"(r[0]), "=r"(r[1]), "=r"(r[2]), "=r"(r[3]) : "r"(a) : "memory");
}
__device__ __forceinline__ void mma(float (&c)[4], uint32_t a0, uint32_t a1, uint32_t a2, uint32_t a3, uint32_t b0, uint32_t b1) {
    asm volatile("mma.sync.aligned.m16n8k16.row.col.f32.bf16.bf16.f32 {%0,%1,%2,%3}, {%4,%5,%6,%7}, {%8,%9}, {%0,%1,%2,%3};"
                 : "+f"(c[0]), "+f"(c[1]), "+f"(c[2]), "+f"(c[3])
                 : "r"(a0), "r"(a1), "r"(a2), "r"(a3), "r"(b0), "r"(b1));
}
__device__ __forceinline__ uint32_t movm(uint32_t a) {
    uint32_t d;
    asm volatile("movmatrix.sync.aligned.m8n8.trans.b16 %0, %1;" : "=r"(d) : "r"(a));
    return d;
}
__device__ __forceinline__ uint32_t lds32(uint32_t a) { uint32_t v; asm volatile("ld.shared.b32 %0, [%1];" : "=r"(v) : "r"(a) : "memory"); return v; }
__device__ __forceinline__ float2 lds64f(uint32_t a) { float2 v; asm volatile("ld.shared.v2.f32 {%0,%1}, [%2];" : "=f"(v.x), "=f"(v.y) : "r"(a) : "memory"); return v; }
__device__ __forceinline__ uint4 lds128(uint32_t a) { uint4 v; asm volatile("ld.shared.v4.b32 {%0,%1,%2,%3}, [%4];" : "=r"(v.x), "=r"(v.y), "=r"(v.z), "=r"(v.w) : "r"(a) : "memory"); return v; }
__device__ __forceinline__ void sts32(uint32_t a, uint32_t v) { asm volatile("st.shared.b32 [%0], %1;" ::"r"(a), "r"(v) : "memory"); }
__device__ __forceinline__ void sts16(uint32_t a, uint16_t v) { asm volatile("st.shared.b16 [%0], %1;" ::"r"(a), "h"(v) : "memory"); }
__device__ __forceinline__ void sts64(uint32_t a, uint32_t x, uint32_t y) { asm volatile("st.shared.v2.b32 [%0], {%1,%2};" ::"r"(a), "r"(x), "r"(y) : "memory"); }
__device__ __forceinline__ void sts128(uint32_t a, uint32_t x, uint32_t y, uint32_t z, uint32_t w) {
    asm volatile("st.shared.v4.b32 [%0], {%1,%2,%3,%4};" ::"r"(a), "r"(x), "r"(y), "r"(z), "r"(w) : "memory");
}
__device__ __forceinline__ void sts128f(uint32_t a, const float (&c)[4]) {
    sts128(a, __float_as_uint(c[0]), __float_as_uint(c[1]), __float_as_uint(c[2]), __float_as_uint(c[3]));
}

__device__ __forceinline__ float sel4(const float (&c)[4], int t) { return (t & 2) ? ((t & 1) ? c[3] : c[2]) : ((t & 1) ? c[1] : c[0]); }

template <int LUT>
__device__ __forceinline__ uint32_t lop3(uint32_t a, uint32_t b, uint32_t c) {
    uint32_t d;
    asm("lop3.b32 %0, %1, %2, %3, %4;" : "=r"(d) : "r"(a), "r"(b), "r"(c), "n"(LUT));
    return d;
}
__device__ __forceinline__ uint32_t pin(uint32_t v) { return __shfl_xor_sync(0xffffffffu, v, 0); }
template <typename T>
__device__ __forceinline__ T* at(T* base, uint32_t bytes) { return (T*)((const char*)base + bytes); }

__device__ __forceinline__ uint32_t clock32(uint32_t dep) {
    uint32_t t;
    asm volatile("{\n.reg .pred p;\nsetp.eq.u32 p, %1, 0x9e3779b9;\n@p nanosleep.u32 1;\nmov.u32 %0, %clock;\n}" : "=r"(t) : "r"(dep) : "memory");
    return t;
}

__device__ __forceinline__ uint32_t nz(uint32_t v) { return v ? v : 0x80000000u; }
__device__ __forceinline__ void st1(uint32_t* p, uint32_t a) { asm volatile("st.relaxed.gpu.global.b32 [%0], %1;" ::"l"(p), "r"(a) : "memory"); }
__device__ __forceinline__ void st2(uint32_t* p, uint32_t a, uint32_t b) {
    asm volatile("st.relaxed.gpu.global.v2.b32 [%0], {%1,%2};" ::"l"(p), "r"(a), "r"(b) : "memory");
}
__device__ __forceinline__ void zero4(uint32_t* p) { asm volatile("st.relaxed.gpu.global.v4.b32 [%0], {%1,%1,%1,%1};" ::"l"(p), "r"(0) : "memory"); }
__device__ __forceinline__ void put1d(uint32_t* p, uint32_t a) { a = nz(a), st1(p, a), st1(p + 1024, a); }
__device__ __forceinline__ void put2d(uint32_t* p, uint32_t a, uint32_t b) { a = nz(a), b = nz(b), st2(p, a, b), st2(p + 1024, a, b); }
__device__ __forceinline__ uint32_t ld1(const uint32_t* p) {
    uint32_t v;
    asm volatile("ld.relaxed.gpu.global.b32 %0, [%1];" : "=r"(v) : "l"(p) : "memory");
    return v;
}
template <int N, int V>
__device__ __forceinline__ void fetch(const uint32_t* p, int stride, uint32_t (&a)[N * V]) {
#pragma unroll
    for (int i = 0; i < N; i++) {
        if (V == 1)
            asm volatile("{\n.reg .pred p;\nsetp.eq.u32 p, %0, 0;\n@p ld.relaxed.gpu.global.b32 %0, [%1];\n}"
                         : "+r"(a[i]) : "l"(p + i * stride) : "memory");
        if (V == 4)
            asm volatile("{\n.reg .pred p;\nsetp.eq.u32 p, %4, 0;\n@p ld.relaxed.gpu.global.v4.b32 {%0,%1,%2,%3}, [%5];\n}"
                         : "+r"(a[V * i]), "+r"(a[V * i + V / 4]), "+r"(a[V * i + V / 2]), "+r"(a[V * i + V - 1])
                         : "r"(min(min(a[V * i], a[V * i + V / 4]), min(a[V * i + V / 2], a[V * i + V - 1]))), "l"(p + i * stride) : "memory");
    }
}
template <int N>
__device__ __forceinline__ bool missing(const uint32_t (&a)[N]) {
    uint32_t lo = a[0];
#pragma unroll
    for (int i = 1; i < N; i++) lo = min(lo, a[i]);
    return __any_sync(0xffffffffu, lo == 0);
}
template <int N, int V>
__device__ __forceinline__ void get(const uint32_t* p, int stride, uint32_t (&a)[N * V]) {
    int it = 0;
    do fetch<N, V>(p, stride, a);
    while (missing(a) & (++it < SPIN_LIMIT));
}
__device__ __forceinline__ void cp16(uint32_t dst, const void* src) {
    asm volatile("cp.async.cg.shared.global [%0], [%1], 16;" ::"r"(dst), "l"(src) : "memory");
}

__device__ __forceinline__ uint32_t pack2(float lo, float hi) {
    uint32_t r;
    asm("cvt.rn.bf16x2.f32 %0, %1, %2;" : "=r"(r) : "f"(hi), "f"(lo));
    return r;
}
__device__ __forceinline__ float rbf(float x) { return __uint_as_float(pack2(0.f, x)); }
__device__ __forceinline__ float blo(uint32_t v) { return __uint_as_float(v << 16); }
__device__ __forceinline__ float bhi(uint32_t v) { return __uint_as_float(v & 0xffff0000u); }
__device__ __forceinline__ uint32_t badd2(uint32_t a, uint32_t b) { uint32_t r; asm("add.rn.bf16x2 %0, %1, %2;" : "=r"(r) : "r"(a), "r"(b)); return r; }
__device__ __forceinline__ uint32_t bsub2(uint32_t a, uint32_t b) { uint32_t r; asm("sub.rn.bf16x2 %0, %1, %2;" : "=r"(r) : "r"(a), "r"(b)); return r; }
__device__ __forceinline__ uint32_t bmul2(uint32_t a, uint32_t b) { uint32_t r; asm("mul.rn.bf16x2 %0, %1, %2;" : "=r"(r) : "r"(a), "r"(b)); return r; }
__device__ __forceinline__ float ex2(float x) { float r; asm("ex2.approx.ftz.f32 %0, %1;" : "=f"(r) : "f"(x)); return r; }
__device__ __forceinline__ float rcp(float x) { float r; asm("rcp.approx.ftz.f32 %0, %1;" : "=f"(r) : "f"(x)); return r; }
__device__ __forceinline__ float sqrt_f(float x) { float r; asm("sqrt.approx.ftz.f32 %0, %1;" : "=f"(r) : "f"(x)); return r; }
constexpr float LOG2E = 1.4426950408889634f;
constexpr uint32_t ONE2 = 0x3f803f80u;
__device__ __forceinline__ float sigmoid_f(float x) { return rcp(1.0f + ex2(-LOG2E * x)); }
__device__ __forceinline__ uint32_t silu2(uint32_t v) {
    const float a = blo(v), b = bhi(v);
    return pack2(a * sigmoid_f(a), b * sigmoid_f(b));
}
__device__ __forceinline__ float quad_sum(float v) {
    v += __shfl_xor_sync(0xffffffffu, v, 1);
    return v + __shfl_xor_sync(0xffffffffu, v, 2);
}
__device__ __forceinline__ void ln_partial(const uint32_t (&v)[8], uint32_t dst, bool writer) {
    float s0 = 0.f, s1 = 0.f;
#pragma unroll
    for (int i = 0; i < 8; i++) {
        s0 += blo(v[i]);
        s1 += bhi(v[i]);
    }
    const float mean = quad_sum(s0 + s1) * (1.0f / 64);
    s0 = s1 = 0.f;
#pragma unroll
    for (int i = 0; i < 8; i++) {
        const float a = blo(v[i]) - mean, b = bhi(v[i]) - mean;
        s0 = fmaf(a, a, s0);
        s1 = fmaf(b, b, s1);
    }
    s0 = quad_sum(s0 + s1);
    if (writer) sts64(dst, __float_as_uint(mean), __float_as_uint(s0));
}
__device__ __forceinline__ void ln_combine(uint32_t src, uint32_t& mean2, float& inv) {
    float m[10], q0 = 0.f, q1 = 0.f, s = 0.f;
#pragma unroll
    for (int i = 0; i < 5; i++) {
        const uint4 v = lds128(src + i * 16);
        m[2 * i] = __uint_as_float(v.x);
        m[2 * i + 1] = __uint_as_float(v.z);
        q0 += __uint_as_float(v.y);
        if (i < 4) q1 += __uint_as_float(v.w);
    }
    const float mean = (((m[0] + m[1]) + (m[2] + m[3])) + ((m[4] + m[5]) + (m[6] + m[7])) + m[8]) * (1.0f / 9);
#pragma unroll
    for (int i = 0; i < 9; i++) s = fmaf(m[i] - mean, m[i] - mean, s);
    const float var = fmaf(s, 64.f, q0 + q1) * (1.0f / DM);
    mean2 = pack2(mean, mean);
    inv = rcp(rbf(sqrt_f(rbf(rbf(var) + 1e-5f))));
}
__device__ __forceinline__ uint32_t modulate2(uint32_t x, uint32_t mean2, float inv, uint32_t shift, uint32_t onep) {
    const uint32_t d = bsub2(x, mean2);
    return badd2(bmul2(pack2(blo(d) * inv, bhi(d) * inv), onep), shift);
}
template <int N>
__device__ __forceinline__ void sum_frags(float (&c)[4], uint32_t addr, int stride) {
#pragma unroll
    for (int w = 0; w < N; w++) {
        const uint4 v = lds128(addr + w * stride);
        c[0] += __uint_as_float(v.x); c[1] += __uint_as_float(v.y);
        c[2] += __uint_as_float(v.z); c[3] += __uint_as_float(v.w);
    }
}

template <int ST>
__device__ __forceinline__ void project(uint32_t sm, const uint32_t* src, uint32_t* dst, uint32_t rowoff, uint32_t reds, int nsync, int warp, int lane) {
    constexpr int NW = ST ? 9 : 8;
    const uint32_t red = sm + (ST ? OFF_WO : OFF_P);
    if (warp < NW) {
        const uint32_t wbar = sm + OFF_BAR + (ST ? BAR_WD + (warp < 8 ? ((warp >> 1) - WD_ROT) & 3 : 4) : BAR_WO + (warp >> 1)) * 8;
        const uint32_t ab = sm + (ST ? OFF_WD : OFF_WO) + rowoff;
        const uint32_t ax = sm + (ST ? OFF_DX : OFF_OX) + ((rowoff >> 7) << 4);
        uint32_t a[10][4] = {}, b[4] = {};
        bool have_w = false, need_b = true;
        int it = 0;
        do {
            if (!need_b) mbar_wait(wbar, 0);
            if (!need_b || (!have_w && __all_sync(0xffffffffu, mbar_test(wbar, 0)))) {
                have_w = true;
#pragma unroll
                for (int i = 0; i < 10; i++) ldsm4t(a[i], i % 5 < 4 ? (ab ^ ((i % 5) << 5)) + (i / 5) * 2048 : ax + (i / 5) * 256);
                if (!need_b) break;
            }
            if (ST) fetch<4, 1>(src, 32, b);
            else fetch<1, 4>(src, 0, b);
            need_b = missing(b) & (++it < SPIN_LIMIT);
        } while (need_b | !have_w);
        if (warp == 0) TSL(ST ? 24 : 21);
        float acc[5][4] = {};
#pragma unroll
        for (int i = 0; i < 10; i++) mma(acc[i % 5], a[i][0], a[i][1], a[i][2], a[i][3], b[2 * (i / 5)], b[2 * (i / 5) + 1]);
#pragma unroll
        for (int u = 0; u < 9; u++)
            sts64(red + u * 2304 + (reds & 0xffff), __float_as_uint(acc[u >> 1][2 * (u & 1)]), __float_as_uint(acc[u >> 1][2 * (u & 1) + 1]));
    }
    bar_sync(ST ? 6 : 3, nsync);
    float s[2][2] = {};
#pragma unroll
    for (int w = 0; w < NW; w++) {
        const float2 v = lds64f(red + (reds >> 16) + w * 256);
        s[w & 1][0] += v.x;
        s[w & 1][1] += v.y;
    }
    const uint32_t p0 = (__float_as_uint(s[0][0] + s[1][0]) | 1) ^ ST, p1 = (__float_as_uint(s[0][1] + s[1][1]) | 1) ^ ST;
    st2(dst, p0, p1), st2(dst + 1024, p0, p1);
}

template <int ST, typename F>
__device__ __forceinline__ uint32_t reduce16(const uint32_t* src, F arrived) {
    uint32_t a[32] = {}, bad[16], any;
    int it = 0;
#pragma unroll
    for (int i = 0; i < 16; i++) bad[i] = 1;
    do {
#pragma unroll
        for (int i = 0; i < 16; i++)
            asm volatile("{\n.reg .pred p;\nsetp.ne.u32 p, %2, 0;\n@p ld.relaxed.gpu.global.v2.b32 {%0,%1}, [%3];\n}"
                         : "+r"(a[2 * i]), "+r"(a[2 * i + 1]) : "r"(bad[i]), "l"(src + i * 64) : "memory");
#pragma unroll
        for (int i = 0; i < 16; i++) bad[i] = lop3<ST ? 0xa8 : 0x2a>(a[2 * i], a[2 * i + 1], 1);
        any = lop3<0xfe>(lop3<0xfe>(lop3<0xfe>(bad[0], bad[1], bad[2]), lop3<0xfe>(bad[3], bad[4], bad[5]), lop3<0xfe>(bad[6], bad[7], bad[8])),
                         lop3<0xfe>(lop3<0xfe>(bad[9], bad[10], bad[11]), lop3<0xfe>(bad[12], bad[13], bad[14]), bad[15]), 0);
    } while (__any_sync(0xffffffffu, any != 0) & (++it < SPIN_LIMIT));
    arrived();
    float f[8];
#pragma unroll
    for (int i = 0; i < 8; i++)
        f[i] = (__uint_as_float(a[i]) + __uint_as_float(a[i + 8])) + (__uint_as_float(a[i + 16]) + __uint_as_float(a[i + 24]));
    f[0] = (f[0] + f[2]) + (f[4] + f[6]);
    f[1] = (f[1] + f[3]) + (f[5] + f[7]);
    return movm(pack2(f[0], f[1]));
}

__global__ void __launch_bounds__(NTHREADS, 1) fused_kernel(const Params P, const __grid_constant__ Maps T) {
    extern __shared__ __align__(1024) char smem_raw[];
    constexpr uint32_t sm = 1024;
    const int tid = threadIdx.x, lane = tid & 31;
    const int cta = blockIdx.x, grp = cta >> 3, sub = cta & 7;
    const uint32_t bars = sm + OFF_BAR;
    const int row0 = (sub * HKV + grp) * SK + (SK - WIN);
    if (tid >> 5 == 9) {
#pragma unroll
        for (int i = 0; i < PFK; i++) asm volatile("prefetch.global.L2 [%0];" ::"l"(P.k + (size_t)row0 * DH + (lane + i * 32) * 64) : "memory");
    }
    u64 pol;
    asm volatile("createpolicy.fractional.L2::evict_first.b64 %0, 1.0;" : "=l"(pol));
    if (tid == NCW * 32) {
        TS(0);
        const int n0 = cta < 90 ? 0 : 3;
#pragma unroll
        for (int i = 0; i < 6; i++) mbar_init(bars + i * 8, 1);
        asm volatile("fence.mbarrier_init.release.cluster;" ::: "memory");
#pragma unroll
        for (int i = 0; i < 3; i++) {
            mbar_expect(bars + (n0 + i) * 8, 12288);
            tma3d(sm + OFF_WM + (n0 + i) * 12288, &T.m[cta < 36 ? M_WA : cta < 90 ? M_WM : M_WQ], cta < 36 ? 16 * cta : 32 * cta,
                  i * 192, 0, bars + (n0 + i) * 8);
            TI(n0 + i);
        }
        TS(26);
    }
    if (tid == NCW * 32 + 32) {
#pragma unroll
        for (int i = 0; i < 4; i++) mbar_init(bars + (BAR_FULL + i) * 8, 1);
        asm volatile("fence.mbarrier_init.release.cluster;" ::: "memory");
#pragma unroll
        for (int t = 0; t < NK0; t++) {
            mbar_expect(bars + (BAR_FULL + t) * 8, TILE_BYTES);
            tma3d_hint(sm + OFF_RING + t * TILE_BYTES, &T.m[M_K], 0, row0 + t * 32, 0, bars + (BAR_FULL + t) * 8, pol);
            TI(6 + t);
        }
    }
    if (tid < 288 && cta < 90) {
#pragma unroll
        for (int i = 0; i < 2; i++) {
            const int row = (lane >> 3) + 4 * i, so = row * DM + (tid >> 5) * 64 + (lane & 7) * 8;
            const uint32_t d = sm + OFF_RED + (tid >> 5) * 2048 + row * 128 + (((lane & 7) ^ row) << 4);
            cp16(d, P.c + so);
            if (cta < 36) cp16(d + 1024, P.x + so);
        }
    }
    uint32_t* const g0 = P.scratch;
    const uint32_t epoch = ld1(g0 + G_EPOCH);
    const int warp = __shfl_sync(0xffffffffu, tid >> 5, 0);
    auto pace = [&](int t, int gain) {
        const int d = (int)atomicAdd(g0 + (epoch & 1) * G_SET + G_CNT, 1u) - 32 * (t - 16) - 16;
        sts32(sm + OFF_WIN, min(max((d * gain + 32) >> 6, W_MIN), W_MAX));
    };

    if (warp >= NCW) {
        const int pw = warp - NCW;
        bar_arrive(1, (NCW + 1) * 32);
        if (pw && lane < M_WQ) asm volatile("prefetch.tensormap [%0];" ::"l"(&T.m[M_WQ - lane]) : "memory");
        if (tid == NCW * 32) sts32(sm + OFF_WIN, 0);
        __syncwarp();
        bar_sync(15, NTHREADS);
        if (lane == 0) {
            if (pw == 0 && cta < 90) {
#pragma unroll 1
                for (int n = 3; n < 6; n++) {
                    mbar_expect(bars + n * 8, 12288);
                    mbar_wait(bars + (n - 3) * 8, 0);
                    tma3d(sm + OFF_WM + n * 12288, &T.m[M_WQ], 32 * cta, (n - 3) * 192, 0, bars + n * 8);
                    TI(n);
                }
            }
#pragma unroll 1
            for (int t = NK0 + (1 - pw) * NK1; t < NK0 + NK1 + 3 * (1 - pw); t++) {
                mbar_expect(bars + (BAR_FULL + t) * 8, TILE_BYTES);
                mbar_wait(bars + (t + (pw ? BAR_FULL - NK1 : 3 - NK0 - NK1)) * 8, 0);
                tma3d_hint(sm + OFF_RING + t * TILE_BYTES, &T.m[M_K], 0, row0 + t * 32, 0, bars + (BAR_FULL + t) * 8, pol);
                TI(6 + t);
            }
            if (pw == 0) {
#pragma unroll 1
                for (int t = NK0 + NK1 + 3; t < 2 * NT; t++) {
                    if (t == 14 && cta < 90) mbar_wait(bars + BAR_WMF * 8, 0);
                    if (t == 15) TS(30);
                    const int m = t - ((W_KV + (int)lds32(sm + OFF_WIN) + ((0xd8 >> (2 * t & 6)) & 3)) >> 2);
                    const uint32_t fb = bars + (BAR_FULL + (t & 15)) * 8;
                    mbar_wait(fb + (BAR_EMPTY - BAR_FULL) * 8, (~t >> 4) & 1);
                    mbar_expect(fb, TILE_BYTES);
                    mbar_wait(bars + (BAR_FULL + (m & 15)) * 8, (m >> 4) & 1);
                    tma3d_hint(sm + OFF_RING + (t & 15) * TILE_BYTES, &T.m[t >> 6], 0, row0 + (t & (NT - 1)) * 32, 0, fb, pol);
                    TI(6 + t);
                    if (t == T_CLEAR) mbar_arrive(bars + (BAR_SYNC + 1) * 8);
                }
                mbar_arrive(bars + (BAR_SYNC + 2) * 8);
                mbar_wait(bars + BAR_SYNC * 8, 0);
                auto window = [&](int b, int w) {
                    b -= max((w + (int)lds32(sm + OFF_WIN) + ((0xd8 >> (2 * b & 6)) & 3)) >> 2, 1);
                    b = min(b, BAR_GU + B_CAP);
                    mbar_wait(bars + b * 8, b < BAR_WO);
                };
#pragma unroll 1
                for (int i = 0; i < 4; i++) {
                    window(BAR_WO + i, W_WO);
                    tma3d(sm + OFF_WO + i * 8192, &T.m[M_OD], 64 * sub, grp * 256 + i * 64, P.zo, bars + (BAR_WO + i) * 8);
                    tma3d(sm + OFF_OX + i * 1024, &T.m[M_OX], 512 + 8 * sub, grp * 256 + i * 64, P.zo, bars + (BAR_WO + i) * 8);
                    TI(134 + i);
                }
                TS(28);
#pragma unroll 1
                for (int i = 0; i < 9; i++) {
                    mbar_wait(bars + (BAR_EMPTY + i) * 8, 1);
                    window(BAR_GU + i, sub < 4 ? W_GU : W_GU2);
                    tma3d(sm + OFF_GU + i * 8192, &T.m[M_GU], grp * 288 + 32 * sub, i * 64, 0, bars + (BAR_GU + i) * 8);
                    if (sub < 4) tma3d(sm + OFF_GX + i * 2048, &T.m[M_GX], grp * 288 + 256 + 8 * sub, i * 64, 0, bars + (BAR_GU + i) * 8);
                    TI(138 + i);
                }
                TS(29);
#pragma unroll 1
                for (int i = 0; i < 5; i++) {
                    const int blk = i < 4 ? (i + WD_ROT) & 3 : 4, r = min(blk * 64, 224);
                    mbar_wait(bars + (BAR_EMPTY + 9 + blk) * 8, 1);
                    window(BAR_WD + i, W_WD);
                    tma3d(sm + OFF_WD + r * 128, &T.m[M_OD], 64 * sub, grp * 288 + r, P.zo ^ 1, bars + (BAR_WD + i) * 8);
                    tma3d(sm + OFF_DX + r * 16, &T.m[M_OX], 512 + 8 * sub, grp * 288 + r, P.zo ^ 1, bars + (BAR_WD + i) * 8);
                    TI(147 + i);
                }
                if (cta < 72) {
                    mbar_wait(bars + (BAR_EMPTY + 14) * 8, 1);
                    mbar_wait(bars + (BAR_EMPTY + 15) * 8, 1);
                    mbar_expect(bars + BAR_GB * 8, 9216);
                    mbar_wait(bars + (BAR_WD + GB_AT) * 8, 0);
#pragma unroll
                    for (int i = 0; i < 3; i++) tma3d(sm + OFF_GB + i * 3072, &T.m[M_GB], 5 * DM + 8 * cta, i * 192, 0, bars + BAR_GB * 8);
                }
            } else {
#pragma unroll 1
                for (int i = BAR_WO; i < BAR_WD + 5; i++) mbar_expect(bars + i * 8, i < BAR_GU || i >= BAR_WD ? 9216 : sub < 4 ? 10240 : 8192);
                mbar_arrive(bars + BAR_SYNC * 8);
                mbar_wait(bars + (BAR_SYNC + 2) * 8, 0);
#pragma unroll 1
                for (int t = 124 + (cta & 3); t < 144; t += 4) {
                    mbar_wait(bars + (BAR_FULL - 112 + t) * 8, t < 128);
                    pace(t, GAIN_TAIL);
                }
            }
        }
        return;
    }

    if (lane == 0) {
#pragma unroll
        for (int i = 0; i < 6; i++) mbar_init(bars + (10 + warp * 6 + i) * 8, 1);
        asm volatile("fence.mbarrier_init.release.cluster;" ::: "memory");
    }
    __syncwarp();
    if (warp < 9) bar_arrive(15, NTHREADS);
    const int g = lane >> 2, t4 = lane & 3;
    uint32_t* const gs = g0 + (epoch & 1) * G_SET;

    uint32_t sc[8] = {};
    if (warp < 9) {
        const int off_h = (cta < 36 ? dual(D_H + 2 * cta * 32) : G_M + 4 * (cta - 36) * 32) + tid;
        const int off_h2 = off_h + (cta < 36 ? 1024 : 64);
        const int off_q = dual(D_Q + g * (HQ * 64) + cta * 16) + warp * 8 + t4 * 2;
        uint32_t bf[8] = {}, xp = 0, mean2 = 0;
        float inv = 0.f;
        if (cta < 36) xp = __ldg(reinterpret_cast<const uint32_t*>(P.x) + g * (DM / 2) + 8 * cta + 4 * (warp & 1) + t4);
        if (warp < 2) {
            st2(gs + off_q, 0, 0), st2(gs + off_q + 1024, 0, 0);
            if (cta < 36) st1(gs + off_h, 0), st1(gs + off_h2, 0);
        }
        if (cta < 90) {
            asm volatile("cp.async.wait_all;" ::: "memory");
            __syncwarp();
            const uint32_t fa = sm + OFF_RED + warp * 2048 + (lane & 7) * 128 + (((lane >> 3) ^ (lane & 7)) << 4);
            ldsm4(reinterpret_cast<uint32_t(&)[4]>(bf[0]), fa);
            ldsm4(reinterpret_cast<uint32_t(&)[4]>(bf[4]), fa ^ 64);
            if (cta < 36) {
                uint32_t xv[8];
                ldsm4(reinterpret_cast<uint32_t(&)[4]>(xv[0]), fa + 1024);
                ldsm4(reinterpret_cast<uint32_t(&)[4]>(xv[4]), (fa ^ 64) + 1024);
                ln_partial(xv, sm + OFF_ST + g * 80 + warp * 8, t4 == 0);
            }
#pragma unroll
            for (int i = 0; i < 8; i++) sc[i] = bf[i] = silu2(bf[i]);
        }
        if (warp == 0) TSL(18);
        bar_sync(1, (NCW + 1) * 32);
        if (cta < 36 && warp < 2) ln_combine(sm + OFF_ST + g * 80, mean2, inv);
        const int r = warp * 64 + (lane >> 4) * 8 + (lane & 7), hi8 = (lane >> 3) & 1, box = warp / 3;
#pragma unroll 1
        for (int pass = cta < 90 ? 0 : 1; pass < 2; pass++) {
            const bool pa = pass == 0 && cta < 36;
            const uint32_t ab = sm + OFF_WM + pass * 36864 +
                                (pa ? (box + hi8) * 6144 + r * 32 + ((lane & 4) << 2) : r * 64 + (((2 * hi8) ^ ((r >> 1) & 3)) << 4));
            const uint32_t as = pa ? 512 : 1024, red = sm + OFF_RED + pass * 9216;
            mbar_wait(bars + (pass * 3 + box) * 8, 0);
            if (warp == 8) TSL(pass ? 31 : 19);
            uint32_t a[4][2][4];
#pragma unroll
            for (int i = 0; i < 4; i++) {
                ldsm4t(a[i][0], ab + i * as);
                ldsm4t(a[i][1], (ab ^ 16) + i * as);
            }
            if (pass) {
                bar_sync(8, NCW * 32);
#pragma unroll
                for (int i = 0; i < 8; i++) bf[i] = 0;
                get<8, 1>(gs + near(D_H + warp * 256, lds32(sm + OFF_WIN + 4)) + lane, 32, bf);
                if (warp == 0) TSL(3);
            }
            float acc[2][4] = {};
#pragma unroll
            for (int i = 0; i < 4; i++)
#pragma unroll
                for (int m = 0; m < 2; m++) mma(acc[m], a[i][m][0], a[i][m][1], a[i][m][2], a[i][m][3], bf[2 * i], bf[2 * i + 1]);
            sts128f(red + tid * 16, acc[0]);
            sts128f(red + 4608 + tid * 16, acc[1]);
            bar_sync(3, 288);
            if (warp < 2) {
                float c[4] = {};
                sum_frags<9>(c, red + warp * 4608 + lane * 16, 512);
                uint32_t lo = movm(pack2(c[0], c[1])), hi = movm(pack2(c[2], c[3]));
                if (pass) {
                    put2d(gs + off_q, lo, hi);
                    if (warp == 0) TSL(4);
                } else {
                    const uint32_t hi1 = badd2(hi, ONE2);
                    if (pa) hi = lo = modulate2(xp, mean2, inv, lo, hi1);
                    if (cta >= 72) lo = badd2(lo, ONE2), hi = hi1;
                    st1(gs + off_h, nz(lo));
                    st1(gs + off_h2, nz(hi));
                    if (warp == 0 && pa) TSL(2);
                }
            } else if (tid == 64 && pass == 0) {
                mbar_arrive(bars + BAR_WMF * 8);
            }
        }
    } else {
        if ((uint32_t)__cvta_generic_to_shared(smem_raw) != sm) __trap();
        uint32_t* const ping = g0 + dual(D_PING) + cta * 8;
        if (lane < 16) st1(ping + (lane >> 3) * 1024 + (lane & 7), 0);
        bar_sync(15, NTHREADS);
        uint32_t best[2] = {~0u, ~0u}, v = 0;
#pragma unroll 1
        for (int part = 0; part < 2; part++) {
            if (lane == 0) {
#pragma unroll 1
                for (int r = part ? NPING1 : NPING0; r > 0; r--) {
#pragma unroll
                    for (int k = 0; k < 2; k++) {
                        const uint32_t t0 = clock32(v);
                        v = atomicExch(ping + k * 1024, t0);
                        best[k] = min(best[k], clock32(v) - t0);
                    }
                }
                sts32(sm + OFF_WIN + 4 + 4 * part, ((best[1] < best[0]) ^ __popc(D_PING & 0x16400)) & 1);
            }
            __syncwarp();
            if (part) break;
            TSL(20);
            bar_arrive(8, NCW * 32);
            mbar_wait(bars + 5 * 8, 0);
            uint32_t a[4] = {};
            get<1, 4>(gs + near(D_Q + (sub * HQ + 2 * grp) * 64, lds32(sm + OFF_WIN + 4)) + lane * 4, 0, a);
            sts128(sm + OFF_QS + lane * 16, a[0], a[1], a[2], a[3]);
            __syncwarp();
            TSL(5);
            bar_arrive(4, 288);
        }
#pragma unroll
        for (int i = lane; i < 72; i += 32) cp16(sm + OFF_WR + i * 16, P.wr + i * 8);
        asm volatile("cp.async.wait_all;" ::: "memory");
        __syncwarp();
        bar_arrive(2, NCW * 32);
        if (cta == 0 && lane == 0) st1(g0 + (~epoch & 1) * G_SET + G_CNT, 0);
        mbar_wait(bars + (BAR_SYNC + 1) * 8, 0);
#pragma unroll 1
        for (int c = 0; c < 4; c++) {
            uint32_t* const pg = g0 + (c >> 1) * G_SET + (c & 1) * 1024;
            zero4(pg + dual(D_O + cta * 128) + lane * 4);
            zero4(pg + dual(D_ACT + (grp * 36 + 4 * sub) * 32) + lane * 4);
            if (lane < 8 ? sub < 4 : lane < 16 && cta < 72)
                zero4(pg + dual(lane < 8 ? D_ACT + (grp * 36 + 32 + sub) * 32 : D_X1 + cta * 32) + (lane & 7) * 4);
        }
#pragma unroll 1
        for (int u = 0; u < 9; u++) zero4(g0 + dual(d_part(u < 8 ? 8 * sub + u : 64 + sub)) + (lane >> 4) * 1024 + grp * 64 + (lane & 15) * 4);
        {
            uint32_t* const nx = g0 + (~epoch & 1) * G_SET;
            uint32_t* const q = nx + dual(D_Q + g * (HQ * 64) + cta * 16) + t4 * 4;
            zero4(q), zero4(q + 1024);
            if (cta < 90) zero4(nx + (cta < 36 ? dual(D_H + 2 * cta * 32) + (lane >> 4) * (1024 - 64) : G_M + 4 * (cta - 36) * 32) + lane * 4);
        }
        if (cta >= 72) {
            bar_arrive(5, NCW * 32);
            return;
        }
        const uint32_t io = pin(4 * (g * (DM / 2) + 4 * cta + t4));
        uint32_t x = __ldg(at(reinterpret_cast<const uint32_t*>(P.x), io)), ga[1] = {};
        get<1, 1>(gs + G_M + cta * 32 + lane, 0, ga);
        const uint32_t src_p = pin(4 * (near(d_part(cta), lds32(sm + OFF_WIN + 8)) + lane * 2));
        const uint32_t dst_x = pin(4 * ((epoch & 1) * G_SET + dual(D_X1 + cta * 32) + lane));
        bar_sync(5, NCW * 32);
        x = badd2(x, bmul2(ga[0], reduce16<0>(at(g0, src_p), [] {})));
        put1d(at(g0, dst_x), x);
        TSL(10);
        bar_sync(6, NCW * 32);
        const uint4 r0 = lds128(sm + OFF_RT + g * 48), r1 = lds128(sm + OFF_RT + g * 48 + 16);
        float r = __uint_as_float(lds32(sm + OFF_RT + g * 48 + 32));
        r += ((__uint_as_float(r0.x) + __uint_as_float(r0.y)) + (__uint_as_float(r0.z) + __uint_as_float(r0.w))) +
             ((__uint_as_float(r1.x) + __uint_as_float(r1.y)) + (__uint_as_float(r1.z) + __uint_as_float(r1.w)));
        r = sigmoid_f(rbf(r));
        const uint32_t h = lds32(sm + OFF_HU + lane * 4), rs = pack2(r, r);
        uint32_t gb;
        const uint32_t y = reduce16<1>(at(g0, src_p), [&] {
            bar_sync(9, 64);
            gb = lds32(sm + OFF_QS + lane * 4);
        });
        *at(reinterpret_cast<uint32_t*>(P.out), io) = badd2(x, bmul2(gb, badd2(h, bmul2(y, rs))));
        if (cta == 0 && lane == 0) g0[G_EPOCH] = epoch + 1;
        TSL(15);
        return;
    }

    const uint32_t tile = sm + OFF_RING + warp * TILE_BYTES;
    const uint32_t fullb = bars + (BAR_FULL + warp) * 8;
    const uint32_t pw = sm + OFF_P + warp * (2 * P_PITCH);
    const bool pacer = (tid & 127) == (cta & 3) * 32;
    if (warp < 8) {
        {
            uint32_t q0[8], q1[8];
            bar_sync(4, 288);
#pragma unroll
            for (int i = 0; i < 8; i++) {
                const float2 v = lds64f(sm + OFF_QS + (g & 1) * 256 + i * 32 + t4 * 8);
                q0[i] = __float_as_uint(v.x), q1[i] = __float_as_uint(v.y);
            }
            uint32_t sp = pw + (t4 & 1) * P_PITCH + ((t4 >> 1) * 8 + g) * 2;
#pragma unroll 1
            for (int it = 0; it < 8; it++, sp += 64) {
                const uint32_t ab = tile + (it & 1) * (8 * TILE_BYTES) + (lane & 15) * 128 + (((lane >> 4) ^ (lane & 7)) << 4);
                mbar_wait(fullb + (it & 1) * 64, (it >> 1) & 1);
                float acc[2][2][4] = {};
#pragma unroll
                for (int ks = 0; ks < 8; ks++)
#pragma unroll
                    for (int m = 0; m < 2; m++) {
                        uint32_t a[4];
                        ldsm4(a, (ab ^ ((ks & 3) << 5)) + (ks >> 2) * 4096 + m * 2048);
                        mma(acc[m][ks & 1], a[0], a[1], a[2], a[3], (ks & 1) ? q1[ks - 1] : q0[ks], (ks & 1) ? q1[ks] : q0[ks + 1]);
                    }
                __syncwarp();
                if (lane == 0) mbar_arrive(fullb + (it & 1) * 64 + (BAR_EMPTY - BAR_FULL) * 8);
#pragma unroll
                for (int m = 0; m < 2; m++) {
                    const float s = sel4(acc[m][0], t4) + sel4(acc[m][1], t4);
                    sts16(sp + m * 32, (uint16_t)pack2(rbf(s) * 0.08838834764831845f, 0.f));
                }
                if (pacer && it >= 2) pace(it * 8 + warp, GAIN_KV);
                __syncwarp();
            }
        }
        __syncwarp();
        if (warp == 7) TSL(6);
        const uint32_t pa = pw + (lane >> 4) * P_PITCH + (lane & 15) * 32;
        const uint32_t sa = sm + OFF_SM + (lane >> 4) * 64;
        const uint4 v0 = lds128(pa), v1 = lds128(pa + 16);
        const uint32_t sv[8] = {v0.x, v0.y, v0.z, v0.w, v1.x, v1.y, v1.z, v1.w};
        float e[16];
        float m = -INFINITY;
#pragma unroll
        for (int i = 0; i < 8; i++) {
            e[2 * i] = blo(sv[i]);
            e[2 * i + 1] = bhi(sv[i]);
            m = fmaxf(m, fmaxf(e[2 * i], e[2 * i + 1]));
        }
#pragma unroll
        for (int o = 8; o; o >>= 1) m = fmaxf(m, __shfl_xor_sync(0xffffffffu, m, o));
        float l = 0.f;
#pragma unroll
        for (int i = 0; i < 16; i++) {
            e[i] = ex2((e[i] - m) * LOG2E);
            l += e[i];
        }
#pragma unroll
        for (int o = 8; o; o >>= 1) l += __shfl_xor_sync(0xffffffffu, l, o);
        if ((lane & 15) == 0) sts64(sa + warp * 8, __float_as_uint(m), __float_as_uint(l));
        bar_sync(2, NCW * 32);
        const float2 v = lds64f(sa + (lane & 7) * 8);
        float M = v.x;
#pragma unroll
        for (int o = 4; o; o >>= 1) M = fmaxf(M, __shfl_xor_sync(0xffffffffu, M, o));
        float L = v.y * ex2((v.x - M) * LOG2E);
#pragma unroll
        for (int o = 4; o; o >>= 1) L += __shfl_xor_sync(0xffffffffu, L, o);
        const float sc = ex2((m - M) * LOG2E) * rcp(L);
        sts128(pa, pack2(e[0] * sc, e[1] * sc), pack2(e[2] * sc, e[3] * sc), pack2(e[4] * sc, e[5] * sc), pack2(e[6] * sc, e[7] * sc));
        sts128(pa + 16, pack2(e[8] * sc, e[9] * sc), pack2(e[10] * sc, e[11] * sc), pack2(e[12] * sc, e[13] * sc), pack2(e[14] * sc, e[15] * sc));
        __syncwarp();
    } else {
        bar_sync(2, NCW * 32);
    }

    uint32_t sh[8] = {}, op[8] = {};
    {
        const uint32_t* const src_m = gs + G_M + (72 + warp * 8) * 32 + lane;
        fetch<8, 1>(src_m + 72 * 32, 32, op);
        get<8, 1>(src_m, 32, sh);
        get<8, 1>(src_m + 72 * 32, 32, op);
    }
    const int side = lds32(sm + OFF_WIN + 8), set = (epoch & 1) * G_SET, rr = (lane >> 4) * 8 + (lane & 7);
    const uint32_t dst_o = pin(4 * (set + dual(D_O + cta * 128) + (tid & 0x70) + (tid & 3) * 4 + ((tid >> 2) & 3)));
    const uint32_t src_o = pin(4 * (set + near(D_O + grp * 1024, side) + g * 128 + warp * 16 + t4 * 4));
    const uint32_t dst_p = pin(4 * (dual(d_part(warp < 8 ? 8 * sub + warp : 64 + sub)) + grp * 64 + lane * 2));
    const uint32_t src_x = pin(4 * (set + near(D_X1 + warp * 256, side) + lane));
    const uint32_t dst_a = pin(4 * (set + dual(D_ACT + (grp * 36 + (warp < 4 ? 4 * sub + warp : 32 + sub)) * 32) + lane));
    const uint32_t src_a = pin(4 * (set + near(D_ACT + (grp * 36 + 4 * warp) * 32, side) + lane));
    const uint32_t rowoff = pin((warp * 32 + rr) * 128 + ((((lane >> 3) & 1) ^ (lane & 7)) << 4));
    const uint32_t reds = pin((tid * 8) | (warp * 2304 + lane * 8) << 16);
    const uint32_t ored = pin((warp * 1088 + (t4 & 1) * 576 + ((t4 >> 1) * 8 + g) * 4) | ((tid >> 6) * 64 + tid * 8) << 16);

    if (warp < 8) {
        float acc[8][4] = {};
        uint32_t pp = pw + (lane & 1) * P_PITCH + (lane >> 3) * 16;
#pragma unroll 1
        for (int it = 0; it < 8; it++, pp += 64) {
            const uint32_t ab = tile + (it & 1) * (8 * TILE_BYTES) + ((lane & 7) + (lane >> 4) * 8) * 128 + ((((lane >> 3) & 1) ^ (lane & 7)) << 4);
            uint32_t pb[4];
            ldsm4(pb, pp);
            mbar_wait(fullb + (it & 1) * 64, (it >> 1) & 1);
#pragma unroll
            for (int ks = 0; ks < 2; ks++)
#pragma unroll
                for (int m = 0; m < 8; m++) {
                    uint32_t a[4];
                    ldsm4t(a, (ab ^ ((m & 3) << 5)) + (m >> 2) * 4096 + ks * 2048);
                    mma(acc[m], a[0], a[1], a[2], a[3], pb[2 * ks], pb[2 * ks + 1]);
                }
            __syncwarp();
            if (lane == 0) mbar_arrive(fullb + (it & 1) * 64 + (BAR_EMPTY - BAR_FULL) * 8);
            if (pacer && it * 8 + warp < NT - 4) pace(NT + it * 8 + warp, GAIN_KV);
            __syncwarp();
        }
        if (warp == 7) TSL(7);
        const uint32_t ra = sm + OFF_ORED + (ored & 0xffff);
#pragma unroll
        for (int m = 0; m < 8; m++) sts32(ra + m * 64, __float_as_uint(sel4(acc[m], t4)));
    }
    bar_sync(5, NCW * 32);
    if (warp < 4) {
        float s[2][2] = {};
#pragma unroll
        for (int w = 0; w < 8; w++) {
            const float2 v = lds64f(sm + OFF_ORED + w * 1088 + (ored >> 16));
            s[w & 1][0] += v.x;
            s[w & 1][1] += v.y;
        }
        put1d(at(g0, dst_o), pack2(s[0][0] + s[1][0], s[0][1] + s[1][1]));
        if (warp == 0) TSL(8);
    }

    project<0>(sm, at(g0, src_o), at(g0, dst_p), rowoff, reds, 288, warp, lane);
    if (warp == 0) TSL(9);

    const uint32_t gbar = bars + (BAR_GU + warp) * 8;
    const int pl = ((lane >> 3) & 1) ^ P.zg;
    const uint32_t ab = sm + OFF_GU + warp * 8192 + pl * 4096 + rr * 64 + ((lane & 6) << 3);
    const uint32_t ax = sm + OFF_GX + warp * 2048 + pl * 1024 + rr * 16;
    uint32_t a[20][4] = {}, h[8] = {};
    auto load_gu = [&]() {
#pragma unroll
        for (int i = 0; i < 20; i++) ldsm4t(a[i], i % 5 < 4 ? (ab ^ ((i % 5) << 4)) + (i / 5) * 1024 : ax + (i / 5) * 256);
    };
    bool gpre = false;
    {
        int it = 0;
        do {
            if (!gpre && __all_sync(0xffffffffu, mbar_test(gbar, 0))) gpre = true, load_gu();
            fetch<8, 1>(at(g0, src_x), 32, h);
        } while (missing(h) & (++it < SPIN_LIMIT));
    }
    if (warp == 0) TSL(11);
    ln_partial(h, sm + OFF_ST + g * 80 + warp * 8, t4 == 0);
    bar_sync(3, 288);
    {
        uint32_t mean2;
        float inv;
        ln_combine(sm + OFF_ST + g * 80, mean2, inv);
#pragma unroll
        for (int i = 0; i < 8; i++) h[i] = modulate2(h[i], mean2, inv, sh[i], op[i]);
    }
    if (warp == 0) TSL(12);
    if (!gpre) {
        mbar_wait(gbar, 0);
        load_gu();
    }
    if (warp == 8) TSL(17);
    {
        float acc[5][4] = {};
#pragma unroll
        for (int i = 0; i < 20; i++) mma(acc[i % 5], a[i][0], a[i][1], a[i][2], a[i][3], h[2 * (i / 5)], h[2 * (i / 5) + 1]);
#pragma unroll
        for (int m = 0; m < 5; m++) sts128f(sm + OFF_RED + m * 4608 + 2 * (reds & 0xffff), acc[m]);
    }
    bar_sync(3, 288);
    if (warp < 5) {
        float c[4] = {};
        sum_frags<9>(c, sm + OFF_RED + 2 * (reds >> 16), 512);
        const uint32_t w = movm(bmul2(silu2(pack2(c[0], c[1])), pack2(c[2], c[3])));
        if (warp < 4 || sub < 4) put1d(at(g0, dst_a), w);
        if (warp == 1) TSL(13);
    }
    if (cta < 72) {
        float r = 0.f;
#pragma unroll
        for (int i = 0; i < 8; i++) {
            const uint32_t wr = lds32(sm + OFF_WR + (warp * 32 + i * 4 + t4) * 4);
            r = fmaf(blo(h[i]), blo(wr), fmaf(bhi(h[i]), bhi(wr), r));
            if (warp * 8 + i == cta) sts32(sm + OFF_HU + lane * 4, h[i]);
        }
        r = quad_sum(r);
        if (t4 == 0) sts32(sm + OFF_RT + g * 48 + warp * 4, __float_as_uint(r));
    }

    project<1>(sm, at(g0, src_a), at(g0, dst_p), rowoff, reds, cta < 72 ? 320 : 288, warp, lane);
    if (warp == 0) TSL(14);

    if (cta < 72) {
        const uint32_t ga = sm + OFF_GB + warp * 1024 + ((lane >> 3) & 1) * 256 + (lane >> 4) * 128 + (lane & 7) * 16;
        float acc[2][4] = {};
        mbar_wait(bars + BAR_GB * 8, 0);
        if (warp == 0) TSL(22);
#pragma unroll
        for (int i = 0; i < 2; i++) {
            uint32_t w[4];
            ldsm4t(w, ga + i * 512);
            mma(acc[0], w[0], w[1], w[2], w[3], sc[4 * i], sc[4 * i + 1]);
            mma(acc[1], w[0], w[1], w[2], w[3], sc[4 * i + 2], sc[4 * i + 3]);
        }
        sts64(sm + OFF_RED + (reds & 0xffff), __float_as_uint(acc[0][0] + acc[1][2]), __float_as_uint(acc[0][1] + acc[1][3]));
        if (warp) {
            bar_arrive(7, 288);
        } else {
            bar_sync(7, 288);
            float s[2][2] = {};
#pragma unroll
            for (int w = 0; w < 9; w++) {
                const float2 v = lds64f(sm + OFF_RED + (reds & 0xffff) + w * 256);
                s[w & 1][0] += v.x;
                s[w & 1][1] += v.y;
            }
            sts32(sm + OFF_QS + lane * 4, movm(pack2(s[0][0] + s[1][0], s[0][1] + s[1][1])));
            __syncwarp();
            bar_arrive(9, 64);
        }
    }
}

typedef CUresult (*EncodeFn)(CUtensorMap*, CUtensorMapDataType, cuuint32_t, void*, const cuuint64_t*, const cuuint64_t*,
                             const cuuint32_t*, const cuuint32_t*, CUtensorMapInterleave, CUtensorMapSwizzle,
                             CUtensorMapL2promotion, CUtensorMapFloatOOBfill);

void make_map(EncodeFn enc, CUtensorMap* m, void* p, int cols, int rows, int pitch, int bc, int br, int bp, int planes, size_t pstride,
              CUtensorMapSwizzle sw, int promo) {
    cuuint64_t dims[3] = {(cuuint64_t)cols, (cuuint64_t)rows, (cuuint64_t)planes};
    cuuint64_t strides[2] = {(cuuint64_t)pitch * 2, (cuuint64_t)pstride};
    cuuint32_t box[3] = {(cuuint32_t)bc, (cuuint32_t)br, (cuuint32_t)bp};
    cuuint32_t es[3] = {1, 1, 1};
    enc(m, CU_TENSOR_MAP_DATA_TYPE_BFLOAT16, 3, p, dims, strides, box, es, CU_TENSOR_MAP_INTERLEAVE_NONE, sw,
        (CUtensorMapL2promotion)promo, CU_TENSOR_MAP_FLOAT_OOB_FILL_NONE);
}

}

extern "C" void kernel_launch(void* const* d_in, const int* in_sizes, int n_in, void* d_out, int out_size) {
    static EncodeFn enc = nullptr;
    static uint32_t* scratch = nullptr;
    if (!enc) {
        void* fn = nullptr;
        cudaDriverEntryPointQueryResult st;
        cudaGetDriverEntryPoint("cuTensorMapEncodeTiled", &fn, cudaEnableDefault, &st);
        enc = (EncodeFn)fn;
        cudaGetSymbolAddress(&fn, g_scratch);
        scratch = (uint32_t*)(((uintptr_t)fn + 8 * G_SET - 1) & ~(uintptr_t)(8 * G_SET - 1));
        cudaFuncSetAttribute(fused_kernel, cudaFuncAttributeMaxDynamicSharedMemorySize, SMEM_BYTES);
    }
    Params P;
    Maps T;
    const CUtensorMapSwizzle none = CU_TENSOR_MAP_SWIZZLE_NONE;
    make_map(enc, &T.m[M_K], d_in[1], 64, NB * HKV * SK, DH, 64, 32, 2, 2, 128, CU_TENSOR_MAP_SWIZZLE_128B, PROMO_KV);
    make_map(enc, &T.m[M_V], d_in[2], 64, NB * HKV * SK, DH, 64, 32, 2, 2, 128, CU_TENSOR_MAP_SWIZZLE_128B, PROMO_KV);
    make_map(enc, &T.m[M_WQ], d_in[3], HQ * DH, DM, HQ * DH, 32, 192, 1, 1, 16, CU_TENSOR_MAP_SWIZZLE_64B, PROMO_W);
    make_map(enc, &T.m[M_WM], d_in[11], 6 * DM, DM, 6 * DM, 32, 192, 1, 1, 16, CU_TENSOR_MAP_SWIZZLE_64B, PROMO_W);
    make_map(enc, &T.m[M_WA], d_in[11], DM, DM, 6 * DM, 16, 192, 2, 2, DM * 2, CU_TENSOR_MAP_SWIZZLE_32B, PROMO_W);
    make_map(enc, &T.m[M_GB], d_in[11], 6 * DM, DM, 6 * DM, 8, 192, 1, 1, 16, none, PROMO_W);
    char *wg = (char*)d_in[7], *wu = (char*)d_in[8], *wo = (char*)d_in[4], *wd = (char*)d_in[9];
    P.zg = wg > wu;
    P.zo = wo > wd;
    const size_t sg = P.zg ? wg - wu : wu - wg, so = P.zo ? wo - wd : wd - wo;
    make_map(enc, &T.m[M_GU], P.zg ? wu : wg, FF, DM, FF, 32, 64, 2, 2, sg, CU_TENSOR_MAP_SWIZZLE_64B, PROMO_GU);
    make_map(enc, &T.m[M_GX], P.zg ? wu : wg, FF, DM, FF, 8, 64, 2, 2, sg, none, PROMO_GX);
    make_map(enc, &T.m[M_OD], P.zo ? wd : wo, DM, FF, DM, 64, 64, 1, 2, so, CU_TENSOR_MAP_SWIZZLE_128B, PROMO_W);
    make_map(enc, &T.m[M_OX], P.zo ? wd : wo, DM, FF, DM, 8, 64, 1, 2, so, none, PROMO_OX);
    P.x = (const __nv_bfloat16*)d_in[0];
    P.wr = (const __nv_bfloat16*)d_in[6];
    P.c = (const __nv_bfloat16*)d_in[10];
    P.k = (const __nv_bfloat16*)d_in[1];
    P.out = (__nv_bfloat16*)d_out;
    P.scratch = scratch;
    fused_kernel<<<NCTA, NTHREADS, SMEM_BYTES>>>(P, T);
}
```

```cpp
#include <cuda_runtime.h>
#include <cuda_bf16.h>
#include <cuda.h>
#include <stdint.h>

typedef unsigned long long u64;

#define W_KV 21
#define W_WO 19
#define W_GU 19
#define W_WD 14
#define W_MIN -6
#define W_MAX 8
#define GAIN_KV 2
#define GAIN_TAIL 3
#define NK0 3
#define NK1 2
#define PFK 2
#define T_CLEAR 116
#define B_CAP 8
#define GB_AT 2
#define NPING0 4
#define NPING1 16

namespace {

constexpr int NB = 8, DM = 576, HQ = 32, HKV = 16, SK = 8192, WIN = 2048, DH = 128, FF = 4608;
constexpr int NCTA = 128;
constexpr int NCW = 10;
constexpr int NTHREADS = (NCW + 2) * 32;
constexpr int TILE_BYTES = 8192, NT = 64;
constexpr int SPIN_LIMIT = 1 << 22;

constexpr int OFF_RING = 0;
constexpr int OFF_WM = 121856;
constexpr int OFF_WQ = OFF_WM + 36864;
constexpr int OFF_GU = 0;
constexpr int OFF_WD = 73728;
constexpr int OFF_GB = 114688;
constexpr int OFF_OX = 131072;
constexpr int OFF_DX = OFF_OX + 4096;
constexpr int OFF_GX = OFF_DX + 4608;
constexpr int OFF_WO = OFF_WQ;
constexpr int OFF_P = OFF_WQ + 36864;
constexpr int P_PITCH = 528;
constexpr int OFF_RED = OFF_P + 16 * P_PITCH;
constexpr int OFF_ORED = OFF_RED + 5 * 4608 - 8704;
constexpr int OFF_ST = OFF_RED + 5 * 4608;
constexpr int OFF_SM = OFF_ST + 640;
constexpr int OFF_RT = OFF_SM + 128;
constexpr int OFF_HU = OFF_RT + 384;
constexpr int OFF_QS = OFF_HU + 128;
constexpr int OFF_WR = OFF_QS + 512;
constexpr int OFF_WIN = OFF_WR + 1152;
constexpr int OFF_BAR = OFF_WIN + 16;
constexpr int BAR_FULL = 6, BAR_WO = 22, BAR_GU = 26, BAR_WD = 35, BAR_EMPTY = 40, BAR_SYNC = 56, BAR_WMF = 59, BAR_GB = 60, NBAR = 70;
constexpr int SMEM_BYTES = OFF_BAR + NBAR * 8;

constexpr int D_X1 = 0;
constexpr int D_O = 3072;
constexpr int D_ACT = D_O + 512 * 32;
constexpr int D_H = D_ACT + 576 * 32;
constexpr int D_Q = D_H + 3072;
constexpr int G_M = 2 * (D_Q + NB * HQ * 64);
constexpr int G_CNT = G_M + 216 * 32;
constexpr int G_SET = 1 << 18;
__device__ __forceinline__ int d_part(int unit) { return (64 + unit + (unit & 64)) * 1024; }
constexpr int D_PING = 200 * 1024;
constexpr int G_EPOCH = 201 * 2048;
static_assert(G_CNT < 64 * 2048, "scratch layout");
__device__ uint32_t g_scratch[4 * G_SET];
__device__ __forceinline__ int dual(int w) { return w + (w & ~1023); }
__device__ __forceinline__ int near(int w, int side) { return dual(w) + (((__popc(w & 0x16400) ^ side) & 1) << 10); }

#define TI(i)
#define TS(i)
#define TSL(i)

enum { M_K, M_V, M_GU, M_GX, M_OD, M_OX, M_WQ, M_WM, M_WA, M_GB, NMAP };
struct Params {
    const __nv_bfloat16 *c, *x, *k;
    __nv_bfloat16* out;
    uint32_t* scratch;
    const __nv_bfloat16* wr;
    int zg, zo;
};
struct Maps {
    CUtensorMap m[NMAP];
};

__device__ __forceinline__ void mbar_init(uint32_t bar, int cnt) {
    asm volatile("mbarrier.init.shared::cta.b64 [%0], %1;" ::"r"(bar), "r"(cnt));
}
__device__ __forceinline__ void mbar_expect(uint32_t bar, uint32_t bytes) {
    asm volatile("mbarrier.arrive.expect_tx.shared::cta.b64 _, [%0], %1;" ::"r"(bar), "r"(bytes) : "memory");
}
__device__ __forceinline__ void mbar_arrive(uint32_t bar) {
    asm volatile("mbarrier.arrive.shared::cta.b64 _, [%0];" ::"r"(bar) : "memory");
}
__device__ __forceinline__ void mbar_wait(uint32_t bar, uint32_t parity) {
    asm volatile("{\n.reg .pred p;\n.reg .u32 c;\n"
                 "mbarrier.try_wait.parity.shared::cta.b64 p, [%0], %1;\n@p bra DONE;\nmov.u32 c, %2;\n"
                 "AGAIN:\nmbarrier.try_wait.parity.shared::cta.b64 p, [%0], %1;\nsub.u32 c, c, 1;\n"
                 "setp.eq.or.u32 p, c, 0, p;\n@!p bra AGAIN;\nDONE:\n}"
                 ::"r"(bar), "r"(parity), "n"(SPIN_LIMIT) : "memory");
}
__device__ __forceinline__ bool mbar_test(uint32_t bar, uint32_t parity) {
    uint32_t ok;
    asm volatile("{\n.reg .pred p;\nmbarrier.test_wait.parity.shared::cta.b64 p, [%1], %2;\nselp.u32 %0, 1, 0, p;\n}"
                 : "=r"(ok) : "r"(bar), "r"(parity) : "memory");
    return ok;
}
__device__ __forceinline__ void tma3d_hint(uint32_t dst, const CUtensorMap* m, int x, int y, int z, uint32_t bar, u64 pol) {
    asm volatile("cp.async.bulk.tensor.3d.shared::cluster.global.mbarrier::complete_tx::bytes.L2::cache_hint"
                 " [%0], [%1, {%2, %3, %4}], [%5], %6;"
                 ::"r"(dst), "l"(m), "r"(x), "r"(y), "r"(z), "r"(bar), "l"(pol) : "memory");
}
__device__ __forceinline__ void tma3d(uint32_t dst, const CUtensorMap* m, int x, int y, int z, uint32_t bar) {
    asm volatile("cp.async.bulk.tensor.3d.shared::cluster.global.mbarrier::complete_tx::bytes [%0], [%1, {%2, %3, %4}], [%5];"
                 ::"r"(dst), "l"(m), "r"(x), "r"(y), "r"(z), "r"(bar) : "memory");
}
__device__ __forceinline__ void bar_sync(int id, int n) { asm volatile("bar.sync %0, %1;" ::"r"(id), "r"(n) : "memory"); }
__device__ __forceinline__ void bar_arrive(int id, int n) { asm volatile("bar.arrive %0, %1;" ::"r"(id), "r"(n) : "memory"); }
__device__ __forceinline__ void ldsm4(uint32_t (&r)[4], uint32_t a) {
    asm volatile("ldmatrix.sync.aligned.m8n8.x4.shared.b16 {%0,%1,%2,%3}, [%4];"
                 : "=r"(r[0]), "=r"(r[1]), "=r"(r[2]), "=r"(r[3]) : "r"(a) : "memory");
}
__device__ __forceinline__ void ldsm4t(uint32_t (&r)[4], uint32_t a) {
    asm volatile("ldmatrix.sync.aligned.m8n8.x4.trans.shared.b16 {%0,%1,%2,%3}, [%4];"
                 : "=r"(r[0]), "=r"(r[1]), "=r"(r[2]), "=r"(r[3]) : "r"(a) : "memory");
}
__device__ __forceinline__ void mma(float (&c)[4], uint32_t a0, uint32_t a1, uint32_t a2, uint32_t a3, uint32_t b0, uint32_t b1) {
    asm volatile("mma.sync.aligned.m16n8k16.row.col.f32.bf16.bf16.f32 {%0,%1,%2,%3}, {%4,%5,%6,%7}, {%8,%9}, {%0,%1,%2,%3};"
                 : "+f"(c[0]), "+f"(c[1]), "+f"(c[2]), "+f"(c[3])
                 : "r"(a0), "r"(a1), "r"(a2), "r"(a3), "r"(b0), "r"(b1));
}
__device__ __forceinline__ uint32_t movm(uint32_t a) {
    uint32_t d;
    asm volatile("movmatrix.sync.aligned.m8n8.trans.b16 %0, %1;" : "=r"(d) : "r"(a));
    return d;
}
__device__ __forceinline__ uint32_t lds32(uint32_t a) { uint32_t v; asm volatile("ld.shared.b32 %0, [%1];" : "=r"(v) : "r"(a) : "memory"); return v; }
__device__ __forceinline__ float2 lds64f(uint32_t a) { float2 v; asm volatile("ld.shared.v2.f32 {%0,%1}, [%2];" : "=f"(v.x), "=f"(v.y) : "r"(a) : "memory"); return v; }
__device__ __forceinline__ uint4 lds128(uint32_t a) { uint4 v; asm volatile("ld.shared.v4.b32 {%0,%1,%2,%3}, [%4];" : "=r"(v.x), "=r"(v.y), "=r"(v.z), "=r"(v.w) : "r"(a) : "memory"); return v; }
__device__ __forceinline__ void sts32(uint32_t a, uint32_t v) { asm volatile("st.shared.b32 [%0], %1;" ::"r"(a), "r"(v) : "memory"); }
__device__ __forceinline__ void sts16(uint32_t a, uint16_t v) { asm volatile("st.shared.b16 [%0], %1;" ::"r"(a), "h"(v) : "memory"); }
__device__ __forceinline__ void sts64(uint32_t a, uint32_t x, uint32_t y) { asm volatile("st.shared.v2.b32 [%0], {%1,%2};" ::"r"(a), "r"(x), "r"(y) : "memory"); }
__device__ __forceinline__ void sts128(uint32_t a, uint32_t x, uint32_t y, uint32_t z, uint32_t w) {
    asm volatile("st.shared.v4.b32 [%0], {%1,%2,%3,%4};" ::"r"(a), "r"(x), "r"(y), "r"(z), "r"(w) : "memory");
}
__device__ __forceinline__ void sts128f(uint32_t a, const float (&c)[4]) {
    sts128(a, __float_as_uint(c[0]), __float_as_uint(c[1]), __float_as_uint(c[2]), __float_as_uint(c[3]));
}

__device__ __forceinline__ float sel4(const float (&c)[4], int t) { return (t & 2) ? ((t & 1) ? c[3] : c[2]) : ((t & 1) ? c[1] : c[0]); }

template <int LUT>
__device__ __forceinline__ uint32_t lop3(uint32_t a, uint32_t b, uint32_t c) {
    uint32_t d;
    asm("lop3.b32 %0, %1, %2, %3, %4;" : "=r"(d) : "r"(a), "r"(b), "r"(c), "n"(LUT));
    return d;
}
__device__ __forceinline__ uint32_t pin(uint32_t v) { return __shfl_xor_sync(0xffffffffu, v, 0); }
template <typename T>
__device__ __forceinline__ T* at(T* base, uint32_t bytes) { return (T*)((const char*)base + bytes); }

__device__ __forceinline__ uint32_t clock32(uint32_t dep) {
    uint32_t t;
    asm volatile("{\n.reg .pred p;\nsetp.eq.u32 p, %1, 0x9e3779b9;\n@p nanosleep.u32 1;\nmov.u32 %0, %clock;\n}" : "=r"(t) : "r"(dep) : "memory");
    return t;
}

__device__ __forceinline__ uint32_t nz(uint32_t v) { return v ? v : 0x80000000u; }
__device__ __forceinline__ void st1(uint32_t* p, uint32_t a) { asm volatile("st.relaxed.gpu.global.b32 [%0], %1;" ::"l"(p), "r"(a) : "memory"); }
__device__ __forceinline__ void st2(uint32_t* p, uint32_t a, uint32_t b) {
    asm volatile("st.relaxed.gpu.global.v2.b32 [%0], {%1,%2};" ::"l"(p), "r"(a), "r"(b) : "memory");
}
__device__ __forceinline__ void zero4(uint32_t* p) { asm volatile("st.relaxed.gpu.global.v4.b32 [%0], {%1,%1,%1,%1};" ::"l"(p), "r"(0) : "memory"); }
__device__ __forceinline__ void put1d(uint32_t* p, uint32_t a) { a = nz(a), st1(p, a), st1(p + 1024, a); }
__device__ __forceinline__ void put2d(uint32_t* p, uint32_t a, uint32_t b) { a = nz(a), b = nz(b), st2(p, a, b), st2(p + 1024, a, b); }
__device__ __forceinline__ uint32_t ld1(const uint32_t* p) {
    uint32_t v;
    asm volatile("ld.relaxed.gpu.global.b32 %0, [%1];" : "=r"(v) : "l"(p) : "memory");
    return v;
}
template <int N, int V>
__device__ __forceinline__ void fetch(const uint32_t* p, int stride, uint32_t (&a)[N * V]) {
#pragma unroll
    for (int i = 0; i < N; i++) {
        if (V == 1)
            asm volatile("{\n.reg .pred p;\nsetp.eq.u32 p, %0, 0;\n@p ld.relaxed.gpu.global.b32 %0, [%1];\n}"
                         : "+r"(a[i]) : "l"(p + i * stride) : "memory");
        if (V == 4)
            asm volatile("{\n.reg .pred p;\nsetp.eq.u32 p, %4, 0;\n@p ld.relaxed.gpu.global.v4.b32 {%0,%1,%2,%3}, [%5];\n}"
                         : "+r"(a[V * i]), "+r"(a[V * i + V / 4]), "+r"(a[V * i + V / 2]), "+r"(a[V * i + V - 1])
                         : "r"(min(min(a[V * i], a[V * i + V / 4]), min(a[V * i + V / 2], a[V * i + V - 1]))), "l"(p + i * stride) : "memory");
    }
}
template <int N>
__device__ __forceinline__ bool missing(const uint32_t (&a)[N]) {
    uint32_t lo = a[0];
#pragma unroll
    for (int i = 1; i < N; i++) lo = min(lo, a[i]);
    return __any_sync(0xffffffffu, lo == 0);
}
template <int N, int V>
__device__ __forceinline__ void get(const uint32_t* p, int stride, uint32_t (&a)[N * V]) {
    int it = 0;
    do fetch<N, V>(p, stride, a);
    while (missing(a) & (++it < SPIN_LIMIT));
}
__device__ __forceinline__ void cp16(uint32_t dst, const void* src) {
    asm volatile("cp.async.cg.shared.global [%0], [%1], 16;" ::"r"(dst), "l"(src) : "memory");
}

__device__ __forceinline__ uint32_t pack2(float lo, float hi) {
    uint32_t r;
    asm("cvt.rn.bf16x2.f32 %0, %1, %2;" : "=r"(r) : "f"(hi), "f"(lo));
    return r;
}
__device__ __forceinline__ float rbf(float x) { return __uint_as_float(pack2(0.f, x)); }
__device__ __forceinline__ float blo(uint32_t v) { return __uint_as_float(v << 16); }
__device__ __forceinline__ float bhi(uint32_t v) { return __uint_as_float(v & 0xffff0000u); }
__device__ __forceinline__ uint32_t badd2(uint32_t a, uint32_t b) { uint32_t r; asm("add.rn.bf16x2 %0, %1, %2;" : "=r"(r) : "r"(a), "r"(b)); return r; }
__device__ __forceinline__ uint32_t bsub2(uint32_t a, uint32_t b) { uint32_t r; asm("sub.rn.bf16x2 %0, %1, %2;" : "=r"(r) : "r"(a), "r"(b)); return r; }
__device__ __forceinline__ uint32_t bmul2(uint32_t a, uint32_t b) { uint32_t r; asm("mul.rn.bf16x2 %0, %1, %2;" : "=r"(r) : "r"(a), "r"(b)); return r; }
__device__ __forceinline__ float ex2(float x) { float r; asm("ex2.approx.ftz.f32 %0, %1;" : "=f"(r) : "f"(x)); return r; }
__device__ __forceinline__ float rcp(float x) { float r; asm("rcp.approx.ftz.f32 %0, %1;" : "=f"(r) : "f"(x)); return r; }
__device__ __forceinline__ float sqrt_f(float x) { float r; asm("sqrt.approx.ftz.f32 %0, %1;" : "=f"(r) : "f"(x)); return r; }
constexpr float LOG2E = 1.4426950408889634f;
constexpr uint32_t ONE2 = 0x3f803f80u;
__device__ __forceinline__ float sigmoid_f(float x) { return rcp(1.0f + ex2(-LOG2E * x)); }
__device__ __forceinline__ uint32_t silu2(uint32_t v) {
    const float a = blo(v), b = bhi(v);
    return pack2(a * sigmoid_f(a), b * sigmoid_f(b));
}
__device__ __forceinline__ float quad_sum(float v) {
    v += __shfl_xor_sync(0xffffffffu, v, 1);
    return v + __shfl_xor_sync(0xffffffffu, v, 2);
}
__device__ __forceinline__ void ln_partial(const uint32_t (&v)[8], uint32_t dst, bool writer) {
    float s0 = 0.f, s1 = 0.f;
#pragma unroll
    for (int i = 0; i < 8; i++) {
        s0 += blo(v[i]);
        s1 += bhi(v[i]);
    }
    const float mean = quad_sum(s0 + s1) * (1.0f / 64);
    s0 = s1 = 0.f;
#pragma unroll
    for (int i = 0; i < 8; i++) {
        const float a = blo(v[i]) - mean, b = bhi(v[i]) - mean;
        s0 = fmaf(a, a, s0);
        s1 = fmaf(b, b, s1);
    }
    s0 = quad_sum(s0 + s1);
    if (writer) sts64(dst, __float_as_uint(mean), __float_as_uint(s0));
}
__device__ __forceinline__ void ln_combine(uint32_t src, uint32_t& mean2, float& inv) {
    float m[10], q0 = 0.f, q1 = 0.f, s = 0.f;
#pragma unroll
    for (int i = 0; i < 5; i++) {
        const uint4 v = lds128(src + i * 16);
        m[2 * i] = __uint_as_float(v.x);
        m[2 * i + 1] = __uint_as_float(v.z);
        q0 += __uint_as_float(v.y);
        if (i < 4) q1 += __uint_as_float(v.w);
    }
    const float mean = (((m[0] + m[1]) + (m[2] + m[3])) + ((m[4] + m[5]) + (m[6] + m[7])) + m[8]) * (1.0f / 9);
#pragma unroll
    for (int i = 0; i < 9; i++) s = fmaf(m[i] - mean, m[i] - mean, s);
    const float var = fmaf(s, 64.f, q0 + q1) * (1.0f / DM);
    mean2 = pack2(mean, mean);
    inv = rcp(rbf(sqrt_f(rbf(rbf(var) + 1e-5f))));
}
__device__ __forceinline__ uint32_t modulate2(uint32_t x, uint32_t mean2, float inv, uint32_t shift, uint32_t onep) {
    const uint32_t d = bsub2(x, mean2);
    return badd2(bmul2(pack2(blo(d) * inv, bhi(d) * inv), onep), shift);
}
template <int N>
__device__ __forceinline__ void sum_frags(float (&c)[4], uint32_t addr, int stride) {
#pragma unroll
    for (int w = 0; w < N; w++) {
        const uint4 v = lds128(addr + w * stride);
        c[0] += __uint_as_float(v.x); c[1] += __uint_as_float(v.y);
        c[2] += __uint_as_float(v.z); c[3] += __uint_as_float(v.w);
    }
}

template <int ST>
__device__ __forceinline__ void project(uint32_t sm, const uint32_t* src, uint32_t* dst, uint32_t rowoff, uint32_t reds, int nsync, int warp, int lane) {
    constexpr int NW = ST ? 9 : 8;
    const uint32_t red = sm + (ST ? OFF_WO : OFF_P);
    if (warp < NW) {
        const uint32_t wbar = sm + OFF_BAR + (ST ? BAR_WD + (warp < 8 ? ((warp >> 1) + 1) & 3 : 4) : BAR_WO + (warp >> 1)) * 8;
        const uint32_t ab = sm + (ST ? OFF_WD : OFF_WO) + rowoff;
        const uint32_t ax = sm + (ST ? OFF_DX : OFF_OX) + ((rowoff >> 7) << 4);
        uint32_t a[10][4] = {}, b[4] = {};
        bool have_w = false, need_b = true;
        int it = 0;
        do {
            if (!need_b) mbar_wait(wbar, 0);
            if (!need_b || (!have_w && __all_sync(0xffffffffu, mbar_test(wbar, 0)))) {
                have_w = true;
#pragma unroll
                for (int i = 0; i < 10; i++) ldsm4t(a[i], i % 5 < 4 ? (ab ^ ((i % 5) << 5)) + (i / 5) * 2048 : ax + (i / 5) * 256);
                if (!need_b) break;
            }
            if (ST) fetch<4, 1>(src, 32, b);
            else fetch<1, 4>(src, 0, b);
            need_b = missing(b) & (++it < SPIN_LIMIT);
        } while (need_b | !have_w);
        if (warp == 0) TSL(ST ? 24 : 21);
        float acc[5][4] = {};
#pragma unroll
        for (int i = 0; i < 10; i++) mma(acc[i % 5], a[i][0], a[i][1], a[i][2], a[i][3], b[2 * (i / 5)], b[2 * (i / 5) + 1]);
#pragma unroll
        for (int u = 0; u < 9; u++)
            sts64(red + u * 2304 + (reds & 0xffff), __float_as_uint(acc[u >> 1][2 * (u & 1)]), __float_as_uint(acc[u >> 1][2 * (u & 1) + 1]));
    }
    bar_sync(ST ? 6 : 3, nsync);
    float s[2][2] = {};
#pragma unroll
    for (int w = 0; w < NW; w++) {
        const float2 v = lds64f(red + (reds >> 16) + w * 256);
        s[w & 1][0] += v.x;
        s[w & 1][1] += v.y;
    }
    const uint32_t p0 = (__float_as_uint(s[0][0] + s[1][0]) | 1) ^ ST, p1 = (__float_as_uint(s[0][1] + s[1][1]) | 1) ^ ST;
    st2(dst, p0, p1), st2(dst + 1024, p0, p1);
}

template <int ST, typename F>
__device__ __forceinline__ uint32_t reduce16(const uint32_t* src, F arrived) {
    uint32_t a[32] = {}, bad[16], any;
    int it = 0;
#pragma unroll
    for (int i = 0; i < 16; i++) bad[i] = 1;
    do {
#pragma unroll
        for (int i = 0; i < 16; i++)
            asm volatile("{\n.reg .pred p;\nsetp.ne.u32 p, %2, 0;\n@p ld.relaxed.gpu.global.v2.b32 {%0,%1}, [%3];\n}"
                         : "+r"(a[2 * i]), "+r"(a[2 * i + 1]) : "r"(bad[i]), "l"(src + i * 64) : "memory");
#pragma unroll
        for (int i = 0; i < 16; i++) bad[i] = lop3<ST ? 0xa8 : 0x2a>(a[2 * i], a[2 * i + 1], 1);
        any = lop3<0xfe>(lop3<0xfe>(lop3<0xfe>(bad[0], bad[1], bad[2]), lop3<0xfe>(bad[3], bad[4], bad[5]), lop3<0xfe>(bad[6], bad[7], bad[8])),
                         lop3<0xfe>(lop3<0xfe>(bad[9], bad[10], bad[11]), lop3<0xfe>(bad[12], bad[13], bad[14]), bad[15]), 0);
    } while (__any_sync(0xffffffffu, any != 0) & (++it < SPIN_LIMIT));
    arrived();
    float f[8];
#pragma unroll
    for (int i = 0; i < 8; i++)
        f[i] = (__uint_as_float(a[i]) + __uint_as_float(a[i + 8])) + (__uint_as_float(a[i + 16]) + __uint_as_float(a[i + 24]));
    f[0] = (f[0] + f[2]) + (f[4] + f[6]);
    f[1] = (f[1] + f[3]) + (f[5] + f[7]);
    return movm(pack2(f[0], f[1]));
}

__global__ void __launch_bounds__(NTHREADS, 1) fused_kernel(const Params P, const __grid_constant__ Maps T) {
    extern __shared__ __align__(1024) char smem_raw[];
    constexpr uint32_t sm = 1024;
    const int tid = threadIdx.x, lane = tid & 31;
    const int cta = blockIdx.x, grp = cta >> 3, sub = cta & 7;
    const uint32_t bars = sm + OFF_BAR;
    const int row0 = (sub * HKV + grp) * SK + (SK - WIN);
    if (tid >> 5 == 9) {
#pragma unroll
        for (int i = 0; i < PFK; i++) asm volatile("prefetch.global.L2 [%0];" ::"l"(P.k + (size_t)row0 * DH + (lane + i * 32) * 64) : "memory");
    }
    u64 pol;
    asm volatile("createpolicy.fractional.L2::evict_first.b64 %0, 1.0;" : "=l"(pol));
    if (tid == NCW * 32) {
        TS(0);
        const int n0 = cta < 90 ? 0 : 3;
#pragma unroll
        for (int i = 0; i < 6; i++) mbar_init(bars + i * 8, 1);
        asm volatile("fence.mbarrier_init.release.cluster;" ::: "memory");
#pragma unroll
        for (int i = 0; i < 3; i++) {
            mbar_expect(bars + (n0 + i) * 8, 12288);
            tma3d(sm + OFF_WM + (n0 + i) * 12288, &T.m[cta < 36 ? M_WA : cta < 90 ? M_WM : M_WQ], cta < 36 ? 16 * cta : 32 * cta,
                  i * 192, 0, bars + (n0 + i) * 8);
            TI(n0 + i);
        }
        TS(26);
    }
    if (tid == NCW * 32 + 32) {
#pragma unroll
        for (int i = 0; i < 4; i++) mbar_init(bars + (BAR_FULL + i) * 8, 1);
        asm volatile("fence.mbarrier_init.release.cluster;" ::: "memory");
#pragma unroll
        for (int t = 0; t < NK0; t++) {
            mbar_expect(bars + (BAR_FULL + t) * 8, TILE_BYTES);
            tma3d_hint(sm + OFF_RING + t * TILE_BYTES, &T.m[M_K], 0, row0 + t * 32, 0, bars + (BAR_FULL + t) * 8, pol);
            TI(6 + t);
        }
    }
    if (tid < 288 && cta < 90) {
#pragma unroll
        for (int i = 0; i < 2; i++) {
            const int row = (lane >> 3) + 4 * i, so = row * DM + (tid >> 5) * 64 + (lane & 7) * 8;
            const uint32_t d = sm + OFF_RED + (tid >> 5) * 2048 + row * 128 + (((lane & 7) ^ row) << 4);
            cp16(d, P.c + so);
            if (cta < 36) cp16(d + 1024, P.x + so);
        }
    }
    uint32_t* const g0 = P.scratch;
    const uint32_t epoch = ld1(g0 + G_EPOCH);
    const int warp = __shfl_sync(0xffffffffu, tid >> 5, 0);
    auto pace = [&](int t, int gain) {
        const int d = (int)atomicAdd(g0 + (epoch & 1) * G_SET + G_CNT, 1u) - 32 * (t - 16) - 16;
        sts32(sm + OFF_WIN, min(max((d * gain + 32) >> 6, W_MIN), W_MAX));
    };

    if (warp >= NCW) {
        const int pw = warp - NCW;
        bar_arrive(1, (NCW + 1) * 32);
        if (pw && lane < M_WQ) asm volatile("prefetch.tensormap [%0];" ::"l"(&T.m[M_WQ - lane]) : "memory");
        if (tid == NCW * 32) sts32(sm + OFF_WIN, 0);
        __syncwarp();
        bar_sync(15, NTHREADS);
        if (lane == 0) {
            if (pw == 0 && cta < 90) {
#pragma unroll 1
                for (int n = 3; n < 6; n++) {
                    mbar_expect(bars + n * 8, 12288);
                    mbar_wait(bars + (n - 3) * 8, 0);
                    tma3d(sm + OFF_WM + n * 12288, &T.m[M_WQ], 32 * cta, (n - 3) * 192, 0, bars + n * 8);
                    TI(n);
                }
            }
#pragma unroll 1
            for (int t = NK0 + (1 - pw) * NK1; t < NK0 + NK1 + 3 * (1 - pw); t++) {
                mbar_expect(bars + (BAR_FULL + t) * 8, TILE_BYTES);
                mbar_wait(bars + (t + (pw ? BAR_FULL - NK1 : 3 - NK0 - NK1)) * 8, 0);
                tma3d_hint(sm + OFF_RING + t * TILE_BYTES, &T.m[M_K], 0, row0 + t * 32, 0, bars + (BAR_FULL + t) * 8, pol);
                TI(6 + t);
            }
            if (pw == 0) {
#pragma unroll 1
                for (int t = NK0 + NK1 + 3; t < 2 * NT; t++) {
                    if (t == 14 && cta < 90) mbar_wait(bars + BAR_WMF * 8, 0);
                    if (t == 15) TS(30);
                    const int m = t - ((W_KV + (int)lds32(sm + OFF_WIN) + ((0xd8 >> (2 * t & 6)) & 3)) >> 2);
                    const uint32_t fb = bars + (BAR_FULL + (t & 15)) * 8;
                    mbar_wait(fb + (BAR_EMPTY - BAR_FULL) * 8, (~t >> 4) & 1);
                    mbar_expect(fb, TILE_BYTES);
                    mbar_wait(bars + (BAR_FULL + (m & 15)) * 8, (m >> 4) & 1);
                    tma3d_hint(sm + OFF_RING + (t & 15) * TILE_BYTES, &T.m[t >> 6], 0, row0 + (t & (NT - 1)) * 32, 0, fb, pol);
                    TI(6 + t);
                    if (t == T_CLEAR) mbar_arrive(bars + (BAR_SYNC + 1) * 8);
                }
                mbar_arrive(bars + (BAR_SYNC + 2) * 8);
                mbar_wait(bars + BAR_SYNC * 8, 0);
                auto window = [&](int b, int w) {
                    b -= max((w + (int)lds32(sm + OFF_WIN) + ((0xd8 >> (2 * b & 6)) & 3)) >> 2, 1);
                    b = min(b, BAR_GU + B_CAP);
                    mbar_wait(bars + b * 8, b < BAR_WO);
                };
#pragma unroll 1
                for (int i = 0; i < 4; i++) {
                    window(BAR_WO + i, W_WO);
                    tma3d(sm + OFF_WO + i * 8192, &T.m[M_OD], 64 * sub, grp * 256 + i * 64, P.zo, bars + (BAR_WO + i) * 8);
                    tma3d(sm + OFF_OX + i * 1024, &T.m[M_OX], 512 + 8 * sub, grp * 256 + i * 64, P.zo, bars + (BAR_WO + i) * 8);
                    TI(134 + i);
                }
                TS(28);
#pragma unroll 1
                for (int i = 0; i < 9; i++) {
                    mbar_wait(bars + (BAR_EMPTY + i) * 8, 1);
                    window(BAR_GU + i, W_GU);
                    tma3d(sm + OFF_GU + i * 8192, &T.m[M_GU], grp * 288 + 32 * sub, i * 64, 0, bars + (BAR_GU + i) * 8);
                    if (sub < 4) tma3d(sm + OFF_GX + i * 2048, &T.m[M_GX], grp * 288 + 256 + 8 * sub, i * 64, 0, bars + (BAR_GU + i) * 8);
                    TI(138 + i);
                }
                TS(29);
#pragma unroll 1
                for (int i = 0; i < 5; i++) {
                    const int blk = i < 4 ? (i + 3) & 3 : 4, r = min(blk * 64, 224);
                    mbar_wait(bars + (BAR_EMPTY + 9 + blk) * 8, 1);
                    window(BAR_WD + i, W_WD);
                    tma3d(sm + OFF_WD + r * 128, &T.m[M_OD], 64 * sub, grp * 288 + r, P.zo ^ 1, bars + (BAR_WD + i) * 8);
                    tma3d(sm + OFF_DX + r * 16, &T.m[M_OX], 512 + 8 * sub, grp * 288 + r, P.zo ^ 1, bars + (BAR_WD + i) * 8);
                    TI(147 + i);
                }
                if (cta < 72) {
                    mbar_wait(bars + (BAR_EMPTY + 14) * 8, 1);
                    mbar_wait(bars + (BAR_EMPTY + 15) * 8, 1);
                    mbar_expect(bars + BAR_GB * 8, 9216);
                    mbar_wait(bars + (BAR_WD + GB_AT) * 8, 0);
#pragma unroll
                    for (int i = 0; i < 3; i++) tma3d(sm + OFF_GB + i * 3072, &T.m[M_GB], 5 * DM + 8 * cta, i * 192, 0, bars + BAR_GB * 8);
                }
            } else {
#pragma unroll 1
                for (int i = BAR_WO; i < BAR_WD + 5; i++) mbar_expect(bars + i * 8, i < BAR_GU || i >= BAR_WD ? 9216 : sub < 4 ? 10240 : 8192);
                mbar_arrive(bars + BAR_SYNC * 8);
                mbar_wait(bars + (BAR_SYNC + 2) * 8, 0);
#pragma unroll 1
                for (int t = 124 + (cta & 3); t < 144; t += 4) {
                    mbar_wait(bars + (BAR_FULL - 112 + t) * 8, t < 128);
                    pace(t, GAIN_TAIL);
                }
            }
        }
        return;
    }

    if (lane == 0) {
#pragma unroll
        for (int i = 0; i < 6; i++) mbar_init(bars + (10 + warp * 6 + i) * 8, 1);
        asm volatile("fence.mbarrier_init.release.cluster;" ::: "memory");
    }
    __syncwarp();
    if (warp < 9) bar_arrive(15, NTHREADS);
    const int g = lane >> 2, t4 = lane & 3;
    uint32_t* const gs = g0 + (epoch & 1) * G_SET;

    uint32_t sc[8] = {};
    if (warp < 9) {
        const int off_h = (cta < 36 ? dual(D_H + 2 * cta * 32) : G_M + 4 * (cta - 36) * 32) + tid;
        const int off_h2 = off_h + (cta < 36 ? 1024 : 64);
        const int off_q = dual(D_Q + g * (HQ * 64) + cta * 16) + warp * 8 + t4 * 2;
        uint32_t bf[8] = {}, xp = 0, mean2 = 0;
        float inv = 0.f;
        if (cta < 36) xp = __ldg(reinterpret_cast<const uint32_t*>(P.x) + g * (DM / 2) + 8 * cta + 4 * (warp & 1) + t4);
        if (warp < 2) {
            st2(gs + off_q, 0, 0), st2(gs + off_q + 1024, 0, 0);
            if (cta < 36) st1(gs + off_h, 0), st1(gs + off_h2, 0);
        }
        if (cta < 90) {
            asm volatile("cp.async.wait_all;" ::: "memory");
            __syncwarp();
            const uint32_t fa = sm + OFF_RED + warp * 2048 + (lane & 7) * 128 + (((lane >> 3) ^ (lane & 7)) << 4);
            ldsm4(reinterpret_cast<uint32_t(&)[4]>(bf[0]), fa);
            ldsm4(reinterpret_cast<uint32_t(&)[4]>(bf[4]), fa ^ 64);
            if (cta < 36) {
                uint32_t xv[8];
                ldsm4(reinterpret_cast<uint32_t(&)[4]>(xv[0]), fa + 1024);
                ldsm4(reinterpret_cast<uint32_t(&)[4]>(xv[4]), (fa ^ 64) + 1024);
                ln_partial(xv, sm + OFF_ST + g * 80 + warp * 8, t4 == 0);
            }
#pragma unroll
            for (int i = 0; i < 8; i++) sc[i] = bf[i] = silu2(bf[i]);
        }
        if (warp == 0) TSL(18);
        bar_sync(1, (NCW + 1) * 32);
        if (cta < 36 && warp < 2) ln_combine(sm + OFF_ST + g * 80, mean2, inv);
        const int r = warp * 64 + (lane >> 4) * 8 + (lane & 7), hi8 = (lane >> 3) & 1, box = warp / 3;
#pragma unroll 1
        for (int pass = cta < 90 ? 0 : 1; pass < 2; pass++) {
            const bool pa = pass == 0 && cta < 36;
            const uint32_t ab = sm + OFF_WM + pass * 36864 +
                                (pa ? (box + hi8) * 6144 + r * 32 + ((lane & 4) << 2) : r * 64 + (((2 * hi8) ^ ((r >> 1) & 3)) << 4));
            const uint32_t as = pa ? 512 : 1024, red = sm + OFF_RED + pass * 9216;
            mbar_wait(bars + (pass * 3 + box) * 8, 0);
            if (warp == 8) TSL(pass ? 31 : 19);
            uint32_t a[4][2][4];
#pragma unroll
            for (int i = 0; i < 4; i++) {
                ldsm4t(a[i][0], ab + i * as);
                ldsm4t(a[i][1], (ab ^ 16) + i * as);
            }
            if (pass) {
                bar_sync(8, NCW * 32);
#pragma unroll
                for (int i = 0; i < 8; i++) bf[i] = 0;
                get<8, 1>(gs + near(D_H + warp * 256, lds32(sm + OFF_WIN + 4)) + lane, 32, bf);
                if (warp == 0) TSL(3);
            }
            float acc[2][4] = {};
#pragma unroll
            for (int i = 0; i < 4; i++)
#pragma unroll
                for (int m = 0; m < 2; m++) mma(acc[m], a[i][m][0], a[i][m][1], a[i][m][2], a[i][m][3], bf[2 * i], bf[2 * i + 1]);
            sts128f(red + tid * 16, acc[0]);
            sts128f(red + 4608 + tid * 16, acc[1]);
            bar_sync(3, 288);
            if (warp < 2) {
                float c[4] = {};
                sum_frags<9>(c, red + warp * 4608 + lane * 16, 512);
                uint32_t lo = movm(pack2(c[0], c[1])), hi = movm(pack2(c[2], c[3]));
                if (pass) {
                    put2d(gs + off_q, lo, hi);
                    if (warp == 0) TSL(4);
                } else {
                    const uint32_t hi1 = badd2(hi, ONE2);
                    if (pa) hi = lo = modulate2(xp, mean2, inv, lo, hi1);
                    if (cta >= 72) lo = badd2(lo, ONE2), hi = hi1;
                    st1(gs + off_h, nz(lo));
                    st1(gs + off_h2, nz(hi));
                    if (warp == 0 && pa) TSL(2);
                }
            } else if (tid == 64 && pass == 0) {
                mbar_arrive(bars + BAR_WMF * 8);
            }
        }
    } else {
        if ((uint32_t)__cvta_generic_to_shared(smem_raw) != sm) __trap();
        uint32_t* const ping = g0 + dual(D_PING) + cta * 8;
        if (lane < 16) st1(ping + (lane >> 3) * 1024 + (lane & 7), 0);
        bar_sync(15, NTHREADS);
        uint32_t best[2] = {~0u, ~0u}, v = 0;
#pragma unroll 1
        for (int part = 0; part < 2; part++) {
            if (lane == 0) {
#pragma unroll 1
                for (int r = part ? NPING1 : NPING0; r > 0; r--) {
#pragma unroll
                    for (int k = 0; k < 2; k++) {
                        const uint32_t t0 = clock32(v);
                        v = atomicExch(ping + k * 1024, t0);
                        best[k] = min(best[k], clock32(v) - t0);
                    }
                }
                sts32(sm + OFF_WIN + 4 + 4 * part, ((best[1] < best[0]) ^ __popc(D_PING & 0x16400)) & 1);
            }
            __syncwarp();
            if (part) break;
            TSL(20);
            bar_arrive(8, NCW * 32);
            mbar_wait(bars + 5 * 8, 0);
            uint32_t a[4] = {};
            get<1, 4>(gs + near(D_Q + (sub * HQ + 2 * grp) * 64, lds32(sm + OFF_WIN + 4)) + lane * 4, 0, a);
            sts128(sm + OFF_QS + lane * 16, a[0], a[1], a[2], a[3]);
            __syncwarp();
            TSL(5);
            bar_arrive(4, 288);
        }
#pragma unroll
        for (int i = lane; i < 72; i += 32) cp16(sm + OFF_WR + i * 16, P.wr + i * 8);
        asm volatile("cp.async.wait_all;" ::: "memory");
        __syncwarp();
        bar_arrive(2, NCW * 32);
        if (cta == 0 && lane == 0) st1(g0 + (~epoch & 1) * G_SET + G_CNT, 0);
        mbar_wait(bars + (BAR_SYNC + 1) * 8, 0);
#pragma unroll 1
        for (int c = 0; c < 4; c++) {
            uint32_t* const pg = g0 + (c >> 1) * G_SET + (c & 1) * 1024;
            zero4(pg + dual(D_O + cta * 128) + lane * 4);
            zero4(pg + dual(D_ACT + (grp * 36 + 4 * sub) * 32) + lane * 4);
            if (lane < 8 ? sub < 4 : lane < 16 && cta < 72)
                zero4(pg + dual(lane < 8 ? D_ACT + (grp * 36 + 32 + sub) * 32 : D_X1 + cta * 32) + (lane & 7) * 4);
        }
#pragma unroll 1
        for (int u = 0; u < 9; u++) zero4(g0 + dual(d_part(u < 8 ? 8 * sub + u : 64 + sub)) + (lane >> 4) * 1024 + grp * 64 + (lane & 15) * 4);
        {
            uint32_t* const nx = g0 + (~epoch & 1) * G_SET;
            uint32_t* const q = nx + dual(D_Q + g * (HQ * 64) + cta * 16) + t4 * 4;
            zero4(q), zero4(q + 1024);
            if (cta < 90) zero4(nx + (cta < 36 ? dual(D_H + 2 * cta * 32) + (lane >> 4) * (1024 - 64) : G_M + 4 * (cta - 36) * 32) + lane * 4);
        }
        if (cta >= 72) {
            bar_arrive(5, NCW * 32);
            return;
        }
        const uint32_t io = pin(4 * (g * (DM / 2) + 4 * cta + t4));
        uint32_t x = __ldg(at(reinterpret_cast<const uint32_t*>(P.x), io)), ga[1] = {};
        get<1, 1>(gs + G_M + cta * 32 + lane, 0, ga);
        const uint32_t src_p = pin(4 * (near(d_part(cta), lds32(sm + OFF_WIN + 8)) + lane * 2));
        const uint32_t dst_x = pin(4 * ((epoch & 1) * G_SET + dual(D_X1 + cta * 32) + lane));
        bar_sync(5, NCW * 32);
        x = badd2(x, bmul2(ga[0], reduce16<0>(at(g0, src_p), [] {})));
        put1d(at(g0, dst_x), x);
        TSL(10);
        bar_sync(6, NCW * 32);
        const uint4 r0 = lds128(sm + OFF_RT + g * 48), r1 = lds128(sm + OFF_RT + g * 48 + 16);
        float r = __uint_as_float(lds32(sm + OFF_RT + g * 48 + 32));
        r += ((__uint_as_float(r0.x) + __uint_as_float(r0.y)) + (__uint_as_float(r0.z) + __uint_as_float(r0.w))) +
             ((__uint_as_float(r1.x) + __uint_as_float(r1.y)) + (__uint_as_float(r1.z) + __uint_as_float(r1.w)));
        r = sigmoid_f(rbf(r));
        const uint32_t h = lds32(sm + OFF_HU + lane * 4), rs = pack2(r, r);
        uint32_t gb;
        const uint32_t y = reduce16<1>(at(g0, src_p), [&] {
            bar_sync(9, 64);
            gb = lds32(sm + OFF_QS + lane * 4);
        });
        *at(reinterpret_cast<uint32_t*>(P.out), io) = badd2(x, bmul2(gb, badd2(h, bmul2(y, rs))));
        if (cta == 0 && lane == 0) g0[G_EPOCH] = epoch + 1;
        TSL(15);
        return;
    }

    const uint32_t tile = sm + OFF_RING + warp * TILE_BYTES;
    const uint32_t fullb = bars + (BAR_FULL + warp) * 8;
    const uint32_t pw = sm + OFF_P + warp * (2 * P_PITCH);
    const bool pacer = (tid & 127) == (cta & 3) * 32;
    if (warp < 8) {
        {
            uint32_t q0[8], q1[8];
            bar_sync(4, 288);
#pragma unroll
            for (int i = 0; i < 8; i++) {
                const float2 v = lds64f(sm + OFF_QS + (g & 1) * 256 + i * 32 + t4 * 8);
                q0[i] = __float_as_uint(v.x), q1[i] = __float_as_uint(v.y);
            }
            uint32_t sp = pw + (t4 & 1) * P_PITCH + ((t4 >> 1) * 8 + g) * 2;
#pragma unroll 1
            for (int it = 0; it < 8; it++, sp += 64) {
                const uint32_t ab = tile + (it & 1) * (8 * TILE_BYTES) + (lane & 15) * 128 + (((lane >> 4) ^ (lane & 7)) << 4);
                mbar_wait(fullb + (it & 1) * 64, (it >> 1) & 1);
                float acc[2][2][4] = {};
#pragma unroll
                for (int ks = 0; ks < 8; ks++)
#pragma unroll
                    for (int m = 0; m < 2; m++) {
                        uint32_t a[4];
                        ldsm4(a, (ab ^ ((ks & 3) << 5)) + (ks >> 2) * 4096 + m * 2048);
                        mma(acc[m][ks & 1], a[0], a[1], a[2], a[3], (ks & 1) ? q1[ks - 1] : q0[ks], (ks & 1) ? q1[ks] : q0[ks + 1]);
                    }
                __syncwarp();
                if (lane == 0) mbar_arrive(fullb + (it & 1) * 64 + (BAR_EMPTY - BAR_FULL) * 8);
#pragma unroll
                for (int m = 0; m < 2; m++) {
                    const float s = sel4(acc[m][0], t4) + sel4(acc[m][1], t4);
                    sts16(sp + m * 32, (uint16_t)pack2(rbf(s) * 0.08838834764831845f, 0.f));
                }
                if (pacer && it >= 2) pace(it * 8 + warp, GAIN_KV);
                __syncwarp();
            }
        }
        __syncwarp();
        if (warp == 7) TSL(6);
        const uint32_t pa = pw + (lane >> 4) * P_PITCH + (lane & 15) * 32;
        const uint32_t sa = sm + OFF_SM + (lane >> 4) * 64;
        const uint4 v0 = lds128(pa), v1 = lds128(pa + 16);
        const uint32_t sv[8] = {v0.x, v0.y, v0.z, v0.w, v1.x, v1.y, v1.z, v1.w};
        float e[16];
        float m = -INFINITY;
#pragma unroll
        for (int i = 0; i < 8; i++) {
            e[2 * i] = blo(sv[i]);
            e[2 * i + 1] = bhi(sv[i]);
            m = fmaxf(m, fmaxf(e[2 * i], e[2 * i + 1]));
        }
#pragma unroll
        for (int o = 8; o; o >>= 1) m = fmaxf(m, __shfl_xor_sync(0xffffffffu, m, o));
        float l = 0.f;
#pragma unroll
        for (int i = 0; i < 16; i++) {
            e[i] = ex2((e[i] - m) * LOG2E);
            l += e[i];
        }
#pragma unroll
        for (int o = 8; o; o >>= 1) l += __shfl_xor_sync(0xffffffffu, l, o);
        if ((lane & 15) == 0) sts64(sa + warp * 8, __float_as_uint(m), __float_as_uint(l));
        bar_sync(2, NCW * 32);
        const float2 v = lds64f(sa + (lane & 7) * 8);
        float M = v.x;
#pragma unroll
        for (int o = 4; o; o >>= 1) M = fmaxf(M, __shfl_xor_sync(0xffffffffu, M, o));
        float L = v.y * ex2((v.x - M) * LOG2E);
#pragma unroll
        for (int o = 4; o; o >>= 1) L += __shfl_xor_sync(0xffffffffu, L, o);
        const float sc = ex2((m - M) * LOG2E) * rcp(L);
        sts128(pa, pack2(e[0] * sc, e[1] * sc), pack2(e[2] * sc, e[3] * sc), pack2(e[4] * sc, e[5] * sc), pack2(e[6] * sc, e[7] * sc));
        sts128(pa + 16, pack2(e[8] * sc, e[9] * sc), pack2(e[10] * sc, e[11] * sc), pack2(e[12] * sc, e[13] * sc), pack2(e[14] * sc, e[15] * sc));
        __syncwarp();
    } else {
        bar_sync(2, NCW * 32);
    }

    uint32_t sh[8] = {}, op[8] = {};
    {
        const uint32_t* const src_m = gs + G_M + (72 + warp * 8) * 32 + lane;
        fetch<8, 1>(src_m + 72 * 32, 32, op);
        get<8, 1>(src_m, 32, sh);
        get<8, 1>(src_m + 72 * 32, 32, op);
    }
    const int side = lds32(sm + OFF_WIN + 8), set = (epoch & 1) * G_SET, rr = (lane >> 4) * 8 + (lane & 7);
    const uint32_t dst_o = pin(4 * (set + dual(D_O + cta * 128) + (tid & 0x70) + (tid & 3) * 4 + ((tid >> 2) & 3)));
    const uint32_t src_o = pin(4 * (set + near(D_O + grp * 1024, side) + g * 128 + warp * 16 + t4 * 4));
    const uint32_t dst_p = pin(4 * (dual(d_part(warp < 8 ? 8 * sub + warp : 64 + sub)) + grp * 64 + lane * 2));
    const uint32_t src_x = pin(4 * (set + near(D_X1 + warp * 256, side) + lane));
    const uint32_t dst_a = pin(4 * (set + dual(D_ACT + (grp * 36 + (warp < 4 ? 4 * sub + warp : 32 + sub)) * 32) + lane));
    const uint32_t src_a = pin(4 * (set + near(D_ACT + (grp * 36 + 4 * warp) * 32, side) + lane));
    const uint32_t rowoff = pin((warp * 32 + rr) * 128 + ((((lane >> 3) & 1) ^ (lane & 7)) << 4));
    const uint32_t reds = pin((tid * 8) | (warp * 2304 + lane * 8) << 16);
    const uint32_t ored = pin((warp * 1088 + (t4 & 1) * 576 + ((t4 >> 1) * 8 + g) * 4) | ((tid >> 6) * 64 + tid * 8) << 16);

    if (warp < 8) {
        float acc[8][4] = {};
        uint32_t pp = pw + (lane & 1) * P_PITCH + (lane >> 3) * 16;
#pragma unroll 1
        for (int it = 0; it < 8; it++, pp += 64) {
            const uint32_t ab = tile + (it & 1) * (8 * TILE_BYTES) + ((lane & 7) + (lane >> 4) * 8) * 128 + ((((lane >> 3) & 1) ^ (lane & 7)) << 4);
            uint32_t pb[4];
            ldsm4(pb, pp);
            mbar_wait(fullb + (it & 1) * 64, (it >> 1) & 1);
#pragma unroll
            for (int ks = 0; ks < 2; ks++)
#pragma unroll
                for (int m = 0; m < 8; m++) {
                    uint32_t a[4];
                    ldsm4t(a, (ab ^ ((m & 3) << 5)) + (m >> 2) * 4096 + ks * 2048);
                    mma(acc[m], a[0], a[1], a[2], a[3], pb[2 * ks], pb[2 * ks + 1]);
                }
            __syncwarp();
            if (lane == 0) mbar_arrive(fullb + (it & 1) * 64 + (BAR_EMPTY - BAR_FULL) * 8);
            if (pacer && it * 8 + warp < NT - 4) pace(NT + it * 8 + warp, GAIN_KV);
            __syncwarp();
        }
        if (warp == 7) TSL(7);
        const uint32_t ra = sm + OFF_ORED + (ored & 0xffff);
#pragma unroll
        for (int m = 0; m < 8; m++) sts32(ra + m * 64, __float_as_uint(sel4(acc[m], t4)));
    }
    bar_sync(5, NCW * 32);
    if (warp < 4) {
        float s[2][2] = {};
#pragma unroll
        for (int w = 0; w < 8; w++) {
            const float2 v = lds64f(sm + OFF_ORED + w * 1088 + (ored >> 16));
            s[w & 1][0] += v.x;
            s[w & 1][1] += v.y;
        }
        put1d(at(g0, dst_o), pack2(s[0][0] + s[1][0], s[0][1] + s[1][1]));
        if (warp == 0) TSL(8);
    }

    project<0>(sm, at(g0, src_o), at(g0, dst_p), rowoff, reds, 288, warp, lane);
    if (warp == 0) TSL(9);

    const uint32_t gbar = bars + (BAR_GU + warp) * 8;
    const int pl = ((lane >> 3) & 1) ^ P.zg;
    const uint32_t ab = sm + OFF_GU + warp * 8192 + pl * 4096 + rr * 64 + ((lane & 6) << 3);
    const uint32_t ax = sm + OFF_GX + warp * 2048 + pl * 1024 + rr * 16;
    uint32_t a[20][4] = {}, h[8] = {};
    auto load_gu = [&]() {
#pragma unroll
        for (int i = 0; i < 20; i++) ldsm4t(a[i], i % 5 < 4 ? (ab ^ ((i % 5) << 4)) + (i / 5) * 1024 : ax + (i / 5) * 256);
    };
    bool gpre = false;
    {
        int it = 0;
        do {
            if (!gpre && __all_sync(0xffffffffu, mbar_test(gbar, 0))) gpre = true, load_gu();
            fetch<8, 1>(at(g0, src_x), 32, h);
        } while (missing(h) & (++it < SPIN_LIMIT));
    }
    if (warp == 0) TSL(11);
    ln_partial(h, sm + OFF_ST + g * 80 + warp * 8, t4 == 0);
    bar_sync(3, 288);
    {
        uint32_t mean2;
        float inv;
        ln_combine(sm + OFF_ST + g * 80, mean2, inv);
#pragma unroll
        for (int i = 0; i < 8; i++) h[i] = modulate2(h[i], mean2, inv, sh[i], op[i]);
    }
    if (warp == 0) TSL(12);
    if (!gpre) {
        mbar_wait(gbar, 0);
        load_gu();
    }
    if (warp == 8) TSL(17);
    {
        float acc[5][4] = {};
#pragma unroll
        for (int i = 0; i < 20; i++) mma(acc[i % 5], a[i][0], a[i][1], a[i][2], a[i][3], h[2 * (i / 5)], h[2 * (i / 5) + 1]);
#pragma unroll
        for (int m = 0; m < 5; m++) sts128f(sm + OFF_RED + m * 4608 + 2 * (reds & 0xffff), acc[m]);
    }
    bar_sync(3, 288);
    if (warp < 5) {
        float c[4] = {};
        sum_frags<9>(c, sm + OFF_RED + 2 * (reds >> 16), 512);
        const uint32_t w = movm(bmul2(silu2(pack2(c[0], c[1])), pack2(c[2], c[3])));
        if (warp < 4 || sub < 4) put1d(at(g0, dst_a), w);
        if (warp == 1) TSL(13);
    }
    if (cta < 72) {
        float r = 0.f;
#pragma unroll
        for (int i = 0; i < 8; i++) {
            const uint32_t wr = lds32(sm + OFF_WR + (warp * 32 + i * 4 + t4) * 4);
            r = fmaf(blo(h[i]), blo(wr), fmaf(bhi(h[i]), bhi(wr), r));
            if (warp * 8 + i == cta) sts32(sm + OFF_HU + lane * 4, h[i]);
        }
        r = quad_sum(r);
        if (t4 == 0) sts32(sm + OFF_RT + g * 48 + warp * 4, __float_as_uint(r));
    }

    project<1>(sm, at(g0, src_a), at(g0, dst_p), rowoff, reds, cta < 72 ? 320 : 288, warp, lane);
    if (warp == 0) TSL(14);

    if (cta < 72) {
        const uint32_t ga = sm + OFF_GB + warp * 1024 + ((lane >> 3) & 1) * 256 + (lane >> 4) * 128 + (lane & 7) * 16;
        float acc[2][4] = {};
        mbar_wait(bars + BAR_GB * 8, 0);
        if (warp == 0) TSL(22);
#pragma unroll
        for (int i = 0; i < 2; i++) {
            uint32_t w[4];
            ldsm4t(w, ga + i * 512);
            mma(acc[0], w[0], w[1], w[2], w[3], sc[4 * i], sc[4 * i + 1]);
            mma(acc[1], w[0], w[1], w[2], w[3], sc[4 * i + 2], sc[4 * i + 3]);
        }
        sts64(sm + OFF_RED + (reds & 0xffff), __float_as_uint(acc[0][0] + acc[1][2]), __float_as_uint(acc[0][1] + acc[1][3]));
        if (warp) {
            bar_arrive(7, 288);
        } else {
            bar_sync(7, 288);
            float s[2][2] = {};
#pragma unroll
            for (int w = 0; w < 9; w++) {
                const float2 v = lds64f(sm + OFF_RED + (reds & 0xffff) + w * 256);
                s[w & 1][0] += v.x;
                s[w & 1][1] += v.y;
            }
            sts32(sm + OFF_QS + lane * 4, movm(pack2(s[0][0] + s[1][0], s[0][1] + s[1][1])));
            __syncwarp();
            bar_arrive(9, 64);
        }
    }
}

typedef CUresult (*EncodeFn)(CUtensorMap*, CUtensorMapDataType, cuuint32_t, void*, const cuuint64_t*, const cuuint64_t*,
                             const cuuint32_t*, const cuuint32_t*, CUtensorMapInterleave, CUtensorMapSwizzle,
                             CUtensorMapL2promotion, CUtensorMapFloatOOBfill);

void make_map(EncodeFn enc, CUtensorMap* m, void* p, int cols, int rows, int pitch, int bc, int br, int bp, int planes, size_t pstride,
              CUtensorMapSwizzle sw, int promo) {
    cuuint64_t dims[3] = {(cuuint64_t)cols, (cuuint64_t)rows, (cuuint64_t)planes};
    cuuint64_t strides[2] = {(cuuint64_t)pitch * 2, (cuuint64_t)pstride};
    cuuint32_t box[3] = {(cuuint32_t)bc, (cuuint32_t)br, (cuuint32_t)bp};
    cuuint32_t es[3] = {1, 1, 1};
    enc(m, CU_TENSOR_MAP_DATA_TYPE_BFLOAT16, 3, p, dims, strides, box, es, CU_TENSOR_MAP_INTERLEAVE_NONE, sw,
        (CUtensorMapL2promotion)promo, CU_TENSOR_MAP_FLOAT_OOB_FILL_NONE);
}

}

extern "C" void kernel_launch(void* const* d_in, const int* in_sizes, int n_in, void* d_out, int out_size) {
    static EncodeFn enc = nullptr;
    static uint32_t* scratch = nullptr;
    if (!enc) {
        void* fn = nullptr;
        cudaDriverEntryPointQueryResult st;
        cudaGetDriverEntryPoint("cuTensorMapEncodeTiled", &fn, cudaEnableDefault, &st);
        enc = (EncodeFn)fn;
        cudaGetSymbolAddress(&fn, g_scratch);
        scratch = (uint32_t*)(((uintptr_t)fn + 8 * G_SET - 1) & ~(uintptr_t)(8 * G_SET - 1));
        cudaFuncSetAttribute(fused_kernel, cudaFuncAttributeMaxDynamicSharedMemorySize, SMEM_BYTES);
    }
    Params P;
    Maps T;
    const CUtensorMapSwizzle none = CU_TENSOR_MAP_SWIZZLE_NONE;
    const int PROMO_W = CU_TENSOR_MAP_L2_PROMOTION_L2_128B, PROMO_KV = CU_TENSOR_MAP_L2_PROMOTION_L2_256B;
    make_map(enc, &T.m[M_K], d_in[1], 64, NB * HKV * SK, DH, 64, 32, 2, 2, 128, CU_TENSOR_MAP_SWIZZLE_128B, PROMO_KV);
    make_map(enc, &T.m[M_V], d_in[2], 64, NB * HKV * SK, DH, 64, 32, 2, 2, 128, CU_TENSOR_MAP_SWIZZLE_128B, PROMO_KV);
    make_map(enc, &T.m[M_WQ], d_in[3], HQ * DH, DM, HQ * DH, 32, 192, 1, 1, 16, CU_TENSOR_MAP_SWIZZLE_64B, PROMO_W);
    make_map(enc, &T.m[M_WM], d_in[11], 6 * DM, DM, 6 * DM, 32, 192, 1, 1, 16, CU_TENSOR_MAP_SWIZZLE_64B, PROMO_W);
    make_map(enc, &T.m[M_WA], d_in[11], DM, DM, 6 * DM, 16, 192, 2, 2, DM * 2, CU_TENSOR_MAP_SWIZZLE_32B, PROMO_W);
    make_map(enc, &T.m[M_GB], d_in[11], 6 * DM, DM, 6 * DM, 8, 192, 1, 1, 16, none, PROMO_W);
    char *wg = (char*)d_in[7], *wu = (char*)d_in[8], *wo = (char*)d_in[4], *wd = (char*)d_in[9];
    P.zg = wg > wu;
    P.zo = wo > wd;
    const size_t sg = P.zg ? wg - wu : wu - wg, so = P.zo ? wo - wd : wd - wo;
    make_map(enc, &T.m[M_GU], P.zg ? wu : wg, FF, DM, FF, 32, 64, 2, 2, sg, CU_TENSOR_MAP_SWIZZLE_64B, PROMO_W);
    make_map(enc, &T.m[M_GX], P.zg ? wu : wg, FF, DM, FF, 8, 64, 2, 2, sg, none, PROMO_W);
    make_map(enc, &T.m[M_OD], P.zo ? wd : wo, DM, FF, DM, 64, 64, 1, 2, so, CU_TENSOR_MAP_SWIZZLE_128B, PROMO_W);
    make_map(enc, &T.m[M_OX], P.zo ? wd : wo, DM, FF, DM, 8, 64, 1, 2, so, none, PROMO_W);
    P.x = (const __nv_bfloat16*)d_in[0];
    P.wr = (const __nv_bfloat16*)d_in[6];
    P.c = (const __nv_bfloat16*)d_in[10];
    P.k = (const __nv_bfloat16*)d_in[1];
    P.out = (__nv_bfloat16*)d_out;
    P.scratch = scratch;
    void* args[2] = {&P, &T};
    cudaLaunchCooperativeKernel((const void*)fused_kernel, dim3(NCTA), dim3(NTHREADS), args, SMEM_BYTES, cudaStreamPerThread);
}
```

```cpp
#include <cuda_runtime.h>
#include <cuda_bf16.h>
#include <cuda.h>
#include <stdint.h>

typedef unsigned long long u64;

#define TAU 568
#define TAU_W 650
#define L_KV 3200
#define L_WO 2850
#define L_GU 2850
#define L_WD 2950
#define L_LAST 500
#define L_GB 2700
#define W_0 6
#define W_LO 2
#define W_HI 8
#define T_PACE 20
#define SMOOTH 1
#define NK0 3
#define NK1 2
#define PFK 2
#define T_CLEAR 116
#define NPING0 4
#define NPING1 16

namespace {

constexpr int NB = 8, DM = 576, HQ = 32, HKV = 16, SK = 8192, WIN = 2048, DH = 128, FF = 4608;
constexpr int NCTA = 128;
constexpr int NCW = 10;
constexpr int NTHREADS = (NCW + 2) * 32;
constexpr int TILE_BYTES = 8192, NT = 64;
constexpr int SPIN_LIMIT = 1 << 22;

constexpr int OFF_RING = 0;
constexpr int OFF_WM = 121856;
constexpr int OFF_WQ = OFF_WM + 36864;
constexpr int OFF_GU = 0;
constexpr int OFF_WD = 73728;
constexpr int OFF_GB = 114688;
constexpr int OFF_OX = 131072;
constexpr int OFF_DX = OFF_OX + 4096;
constexpr int OFF_GX = OFF_DX + 4608;
constexpr int OFF_WO = OFF_WQ;
constexpr int OFF_P = OFF_WQ + 36864;
constexpr int P_PITCH = 528;
constexpr int OFF_RED = OFF_P + 16 * P_PITCH;
constexpr int OFF_ORED = OFF_RED + 5 * 4608 - 8704;
constexpr int OFF_ST = OFF_RED + 5 * 4608;
constexpr int OFF_SM = OFF_ST + 640;
constexpr int OFF_RT = OFF_SM + 128;
constexpr int OFF_HU = OFF_RT + 384;
constexpr int OFF_QS = OFF_HU + 128;
constexpr int OFF_WR = OFF_QS + 512;
constexpr int OFF_WIN = OFF_WR + 1152;
constexpr int OFF_BAR = OFF_WIN + 16;
constexpr int BAR_FULL = 6, BAR_WO = 22, BAR_GU = 26, BAR_WD = 35, BAR_EMPTY = 40, BAR_SYNC = 56, BAR_WMF = 59, BAR_GB = 60, NBAR = 70;
constexpr int SMEM_BYTES = OFF_BAR + NBAR * 8;

constexpr int D_X1 = 0;
constexpr int D_O = 3072;
constexpr int D_ACT = D_O + 512 * 32;
constexpr int D_H = D_ACT + 576 * 32;
constexpr int D_Q = D_H + 3072;
constexpr int G_M = 2 * (D_Q + NB * HQ * 64);
constexpr int G_SIDE = G_M + 216 * 32;
constexpr int G_CNT = G_SIDE + 72 * 8;
constexpr int G_SET = 1 << 18;
__device__ __forceinline__ int d_part(int unit) { return (64 + unit + (unit & 64)) * 1024; }
constexpr int D_PING = 200 * 1024;
constexpr int G_EPOCH = 201 * 2048;
static_assert(G_CNT < 64 * 2048, "scratch layout");
__device__ uint32_t g_scratch[4 * G_SET];
__device__ __forceinline__ int dual(int w) { return w + (w & ~1023); }
__device__ __forceinline__ int near(int w, int side) { return dual(w) + (((__popc(w & 0x16400) ^ side) & 1) << 10); }

#define TI(i)
#define TS(i)
#define TSL(i)

enum { M_K, M_V, M_GU, M_GX, M_OD, M_OX, M_WQ, M_WM, M_WA, M_GB, NMAP };
struct Params {
    const __nv_bfloat16 *c, *x, *k;
    __nv_bfloat16* out;
    uint32_t* scratch;
    const __nv_bfloat16* wr;
    int zg, zo;
};
struct Maps {
    CUtensorMap m[NMAP];
};

__device__ __forceinline__ void mbar_init(uint32_t bar, int cnt) {
    asm volatile("mbarrier.init.shared::cta.b64 [%0], %1;" ::"r"(bar), "r"(cnt));
}
__device__ __forceinline__ void mbar_expect(uint32_t bar, uint32_t bytes) {
    asm volatile("mbarrier.arrive.expect_tx.shared::cta.b64 _, [%0], %1;" ::"r"(bar), "r"(bytes) : "memory");
}
__device__ __forceinline__ void mbar_arrive(uint32_t bar) {
    asm volatile("mbarrier.arrive.shared::cta.b64 _, [%0];" ::"r"(bar) : "memory");
}
__device__ __forceinline__ void mbar_wait(uint32_t bar, uint32_t parity) {
    asm volatile("{\n.reg .pred p;\n.reg .u32 c;\n"
                 "mbarrier.try_wait.parity.shared::cta.b64 p, [%0], %1;\n@p bra DONE;\nmov.u32 c, %2;\n"
                 "AGAIN:\nmbarrier.try_wait.parity.shared::cta.b64 p, [%0], %1;\nsub.u32 c, c, 1;\n"
                 "setp.eq.or.u32 p, c, 0, p;\n@!p bra AGAIN;\nDONE:\n}"
                 ::"r"(bar), "r"(parity), "n"(SPIN_LIMIT) : "memory");
}
__device__ __forceinline__ bool mbar_test(uint32_t bar, uint32_t parity) {
    uint32_t ok;
    asm volatile("{\n.reg .pred p;\nmbarrier.test_wait.parity.shared::cta.b64 p, [%1], %2;\nselp.u32 %0, 1, 0, p;\n}"
                 : "=r"(ok) : "r"(bar), "r"(parity) : "memory");
    return ok;
}
__device__ __forceinline__ void tma3d_hint(uint32_t dst, const CUtensorMap* m, int x, int y, int z, uint32_t bar, u64 pol) {
    asm volatile("cp.async.bulk.tensor.3d.shared::cluster.global.mbarrier::complete_tx::bytes.L2::cache_hint"
                 " [%0], [%1, {%2, %3, %4}], [%5], %6;"
                 ::"r"(dst), "l"(m), "r"(x), "r"(y), "r"(z), "r"(bar), "l"(pol) : "memory");
}
__device__ __forceinline__ void tma3d(uint32_t dst, const CUtensorMap* m, int x, int y, int z, uint32_t bar) {
    asm volatile("cp.async.bulk.tensor.3d.shared::cluster.global.mbarrier::complete_tx::bytes [%0], [%1, {%2, %3, %4}], [%5];"
                 ::"r"(dst), "l"(m), "r"(x), "r"(y), "r"(z), "r"(bar) : "memory");
}
__device__ __forceinline__ void bar_sync(int id, int n) { asm volatile("bar.sync %0, %1;" ::"r"(id), "r"(n) : "memory"); }
__device__ __forceinline__ void bar_arrive(int id, int n) { asm volatile("bar.arrive %0, %1;" ::"r"(id), "r"(n) : "memory"); }
__device__ __forceinline__ void ldsm4(uint32_t (&r)[4], uint32_t a) {
    asm volatile("ldmatrix.sync.aligned.m8n8.x4.shared.b16 {%0,%1,%2,%3}, [%4];"
                 : "=r"(r[0]), "=r"(r[1]), "=r"(r[2]), "=r"(r[3]) : "r"(a) : "memory");
}
__device__ __forceinline__ void ldsm4t(uint32_t (&r)[4], uint32_t a) {
    asm volatile("ldmatrix.sync.aligned.m8n8.x4.trans.shared.b16 {%0,%1,%2,%3}, [%4];"
                 : "=r"(r[0]), "=r"(r[1]), "=r"(r[2]), "=r"(r[3]) : "r"(a) : "memory");
}
__device__ __forceinline__ void mma(float (&c)[4], uint32_t a0, uint32_t a1, uint32_t a2, uint32_t a3, uint32_t b0, uint32_t b1) {
    asm volatile("mma.sync.aligned.m16n8k16.row.col.f32.bf16.bf16.f32 {%0,%1,%2,%3}, {%4,%5,%6,%7}, {%8,%9}, {%0,%1,%2,%3};"
                 : "+f"(c[0]), "+f"(c[1]), "+f"(c[2]), "+f"(c[3])
                 : "r"(a0), "r"(a1), "r"(a2), "r"(a3), "r"(b0), "r"(b1));
}
__device__ __forceinline__ uint32_t movm(uint32_t a) {
    uint32_t d;
    asm volatile("movmatrix.sync.aligned.m8n8.trans.b16 %0, %1;" : "=r"(d) : "r"(a));
    return d;
}
__device__ __forceinline__ uint32_t lds32(uint32_t a) { uint32_t v; asm volatile("ld.volatile.shared.b32 %0, [%1];" : "=r"(v) : "r"(a) : "memory"); return v; }
__device__ __forceinline__ float2 lds64f(uint32_t a) { float2 v; asm volatile("ld.shared.v2.f32 {%0,%1}, [%2];" : "=f"(v.x), "=f"(v.y) : "r"(a) : "memory"); return v; }
__device__ __forceinline__ uint4 lds128(uint32_t a) { uint4 v; asm volatile("ld.shared.v4.b32 {%0,%1,%2,%3}, [%4];" : "=r"(v.x), "=r"(v.y), "=r"(v.z), "=r"(v.w) : "r"(a) : "memory"); return v; }
__device__ __forceinline__ void sts32(uint32_t a, uint32_t v) { asm volatile("st.shared.b32 [%0], %1;" ::"r"(a), "r"(v) : "memory"); }
__device__ __forceinline__ void sts16(uint32_t a, uint16_t v) { asm volatile("st.shared.b16 [%0], %1;" ::"r"(a), "h"(v) : "memory"); }
__device__ __forceinline__ void sts64(uint32_t a, uint32_t x, uint32_t y) { asm volatile("st.shared.v2.b32 [%0], {%1,%2};" ::"r"(a), "r"(x), "r"(y) : "memory"); }
__device__ __forceinline__ void sts128(uint32_t a, uint32_t x, uint32_t y, uint32_t z, uint32_t w) {
    asm volatile("st.shared.v4.b32 [%0], {%1,%2,%3,%4};" ::"r"(a), "r"(x), "r"(y), "r"(z), "r"(w) : "memory");
}
__device__ __forceinline__ void sts128f(uint32_t a, const float (&c)[4]) {
    sts128(a, __float_as_uint(c[0]), __float_as_uint(c[1]), __float_as_uint(c[2]), __float_as_uint(c[3]));
}

__device__ __forceinline__ float sel4(const float (&c)[4], int t) { return (t & 2) ? ((t & 1) ? c[3] : c[2]) : ((t & 1) ? c[1] : c[0]); }

template <int LUT>
__device__ __forceinline__ uint32_t lop3(uint32_t a, uint32_t b, uint32_t c) {
    uint32_t d;
    asm("lop3.b32 %0, %1, %2, %3, %4;" : "=r"(d) : "r"(a), "r"(b), "r"(c), "n"(LUT));
    return d;
}
__device__ __forceinline__ uint32_t pin(uint32_t v) { return __shfl_xor_sync(0xffffffffu, v, 0); }
template <typename T>
__device__ __forceinline__ T* at(T* base, uint32_t bytes) { return (T*)((const char*)base + bytes); }

__device__ __forceinline__ uint32_t clock32(uint32_t dep) {
    uint32_t t;
    asm volatile("{\n.reg .pred p;\nsetp.eq.u32 p, %1, 0x9e3779b9;\n@p nanosleep.u32 1;\nmov.u32 %0, %clock;\n}" : "=r"(t) : "r"(dep) : "memory");
    return t;
}

__device__ __forceinline__ uint32_t nz(uint32_t v) { return v ? v : 0x80000000u; }
__device__ __forceinline__ void st1(uint32_t* p, uint32_t a) { asm volatile("st.relaxed.gpu.global.b32 [%0], %1;" ::"l"(p), "r"(a) : "memory"); }
__device__ __forceinline__ void st2(uint32_t* p, uint32_t a, uint32_t b) {
    asm volatile("st.relaxed.gpu.global.v2.b32 [%0], {%1,%2};" ::"l"(p), "r"(a), "r"(b) : "memory");
}
__device__ __forceinline__ void zero4(uint32_t* p) { asm volatile("st.relaxed.gpu.global.v4.b32 [%0], {%1,%1,%1,%1};" ::"l"(p), "r"(0) : "memory"); }
__device__ __forceinline__ void put1d(uint32_t* p, uint32_t a) { a = nz(a), st1(p, a), st1(p + 1024, a); }
__device__ __forceinline__ void put2d(uint32_t* p, uint32_t a, uint32_t b) { a = nz(a), b = nz(b), st2(p, a, b), st2(p + 1024, a, b); }
__device__ __forceinline__ uint32_t ld1(const uint32_t* p) {
    uint32_t v;
    asm volatile("ld.relaxed.gpu.global.b32 %0, [%1];" : "=r"(v) : "l"(p) : "memory");
    return v;
}
template <int N, int V>
__device__ __forceinline__ void fetch(const uint32_t* p, int stride, uint32_t (&a)[N * V]) {
#pragma unroll
    for (int i = 0; i < N; i++) {
        if (V == 1)
            asm volatile("{\n.reg .pred p;\nsetp.eq.u32 p, %0, 0;\n@p ld.relaxed.gpu.global.b32 %0, [%1];\n}"
                         : "+r"(a[i]) : "l"(p + i * stride) : "memory");
        if (V == 4)
            asm volatile("{\n.reg .pred p;\nsetp.eq.u32 p, %4, 0;\n@p ld.relaxed.gpu.global.v4.b32 {%0,%1,%2,%3}, [%5];\n}"
                         : "+r"(a[V * i]), "+r"(a[V * i + V / 4]), "+r"(a[V * i + V / 2]), "+r"(a[V * i + V - 1])
                         : "r"(min(min(a[V * i], a[V * i + V / 4]), min(a[V * i + V / 2], a[V * i + V - 1]))), "l"(p + i * stride) : "memory");
    }
}
template <int N>
__device__ __forceinline__ bool missing(const uint32_t (&a)[N]) {
    uint32_t lo = a[0];
#pragma unroll
    for (int i = 1; i < N; i++) lo = min(lo, a[i]);
    return __any_sync(0xffffffffu, lo == 0);
}
template <int N, int V>
__device__ __forceinline__ void get(const uint32_t* p, int stride, uint32_t (&a)[N * V]) {
    int it = 0;
    do fetch<N, V>(p, stride, a);
    while (missing(a) & (++it < SPIN_LIMIT));
}
__device__ __forceinline__ void cp16(uint32_t dst, const void* src) {
    asm volatile("cp.async.cg.shared.global [%0], [%1], 16;" ::"r"(dst), "l"(src) : "memory");
}

__device__ __forceinline__ uint32_t pack2(float lo, float hi) {
    uint32_t r;
    asm("cvt.rn.bf16x2.f32 %0, %1, %2;" : "=r"(r) : "f"(hi), "f"(lo));
    return r;
}
__device__ __forceinline__ float rbf(float x) { return __uint_as_float(pack2(0.f, x)); }
__device__ __forceinline__ float blo(uint32_t v) { return __uint_as_float(v << 16); }
__device__ __forceinline__ float bhi(uint32_t v) { return __uint_as_float(v & 0xffff0000u); }
__device__ __forceinline__ uint32_t badd2(uint32_t a, uint32_t b) { uint32_t r; asm("add.rn.bf16x2 %0, %1, %2;" : "=r"(r) : "r"(a), "r"(b)); return r; }
__device__ __forceinline__ uint32_t bsub2(uint32_t a, uint32_t b) { uint32_t r; asm("sub.rn.bf16x2 %0, %1, %2;" : "=r"(r) : "r"(a), "r"(b)); return r; }
__device__ __forceinline__ uint32_t bmul2(uint32_t a, uint32_t b) { uint32_t r; asm("mul.rn.bf16x2 %0, %1, %2;" : "=r"(r) : "r"(a), "r"(b)); return r; }
__device__ __forceinline__ float ex2(float x) { float r; asm("ex2.approx.ftz.f32 %0, %1;" : "=f"(r) : "f"(x)); return r; }
__device__ __forceinline__ float rcp(float x) { float r; asm("rcp.approx.ftz.f32 %0, %1;" : "=f"(r) : "f"(x)); return r; }
__device__ __forceinline__ float sqrt_f(float x) { float r; asm("sqrt.approx.ftz.f32 %0, %1;" : "=f"(r) : "f"(x)); return r; }
constexpr float LOG2E = 1.4426950408889634f;
constexpr uint32_t ONE2 = 0x3f803f80u;
__device__ __forceinline__ float sigmoid_f(float x) { return rcp(1.0f + ex2(-LOG2E * x)); }
__device__ __forceinline__ uint32_t silu2(uint32_t v) {
    const float a = blo(v), b = bhi(v);
    return pack2(a * sigmoid_f(a), b * sigmoid_f(b));
}
__device__ __forceinline__ float quad_sum(float v) {
    v += __shfl_xor_sync(0xffffffffu, v, 1);
    return v + __shfl_xor_sync(0xffffffffu, v, 2);
}
__device__ __forceinline__ void ln_partial(const uint32_t (&v)[8], uint32_t dst, bool writer) {
    float s0 = 0.f, s1 = 0.f;
#pragma unroll
    for (int i = 0; i < 8; i++) {
        s0 += blo(v[i]);
        s1 += bhi(v[i]);
    }
    const float mean = quad_sum(s0 + s1) * (1.0f / 64);
    s0 = s1 = 0.f;
#pragma unroll
    for (int i = 0; i < 8; i++) {
        const float a = blo(v[i]) - mean, b = bhi(v[i]) - mean;
        s0 = fmaf(a, a, s0);
        s1 = fmaf(b, b, s1);
    }
    s0 = quad_sum(s0 + s1);
    if (writer) sts64(dst, __float_as_uint(mean), __float_as_uint(s0));
}
__device__ __forceinline__ void ln_combine(uint32_t src, uint32_t& mean2, float& inv) {
    float m[10], q0 = 0.f, q1 = 0.f, s = 0.f;
#pragma unroll
    for (int i = 0; i < 5; i++) {
        const uint4 v = lds128(src + i * 16);
        m[2 * i] = __uint_as_float(v.x);
        m[2 * i + 1] = __uint_as_float(v.z);
        q0 += __uint_as_float(v.y);
        if (i < 4) q1 += __uint_as_float(v.w);
    }
    const float mean = (((m[0] + m[1]) + (m[2] + m[3])) + ((m[4] + m[5]) + (m[6] + m[7])) + m[8]) * (1.0f / 9);
#pragma unroll
    for (int i = 0; i < 9; i++) s = fmaf(m[i] - mean, m[i] - mean, s);
    const float var = fmaf(s, 64.f, q0 + q1) * (1.0f / DM);
    mean2 = pack2(mean, mean);
    inv = rcp(rbf(sqrt_f(rbf(rbf(var) + 1e-5f))));
}
__device__ __forceinline__ uint32_t modulate2(uint32_t x, uint32_t mean2, float inv, uint32_t shift, uint32_t onep) {
    const uint32_t d = bsub2(x, mean2);
    return badd2(bmul2(pack2(blo(d) * inv, bhi(d) * inv), onep), shift);
}
template <int N>
__device__ __forceinline__ void sum_frags(float (&c)[4], uint32_t addr, int stride) {
#pragma unroll
    for (int w = 0; w < N; w++) {
        const uint4 v = lds128(addr + w * stride);
        c[0] += __uint_as_float(v.x); c[1] += __uint_as_float(v.y);
        c[2] += __uint_as_float(v.z); c[3] += __uint_as_float(v.w);
    }
}

template <int ST>
__device__ __forceinline__ void project(uint32_t sm, const uint32_t* src, uint32_t* dst, uint32_t rowoff, uint32_t reds, int nsync, int warp, int lane) {
    constexpr int NW = ST ? 9 : 8;
    const uint32_t red = sm + (ST ? OFF_WO : OFF_P);
    if (warp < NW) {
        const uint32_t wbar = sm + OFF_BAR + (ST ? BAR_WD + (warp < 8 ? ((warp >> 1) + 1) & 3 : 4) : BAR_WO + (warp >> 1)) * 8;
        const uint32_t ab = sm + (ST ? OFF_WD : OFF_WO) + rowoff;
        const uint32_t ax = sm + (ST ? OFF_DX : OFF_OX) + ((rowoff >> 7) << 4);
        uint32_t a[10][4] = {}, b[4] = {};
        bool have_w = false, need_b = true;
        int it = 0;
        do {
            if (!need_b) mbar_wait(wbar, 0);
            if (!need_b || (!have_w && __all_sync(0xffffffffu, mbar_test(wbar, 0)))) {
                have_w = true;
#pragma unroll
                for (int i = 0; i < 10; i++) ldsm4t(a[i], i % 5 < 4 ? (ab ^ ((i % 5) << 5)) + (i / 5) * 2048 : ax + (i / 5) * 256);
                if (!need_b) break;
            }
            if (ST) fetch<4, 1>(src, 32, b);
            else fetch<1, 4>(src, 0, b);
            need_b = missing(b) & (++it < SPIN_LIMIT);
        } while (need_b | !have_w);
        if (warp == 0) TSL(ST ? 24 : 21);
        float acc[5][4] = {};
#pragma unroll
        for (int i = 0; i < 10; i++) mma(acc[i % 5], a[i][0], a[i][1], a[i][2], a[i][3], b[2 * (i / 5)], b[2 * (i / 5) + 1]);
#pragma unroll
        for (int u = 0; u < 9; u++)
            sts64(red + u * 2304 + (reds & 0xffff), __float_as_uint(acc[u >> 1][2 * (u & 1)]), __float_as_uint(acc[u >> 1][2 * (u & 1) + 1]));
    }
    bar_sync(ST ? 6 : 3, nsync);
    float s[2][2] = {};
#pragma unroll
    for (int w = 0; w < NW; w++) {
        const float2 v = lds64f(red + (reds >> 16) + w * 256);
        s[w & 1][0] += v.x;
        s[w & 1][1] += v.y;
    }
    const uint32_t p0 = (__float_as_uint(s[0][0] + s[1][0]) | 1) ^ ST, p1 = (__float_as_uint(s[0][1] + s[1][1]) | 1) ^ ST;
    st2(dst, p0, p1);
}

template <int ST, typename F>
__device__ __forceinline__ uint32_t reduce16(const uint32_t* src, F arrived) {
    uint32_t a[32] = {}, bad[16], any;
    int it = 0;
#pragma unroll
    for (int i = 0; i < 16; i++) bad[i] = 1;
    do {
#pragma unroll
        for (int i = 0; i < 16; i++)
            asm volatile("{\n.reg .pred p;\nsetp.ne.u32 p, %2, 0;\n@p ld.relaxed.gpu.global.v2.b32 {%0,%1}, [%3];\n}"
                         : "+r"(a[2 * i]), "+r"(a[2 * i + 1]) : "r"(bad[i]), "l"(src + i * 64) : "memory");
#pragma unroll
        for (int i = 0; i < 16; i++) bad[i] = lop3<ST ? 0xa8 : 0x2a>(a[2 * i], a[2 * i + 1], 1);
        any = lop3<0xfe>(lop3<0xfe>(lop3<0xfe>(bad[0], bad[1], bad[2]), lop3<0xfe>(bad[3], bad[4], bad[5]), lop3<0xfe>(bad[6], bad[7], bad[8])),
                         lop3<0xfe>(lop3<0xfe>(bad[9], bad[10], bad[11]), lop3<0xfe>(bad[12], bad[13], bad[14]), bad[15]), 0);
    } while (__any_sync(0xffffffffu, any != 0) & (++it < SPIN_LIMIT));
    arrived();
    float f[8];
#pragma unroll
    for (int i = 0; i < 8; i++)
        f[i] = (__uint_as_float(a[i]) + __uint_as_float(a[i + 8])) + (__uint_as_float(a[i + 16]) + __uint_as_float(a[i + 24]));
    f[0] = (f[0] + f[2]) + (f[4] + f[6]);
    f[1] = (f[1] + f[3]) + (f[5] + f[7]);
    return movm(pack2(f[0], f[1]));
}

__global__ void __launch_bounds__(NTHREADS, 1) fused_kernel(const Params P, const __grid_constant__ Maps T) {
    extern __shared__ __align__(1024) char smem_raw[];
    constexpr uint32_t sm = 1024;
    const int tid = threadIdx.x, lane = tid & 31;
    const int cta = blockIdx.x, grp = cta >> 3, sub = cta & 7;
    const uint32_t bars = sm + OFF_BAR;
    const int row0 = (sub * HKV + grp) * SK + (SK - WIN);
    if (tid >> 5 == 9) {
#pragma unroll
        for (int i = 0; i < PFK; i++) asm volatile("prefetch.global.L2 [%0];" ::"l"(P.k + (size_t)row0 * DH + (lane + i * 32) * 64) : "memory");
    }
    u64 pol;
    asm volatile("createpolicy.fractional.L2::evict_first.b64 %0, 1.0;" : "=l"(pol));
    if (tid == NCW * 32) {
        TS(0);
        const int n0 = cta < 90 ? 0 : 3;
#pragma unroll
        for (int i = 0; i < 6; i++) mbar_init(bars + i * 8, 1);
        asm volatile("fence.mbarrier_init.release.cluster;" ::: "memory");
#pragma unroll
        for (int i = 0; i < 3; i++) {
            mbar_expect(bars + (n0 + i) * 8, 12288);
            tma3d(sm + OFF_WM + (n0 + i) * 12288, &T.m[cta < 36 ? M_WA : cta < 90 ? M_WM : M_WQ], cta < 36 ? 16 * cta : 32 * cta,
                  i * 192, 0, bars + (n0 + i) * 8);
            TI(n0 + i);
        }
        TS(26);
    }
    if (tid == NCW * 32 + 32) {
#pragma unroll
        for (int i = 0; i < 4; i++) mbar_init(bars + (BAR_FULL + i) * 8, 1);
        asm volatile("fence.mbarrier_init.release.cluster;" ::: "memory");
#pragma unroll
        for (int t = 0; t < NK0; t++) {
            mbar_expect(bars + (BAR_FULL + t) * 8, TILE_BYTES);
            tma3d_hint(sm + OFF_RING + t * TILE_BYTES, &T.m[M_K], 0, row0 + t * 32, 0, bars + (BAR_FULL + t) * 8, pol);
            TI(6 + t);
        }
    }
    if (tid < 288 && cta < 90) {
#pragma unroll
        for (int i = 0; i < 2; i++) {
            const int row = (lane >> 3) + 4 * i, so = row * DM + (tid >> 5) * 64 + (lane & 7) * 8;
            const uint32_t d = sm + OFF_RED + (tid >> 5) * 2048 + row * 128 + (((lane & 7) ^ row) << 4);
            cp16(d, P.c + so);
            if (cta < 36) cp16(d + 1024, P.x + so);
        }
    }
    uint32_t* const g0 = P.scratch;
    const uint32_t epoch = ld1(g0 + G_EPOCH);
    const int warp = __shfl_sync(0xffffffffu, tid >> 5, 0);

    if (warp >= NCW) {
        const int pw = warp - NCW;
        bar_arrive(1, (NCW + 1) * 32);
        if (pw && lane < M_WQ) asm volatile("prefetch.tensormap [%0];" ::"l"(&T.m[M_WQ - lane]) : "memory");
        if (tid == NCW * 32) sts32(sm + OFF_WIN, 0);
        __syncwarp();
        bar_sync(15, NTHREADS);
        if (lane == 0) {
            if (pw == 0 && cta < 90) {
#pragma unroll 1
                for (int n = 3; n < 6; n++) {
                    mbar_expect(bars + n * 8, 12288);
                    mbar_wait(bars + (n - 3) * 8, 0);
                    tma3d(sm + OFF_WM + n * 12288, &T.m[M_WQ], 32 * cta, (n - 3) * 192, 0, bars + n * 8);
                    TI(n);
                }
            }
#pragma unroll 1
            for (int t = NK0 + (1 - pw) * NK1; t < NK0 + NK1 + 3 * (1 - pw); t++) {
                mbar_expect(bars + (BAR_FULL + t) * 8, TILE_BYTES);
                mbar_wait(bars + (t + (pw ? BAR_FULL - NK1 : 3 - NK0 - NK1)) * 8, 0);
                tma3d_hint(sm + OFF_RING + t * TILE_BYTES, &T.m[M_K], 0, row0 + t * 32, 0, bars + (BAR_FULL + t) * 8, pol);
                TI(6 + t);
            }
            if (pw == 0) {
                auto on_time = [&](int due, uint32_t bar, uint32_t parity) {
                    uint32_t origin;
                    do origin = lds32(sm + OFF_WIN);
                    while (origin && (int)(clock32(0) - origin - due) < 0 && !mbar_test(bar, parity));
                };
#pragma unroll 1
                for (int t = NK0 + NK1 + 3; t < 2 * NT; t++) {
                    if (t == 14 && cta < 90) mbar_wait(bars + BAR_WMF * 8, 0);
                    if (t == 15) TS(30);
                    const uint32_t fb = bars + (BAR_FULL + (t & 15)) * 8;
                    const int hi = t - (lds32(sm + OFF_WIN) ? W_HI : W_0), lo = t - W_LO;
                    mbar_wait(fb + (BAR_EMPTY - BAR_FULL) * 8, (~t >> 4) & 1);
                    mbar_expect(fb, TILE_BYTES);
                    mbar_wait(bars + (BAR_FULL + (hi & 15)) * 8, (hi >> 4) & 1);
                    on_time(t * TAU - L_KV, bars + (BAR_FULL + (lo & 15)) * 8, (lo >> 4) & 1);
                    tma3d_hint(sm + OFF_RING + (t & 15) * TILE_BYTES, &T.m[t >> 6], 0, row0 + (t & (NT - 1)) * 32, 0, fb, pol);
                    TI(6 + t);
                    if (t == T_CLEAR) mbar_arrive(bars + (BAR_SYNC + 1) * 8);
                }
                mbar_wait(bars + BAR_SYNC * 8, 0);
                auto window = [&](int b, int lead) {
                    mbar_wait(bars + (b - W_HI) * 8, b - W_HI < BAR_WO);
                    on_time((2 * NT - 1) * TAU + (b - BAR_WO + 1) * TAU_W - lead, bars + (b - W_LO) * 8, b - W_LO < BAR_WO);
                };
#pragma unroll 1
                for (int i = 0; i < 4; i++) {
                    window(BAR_WO + i, L_WO);
                    tma3d(sm + OFF_WO + i * 8192, &T.m[M_OD], 64 * sub, grp * 256 + i * 64, P.zo, bars + (BAR_WO + i) * 8);
                    tma3d(sm + OFF_OX + i * 1024, &T.m[M_OX], 512 + 8 * sub, grp * 256 + i * 64, P.zo, bars + (BAR_WO + i) * 8);
                    TI(134 + i);
                }
                TS(28);
#pragma unroll 1
                for (int i = 0; i < 9; i++) {
                    mbar_wait(bars + (BAR_EMPTY + i) * 8, 1);
                    window(BAR_GU + i, L_GU);
                    tma3d(sm + OFF_GU + i * 8192, &T.m[M_GU], grp * 288 + 32 * sub, i * 64, 0, bars + (BAR_GU + i) * 8);
                    if (sub < 4) tma3d(sm + OFF_GX + i * 2048, &T.m[M_GX], grp * 288 + 256 + 8 * sub, i * 64, 0, bars + (BAR_GU + i) * 8);
                    TI(138 + i);
                }
                TS(29);
#pragma unroll 1
                for (int i = 0; i < 5; i++) {
                    const int blk = i < 4 ? (i + 3) & 3 : 4, r = min(blk * 64, 224);
                    mbar_wait(bars + (BAR_EMPTY + 9 + blk) * 8, 1);
                    window(BAR_WD + i, L_WD + (i == 4 ? L_LAST : 0));
                    tma3d(sm + OFF_WD + r * 128, &T.m[M_OD], 64 * sub, grp * 288 + r, P.zo ^ 1, bars + (BAR_WD + i) * 8);
                    tma3d(sm + OFF_DX + r * 16, &T.m[M_OX], 512 + 8 * sub, grp * 288 + r, P.zo ^ 1, bars + (BAR_WD + i) * 8);
                    TI(147 + i);
                }
                if (cta < 72) {
                    mbar_wait(bars + (BAR_EMPTY + 14) * 8, 1);
                    mbar_wait(bars + (BAR_EMPTY + 15) * 8, 1);
                    mbar_expect(bars + BAR_GB * 8, 9216);
                    window(BAR_WD + 5, L_GB);
#pragma unroll
                    for (int i = 0; i < 3; i++) tma3d(sm + OFF_GB + i * 3072, &T.m[M_GB], 5 * DM + 8 * cta, i * 192, 0, bars + BAR_GB * 8);
                }
            } else {
#pragma unroll 1
                for (int i = BAR_WO; i < BAR_WD + 5; i++) mbar_expect(bars + i * 8, i < BAR_GU || i >= BAR_WD ? 9216 : sub < 4 ? 10240 : 8192);
                mbar_arrive(bars + BAR_SYNC * 8);
                uint32_t* const cnt = g0 + (epoch & 1) * G_SET + G_CNT;
                uint32_t origin = 0;
#pragma unroll 1
                for (int t = cta & 3; t < 144; t += 4) {
                    const uint32_t bar = bars + (BAR_FULL + (t < 2 * NT ? t & 15 : t - 112)) * 8;
                    mbar_wait(bar, (t >> 4) & 1);
                    if (t < 2 * NT) mbar_arrive(bar + (BAR_EMPTY - BAR_FULL) * 8);
                    const uint32_t t0 = clock32(0);
                    const int c = (int)atomicAdd(cnt, 1u) - 16;
                    const uint32_t o = t0 + ((clock32(c) - t0) >> 1) - ((c * TAU + max(c - 32 * (2 * NT - 1), 0) * (TAU_W - TAU)) >> 5);
                    if (t < T_PACE) continue;
                    origin = (origin ? origin + ((int)(o - origin) >> SMOOTH) : o) | 1;
                    sts32(sm + OFF_WIN, origin);
                }
            }
        }
        return;
    }

    if (lane == 0) {
#pragma unroll
        for (int i = 0; i < 6; i++) {
            const int b = 10 + warp * 6 + i;
            mbar_init(bars + b * 8, b >= BAR_EMPTY && b < BAR_EMPTY + 16 && ((b ^ cta) & 3) == 0 ? 2 : 1);
        }
        asm volatile("fence.mbarrier_init.release.cluster;" ::: "memory");
    }
    __syncwarp();
    if (warp < 9) bar_arrive(15, NTHREADS);
    const int g = lane >> 2, t4 = lane & 3;
    uint32_t* const gs = g0 + (epoch & 1) * G_SET;

    uint32_t sc[8] = {};
    if (warp < 9) {
        const int off_h = (cta < 36 ? dual(D_H + 2 * cta * 32) : G_M + 4 * (cta - 36) * 32) + tid;
        const int off_h2 = off_h + (cta < 36 ? 1024 : 64);
        const int off_q = dual(D_Q + g * (HQ * 64) + cta * 16) + warp * 8 + t4 * 2;
        uint32_t bf[8] = {}, xp = 0, mean2 = 0;
        float inv = 0.f;
        if (cta < 36) xp = __ldg(reinterpret_cast<const uint32_t*>(P.x) + g * (DM / 2) + 8 * cta + 4 * (warp & 1) + t4);
        if (warp < 2) {
            st2(gs + off_q, 0, 0), st2(gs + off_q + 1024, 0, 0);
            if (cta < 36) st1(gs + off_h, 0), st1(gs + off_h2, 0);
        }
        if (cta < 90) {
            asm volatile("cp.async.wait_all;" ::: "memory");
            __syncwarp();
            const uint32_t fa = sm + OFF_RED + warp * 2048 + (lane & 7) * 128 + (((lane >> 3) ^ (lane & 7)) << 4);
            ldsm4(reinterpret_cast<uint32_t(&)[4]>(bf[0]), fa);
            ldsm4(reinterpret_cast<uint32_t(&)[4]>(bf[4]), fa ^ 64);
            if (cta < 36) {
                uint32_t xv[8];
                ldsm4(reinterpret_cast<uint32_t(&)[4]>(xv[0]), fa + 1024);
                ldsm4(reinterpret_cast<uint32_t(&)[4]>(xv[4]), (fa ^ 64) + 1024);
                ln_partial(xv, sm + OFF_ST + g * 80 + warp * 8, t4 == 0);
            }
#pragma unroll
            for (int i = 0; i < 8; i++) sc[i] = bf[i] = silu2(bf[i]);
        }
        if (warp == 0) TSL(18);
        bar_sync(1, (NCW + 1) * 32);
        if (cta < 36 && warp < 2) ln_combine(sm + OFF_ST + g * 80, mean2, inv);
        const int r = warp * 64 + (lane >> 4) * 8 + (lane & 7), hi8 = (lane >> 3) & 1, box = warp / 3;
#pragma unroll 1
        for (int pass = cta < 90 ? 0 : 1; pass < 2; pass++) {
            const bool pa = pass == 0 && cta < 36;
            const uint32_t ab = sm + OFF_WM + pass * 36864 +
                                (pa ? (box + hi8) * 6144 + r * 32 + ((lane & 4) << 2) : r * 64 + (((2 * hi8) ^ ((r >> 1) & 3)) << 4));
            const uint32_t as = pa ? 512 : 1024, red = sm + OFF_RED + pass * 9216;
            mbar_wait(bars + (pass * 3 + box) * 8, 0);
            if (warp == 8) TSL(pass ? 31 : 19);
            uint32_t a[4][2][4];
#pragma unroll
            for (int i = 0; i < 4; i++) {
                ldsm4t(a[i][0], ab + i * as);
                ldsm4t(a[i][1], (ab ^ 16) + i * as);
            }
            if (pass) {
                bar_sync(8, NCW * 32);
#pragma unroll
                for (int i = 0; i < 8; i++) bf[i] = 0;
                const uint32_t* const src_h = gs + near(D_H + warp * 256, lds32(sm + OFF_WIN + 4)) + lane;
                get<1, 1>(src_h, 0, reinterpret_cast<uint32_t(&)[1]>(bf[0]));
                get<8, 1>(src_h, 32, bf);
                if (warp == 0) TSL(3);
            }
            float acc[2][4] = {};
#pragma unroll
            for (int i = 0; i < 4; i++)
#pragma unroll
                for (int m = 0; m < 2; m++) mma(acc[m], a[i][m][0], a[i][m][1], a[i][m][2], a[i][m][3], bf[2 * i], bf[2 * i + 1]);
            sts128f(red + tid * 16, acc[0]);
            sts128f(red + 4608 + tid * 16, acc[1]);
            bar_sync(3, 288);
            if (warp < 2) {
                float c[4] = {};
                sum_frags<9>(c, red + warp * 4608 + lane * 16, 512);
                uint32_t lo = movm(pack2(c[0], c[1])), hi = movm(pack2(c[2], c[3]));
                if (pass) {
                    put2d(gs + off_q, lo, hi);
                    if (warp == 0) TSL(4);
                } else {
                    const uint32_t hi1 = badd2(hi, ONE2);
                    if (pa) hi = lo = modulate2(xp, mean2, inv, lo, hi1);
                    if (cta >= 72) lo = badd2(lo, ONE2), hi = hi1;
                    st1(gs + off_h, nz(lo));
                    st1(gs + off_h2, nz(hi));
                    if (warp == 0 && pa) TSL(2);
                }
            } else if (tid == 64 && pass == 0) {
                mbar_arrive(bars + BAR_WMF * 8);
            }
        }
    } else {
        if ((uint32_t)__cvta_generic_to_shared(smem_raw) != sm) __trap();
        uint32_t* const ping = g0 + dual(D_PING) + cta * 8;
        if (lane < 16) st1(ping + (lane >> 3) * 1024 + (lane & 7), 0);
        bar_sync(15, NTHREADS);
        uint32_t best[2] = {~0u, ~0u}, v = 0;
#pragma unroll 1
        for (int part = 0; part < 2; part++) {
            if (lane == 0) {
#pragma unroll 1
                for (int r = part ? NPING1 : NPING0; r > 0; r--) {
#pragma unroll
                    for (int k = 0; k < 2; k++) {
                        const uint32_t t0 = clock32(v);
                        v = atomicExch(ping + k * 1024, t0);
                        best[k] = min(best[k], clock32(v) - t0);
                    }
                }
                sts32(sm + OFF_WIN + 4 + 4 * part, ((best[1] < best[0]) ^ __popc(D_PING & 0x16400)) & 1);
            }
            __syncwarp();
            if (part) break;
            TSL(20);
            bar_arrive(8, NCW * 32);
            mbar_wait(bars + 5 * 8, 0);
            uint32_t a[4] = {};
            get<1, 4>(gs + near(D_Q + (sub * HQ + 2 * grp) * 64, lds32(sm + OFF_WIN + 4)) + lane * 4, 0, a);
            sts128(sm + OFF_QS + lane * 16, a[0], a[1], a[2], a[3]);
            __syncwarp();
            TSL(5);
            bar_arrive(4, 288);
        }
#pragma unroll
        for (int i = lane; i < 72; i += 32) cp16(sm + OFF_WR + i * 16, P.wr + i * 8);
        __syncwarp();
        if (cta < 72 && lane < 16) st1(g0 + ((epoch ^ lane >> 3) & 1) * G_SET + G_SIDE + cta * 8 + (lane & 7), lane < 8 ? 1 + lds32(sm + OFF_WIN + 8) : 0);
        asm volatile("cp.async.wait_all;" ::: "memory");
        __syncwarp();
        bar_arrive(2, NCW * 32);
        if (cta == 0 && lane == 0) st1(g0 + (~epoch & 1) * G_SET + G_CNT, 0);
        mbar_wait(bars + (BAR_SYNC + 1) * 8, 0);
#pragma unroll 1
        for (int c = 0; c < 4; c++) {
            uint32_t* const pg = g0 + (c >> 1) * G_SET + (c & 1) * 1024;
            zero4(pg + dual(D_O + cta * 128) + lane * 4);
            zero4(pg + dual(D_ACT + (grp * 36 + 4 * sub) * 32) + lane * 4);
            if (lane < 8 ? sub < 4 : lane < 16 && cta < 72)
                zero4(pg + dual(lane < 8 ? D_ACT + (grp * 36 + 32 + sub) * 32 : D_X1 + cta * 32) + (lane & 7) * 4);
        }
#pragma unroll 1
        for (int u = 0; u < 9; u++) zero4(g0 + dual(d_part(u < 8 ? 8 * sub + u : 64 + sub)) + (lane >> 4) * 1024 + grp * 64 + (lane & 15) * 4);
        {
            uint32_t* const nx = g0 + (~epoch & 1) * G_SET;
            uint32_t* const q = nx + dual(D_Q + g * (HQ * 64) + cta * 16) + t4 * 4;
            zero4(q), zero4(q + 1024);
            if (cta < 90) zero4(nx + (cta < 36 ? dual(D_H + 2 * cta * 32) + (lane >> 4) * (1024 - 64) : G_M + 4 * (cta - 36) * 32) + lane * 4);
        }
        if (cta >= 72) {
            bar_arrive(5, NCW * 32);
            return;
        }
        const uint32_t io = pin(4 * (g * (DM / 2) + 4 * cta + t4));
        uint32_t x = __ldg(at(reinterpret_cast<const uint32_t*>(P.x), io)), ga[1] = {};
        get<1, 1>(gs + G_M + cta * 32 + lane, 0, ga);
        const uint32_t src_p = pin(4 * (near(d_part(cta), lds32(sm + OFF_WIN + 8)) + lane * 2));
        const uint32_t dst_x = pin(4 * ((epoch & 1) * G_SET + dual(D_X1 + cta * 32) + lane));
        bar_sync(5, NCW * 32);
        x = badd2(x, bmul2(ga[0], reduce16<0>(at(g0, src_p), [] {})));
        put1d(at(g0, dst_x), x);
        TSL(10);
        bar_sync(6, NCW * 32);
        const uint4 r0 = lds128(sm + OFF_RT + g * 48), r1 = lds128(sm + OFF_RT + g * 48 + 16);
        float r = __uint_as_float(lds32(sm + OFF_RT + g * 48 + 32));
        r += ((__uint_as_float(r0.x) + __uint_as_float(r0.y)) + (__uint_as_float(r0.z) + __uint_as_float(r0.w))) +
             ((__uint_as_float(r1.x) + __uint_as_float(r1.y)) + (__uint_as_float(r1.z) + __uint_as_float(r1.w)));
        r = sigmoid_f(rbf(r));
        const uint32_t h = lds32(sm + OFF_HU + lane * 4), rs = pack2(r, r);
        uint32_t gb;
        const uint32_t y = reduce16<1>(at(g0, src_p), [&] {
            TSL(23);
            bar_sync(9, 64);
            gb = lds32(sm + OFF_QS + lane * 4);
        });
        *at(reinterpret_cast<uint32_t*>(P.out), io) = badd2(x, bmul2(gb, badd2(h, bmul2(y, rs))));
        if (cta == 0 && lane == 0) g0[G_EPOCH] = epoch + 1;
        TSL(15);
        return;
    }

    const uint32_t tile = sm + OFF_RING + warp * TILE_BYTES;
    const uint32_t fullb = bars + (BAR_FULL + warp) * 8;
    const uint32_t pw = sm + OFF_P + warp * (2 * P_PITCH);
    if (warp < 8) {
        {
            uint32_t q0[8], q1[8];
            bar_sync(4, 288);
#pragma unroll
            for (int i = 0; i < 8; i++) {
                const float2 v = lds64f(sm + OFF_QS + (g & 1) * 256 + i * 32 + t4 * 8);
                q0[i] = __float_as_uint(v.x), q1[i] = __float_as_uint(v.y);
            }
            uint32_t sp = pw + (t4 & 1) * P_PITCH + ((t4 >> 1) * 8 + g) * 2;
#pragma unroll 1
            for (int it = 0; it < 8; it++, sp += 64) {
                const uint32_t ab = tile + (it & 1) * (8 * TILE_BYTES) + (lane & 15) * 128 + (((lane >> 4) ^ (lane & 7)) << 4);
                mbar_wait(fullb + (it & 1) * 64, (it >> 1) & 1);
                float acc[2][2][4] = {};
#pragma unroll
                for (int ks = 0; ks < 8; ks++)
#pragma unroll
                    for (int m = 0; m < 2; m++) {
                        uint32_t a[4];
                        ldsm4(a, (ab ^ ((ks & 3) << 5)) + (ks >> 2) * 4096 + m * 2048);
                        mma(acc[m][ks & 1], a[0], a[1], a[2], a[3], (ks & 1) ? q1[ks - 1] : q0[ks], (ks & 1) ? q1[ks] : q0[ks + 1]);
                    }
                __syncwarp();
                if (lane == 0) mbar_arrive(fullb + (it & 1) * 64 + (BAR_EMPTY - BAR_FULL) * 8);
#pragma unroll
                for (int m = 0; m < 2; m++) {
                    const float s = sel4(acc[m][0], t4) + sel4(acc[m][1], t4);
                    sts16(sp + m * 32, (uint16_t)pack2(rbf(s) * 0.08838834764831845f, 0.f));
                }
            }
        }
        __syncwarp();
        if (warp == 7) TSL(6);
        const uint32_t pa = pw + (lane >> 4) * P_PITCH + (lane & 15) * 32;
        const uint32_t sa = sm + OFF_SM + (lane >> 4) * 64;
        const uint4 v0 = lds128(pa), v1 = lds128(pa + 16);
        const uint32_t sv[8] = {v0.x, v0.y, v0.z, v0.w, v1.x, v1.y, v1.z, v1.w};
        float e[16];
        float m = -INFINITY;
#pragma unroll
        for (int i = 0; i < 8; i++) {
            e[2 * i] = blo(sv[i]);
            e[2 * i + 1] = bhi(sv[i]);
            m = fmaxf(m, fmaxf(e[2 * i], e[2 * i + 1]));
        }
#pragma unroll
        for (int o = 8; o; o >>= 1) m = fmaxf(m, __shfl_xor_sync(0xffffffffu, m, o));
        float l = 0.f;
#pragma unroll
        for (int i = 0; i < 16; i++) {
            e[i] = ex2((e[i] - m) * LOG2E);
            l += e[i];
        }
#pragma unroll
        for (int o = 8; o; o >>= 1) l += __shfl_xor_sync(0xffffffffu, l, o);
        if ((lane & 15) == 0) sts64(sa + warp * 8, __float_as_uint(m), __float_as_uint(l));
        bar_sync(2, NCW * 32);
        const float2 v = lds64f(sa + (lane & 7) * 8);
        float M = v.x;
#pragma unroll
        for (int o = 4; o; o >>= 1) M = fmaxf(M, __shfl_xor_sync(0xffffffffu, M, o));
        float L = v.y * ex2((v.x - M) * LOG2E);
#pragma unroll
        for (int o = 4; o; o >>= 1) L += __shfl_xor_sync(0xffffffffu, L, o);
        const float sc = ex2((m - M) * LOG2E) * rcp(L);
        sts128(pa, pack2(e[0] * sc, e[1] * sc), pack2(e[2] * sc, e[3] * sc), pack2(e[4] * sc, e[5] * sc), pack2(e[6] * sc, e[7] * sc));
        sts128(pa + 16, pack2(e[8] * sc, e[9] * sc), pack2(e[10] * sc, e[11] * sc), pack2(e[12] * sc, e[13] * sc), pack2(e[14] * sc, e[15] * sc));
        __syncwarp();
    } else {
        bar_sync(2, NCW * 32);
    }

    uint32_t sh[8] = {}, op[8] = {};
    {
        const uint32_t* const src_m = gs + G_M + (72 + warp * 8) * 32 + lane;
        fetch<8, 1>(src_m + 72 * 32, 32, op);
        get<8, 1>(src_m, 32, sh);
        get<8, 1>(src_m + 72 * 32, 32, op);
    }
    const int side = lds32(sm + OFF_WIN + 8), set = (epoch & 1) * G_SET, rr = (lane >> 4) * 8 + (lane & 7);
    const uint32_t dst_o = pin(4 * (set + dual(D_O + cta * 128) + (tid & 0x70) + (tid & 3) * 4 + ((tid >> 2) & 3)));
    const uint32_t src_o = pin(4 * (set + near(D_O + grp * 1024, side) + g * 128 + warp * 16 + t4 * 4));
    const int unit = warp < 8 ? 8 * sub + warp : 64 + sub;
    uint32_t rside[1] = {};
    get<1, 1>(gs + G_SIDE + unit * 8, 0, rside);
    const uint32_t dst_p = pin(4 * (near(d_part(unit), rside[0] - 1) + grp * 64 + lane * 2));
    const uint32_t src_x = pin(4 * (set + near(D_X1 + warp * 256, side) + lane));
    const uint32_t dst_a = pin(4 * (set + dual(D_ACT + (grp * 36 + (warp < 4 ? 4 * sub + warp : 32 + sub)) * 32) + lane));
    const uint32_t src_a = pin(4 * (set + near(D_ACT + (grp * 36 + 4 * warp) * 32, side) + lane));
    const uint32_t rowoff = pin((warp * 32 + rr) * 128 + ((((lane >> 3) & 1) ^ (lane & 7)) << 4));
    const uint32_t reds = pin((tid * 8) | (warp * 2304 + lane * 8) << 16);
    const uint32_t ored = pin((warp * 1088 + (t4 & 1) * 576 + ((t4 >> 1) * 8 + g) * 4) | ((tid >> 6) * 64 + tid * 8) << 16);

    if (warp < 8) {
        float acc[8][4] = {};
        uint32_t pp = pw + (lane & 1) * P_PITCH + (lane >> 3) * 16;
#pragma unroll 1
        for (int it = 0; it < 8; it++, pp += 64) {
            const uint32_t ab = tile + (it & 1) * (8 * TILE_BYTES) + ((lane & 7) + (lane >> 4) * 8) * 128 + ((((lane >> 3) & 1) ^ (lane & 7)) << 4);
            uint32_t pb[4];
            ldsm4(pb, pp);
            mbar_wait(fullb + (it & 1) * 64, (it >> 1) & 1);
#pragma unroll
            for (int ks = 0; ks < 2; ks++)
#pragma unroll
                for (int m = 0; m < 8; m++) {
                    uint32_t a[4];
                    ldsm4t(a, (ab ^ ((m & 3) << 5)) + (m >> 2) * 4096 + ks * 2048);
                    mma(acc[m], a[0], a[1], a[2], a[3], pb[2 * ks], pb[2 * ks + 1]);
                }
            __syncwarp();
            if (lane == 0) mbar_arrive(fullb + (it & 1) * 64 + (BAR_EMPTY - BAR_FULL) * 8);
        }
        if (warp == 7) TSL(7);
        const uint32_t ra = sm + OFF_ORED + (ored & 0xffff);
#pragma unroll
        for (int m = 0; m < 8; m++) sts32(ra + m * 64, __float_as_uint(sel4(acc[m], t4)));
    }
    bar_sync(5, NCW * 32);
    if (warp < 4) {
        float s[2][2] = {};
#pragma unroll
        for (int w = 0; w < 8; w++) {
            const float2 v = lds64f(sm + OFF_ORED + w * 1088 + (ored >> 16));
            s[w & 1][0] += v.x;
            s[w & 1][1] += v.y;
        }
        put1d(at(g0, dst_o), pack2(s[0][0] + s[1][0], s[0][1] + s[1][1]));
        if (warp == 0) TSL(8);
    }

    project<0>(sm, at(g0, src_o), at(g0, dst_p), rowoff, reds, 288, warp, lane);
    if (warp == 0) TSL(9);

    const uint32_t gbar = bars + (BAR_GU + warp) * 8;
    const int pl = ((lane >> 3) & 1) ^ P.zg;
    const uint32_t ab = sm + OFF_GU + warp * 8192 + pl * 4096 + rr * 64 + ((lane & 6) << 3);
    const uint32_t ax = sm + OFF_GX + warp * 2048 + pl * 1024 + rr * 16;
    uint32_t a[20][4] = {}, h[8] = {};
    auto load_gu = [&]() {
#pragma unroll
        for (int i = 0; i < 20; i++) ldsm4t(a[i], i % 5 < 4 ? (ab ^ ((i % 5) << 4)) + (i / 5) * 1024 : ax + (i / 5) * 256);
    };
    bool gpre = false;
    {
        int it = 0;
        do {
            if (!gpre && __all_sync(0xffffffffu, mbar_test(gbar, 0))) gpre = true, load_gu();
            if (__any_sync(0xffffffffu, h[0] == 0)) {
                h[0] = ld1(at(g0, src_x));
                continue;
            }
            fetch<8, 1>(at(g0, src_x), 32, h);
        } while (missing(h) & (++it < SPIN_LIMIT));
    }
    if (warp == 0) TSL(11);
    ln_partial(h, sm + OFF_ST + g * 80 + warp * 8, t4 == 0);
    bar_sync(3, 288);
    {
        uint32_t mean2;
        float inv;
        ln_combine(sm + OFF_ST + g * 80, mean2, inv);
#pragma unroll
        for (int i = 0; i < 8; i++) h[i] = modulate2(h[i], mean2, inv, sh[i], op[i]);
    }
    if (warp == 0) TSL(12);
    if (!gpre) {
        mbar_wait(gbar, 0);
        load_gu();
    }
    if (warp == 8) TSL(17);
    {
        float acc[5][4] = {};
#pragma unroll
        for (int i = 0; i < 20; i++) mma(acc[i % 5], a[i][0], a[i][1], a[i][2], a[i][3], h[2 * (i / 5)], h[2 * (i / 5) + 1]);
#pragma unroll
        for (int m = 0; m < 5; m++) sts128f(sm + OFF_RED + m * 4608 + 2 * (reds & 0xffff), acc[m]);
    }
    bar_sync(3, 288);
    if (warp < 5) {
        float c[4] = {};
        sum_frags<9>(c, sm + OFF_RED + 2 * (reds >> 16), 512);
        const uint32_t w = movm(bmul2(silu2(pack2(c[0], c[1])), pack2(c[2], c[3])));
        if (warp < 4 || sub < 4) put1d(at(g0, dst_a), w);
        if (warp == 1) TSL(13);
    }
    if (cta < 72) {
        float r = 0.f;
#pragma unroll
        for (int i = 0; i < 8; i++) {
            const uint32_t wr = lds32(sm + OFF_WR + (warp * 32 + i * 4 + t4) * 4);
            r = fmaf(blo(h[i]), blo(wr), fmaf(bhi(h[i]), bhi(wr), r));
            if (warp * 8 + i == cta) sts32(sm + OFF_HU + lane * 4, h[i]);
        }
        r = quad_sum(r);
        if (t4 == 0) sts32(sm + OFF_RT + g * 48 + warp * 4, __float_as_uint(r));
    }

    project<1>(sm, at(g0, src_a), at(g0, dst_p), rowoff, reds, cta < 72 ? 320 : 288, warp, lane);
    if (warp == 0) TSL(14);
    if (warp == 8) TSL(27);

    if (cta < 72) {
        const uint32_t ga = sm + OFF_GB + warp * 1024 + ((lane >> 3) & 1) * 256 + (lane >> 4) * 128 + (lane & 7) * 16;
        float acc[2][4] = {};
        mbar_wait(bars + BAR_GB * 8, 0);
        if (warp == 0) TSL(22);
#pragma unroll
        for (int i = 0; i < 2; i++) {
            uint32_t w[4];
            ldsm4t(w, ga + i * 512);
            mma(acc[0], w[0], w[1], w[2], w[3], sc[4 * i], sc[4 * i + 1]);
            mma(acc[1], w[0], w[1], w[2], w[3], sc[4 * i + 2], sc[4 * i + 3]);
        }
        sts64(sm + OFF_RED + (reds & 0xffff), __float_as_uint(acc[0][0] + acc[1][2]), __float_as_uint(acc[0][1] + acc[1][3]));
        if (warp) {
            bar_arrive(7, 288);
        } else {
            bar_sync(7, 288);
            float s[2][2] = {};
#pragma unroll
            for (int w = 0; w < 9; w++) {
                const float2 v = lds64f(sm + OFF_RED + (reds & 0xffff) + w * 256);
                s[w & 1][0] += v.x;
                s[w & 1][1] += v.y;
            }
            sts32(sm + OFF_QS + lane * 4, movm(pack2(s[0][0] + s[1][0], s[0][1] + s[1][1])));
            __syncwarp();
            bar_arrive(9, 64);
            TSL(25);
        }
    }
}

typedef CUresult (*EncodeFn)(CUtensorMap*, CUtensorMapDataType, cuuint32_t, void*, const cuuint64_t*, const cuuint64_t*,
                             const cuuint32_t*, const cuuint32_t*, CUtensorMapInterleave, CUtensorMapSwizzle,
                             CUtensorMapL2promotion, CUtensorMapFloatOOBfill);

void make_map(EncodeFn enc, CUtensorMap* m, void* p, int cols, int rows, int pitch, int bc, int br, int bp, int planes, size_t pstride,
              CUtensorMapSwizzle sw, int promo) {
    cuuint64_t dims[3] = {(cuuint64_t)cols, (cuuint64_t)rows, (cuuint64_t)planes};
    cuuint64_t strides[2] = {(cuuint64_t)pitch * 2, (cuuint64_t)pstride};
    cuuint32_t box[3] = {(cuuint32_t)bc, (cuuint32_t)br, (cuuint32_t)bp};
    cuuint32_t es[3] = {1, 1, 1};
    enc(m, CU_TENSOR_MAP_DATA_TYPE_BFLOAT16, 3, p, dims, strides, box, es, CU_TENSOR_MAP_INTERLEAVE_NONE, sw,
        (CUtensorMapL2promotion)promo, CU_TENSOR_MAP_FLOAT_OOB_FILL_NONE);
}

}

extern "C" void kernel_launch(void* const* d_in, const int* in_sizes, int n_in, void* d_out, int out_size) {
    static EncodeFn enc = nullptr;
    static uint32_t* scratch = nullptr;
    if (!enc) {
        void* fn = nullptr;
        cudaDriverEntryPointQueryResult st;
        cudaGetDriverEntryPoint("cuTensorMapEncodeTiled", &fn, cudaEnableDefault, &st);
        enc = (EncodeFn)fn;
        cudaGetSymbolAddress(&fn, g_scratch);
        scratch = (uint32_t*)(((uintptr_t)fn + 8 * G_SET - 1) & ~(uintptr_t)(8 * G_SET - 1));
        cudaFuncSetAttribute(fused_kernel, cudaFuncAttributeMaxDynamicSharedMemorySize, SMEM_BYTES);
    }
    Params P;
    Maps T;
    const CUtensorMapSwizzle none = CU_TENSOR_MAP_SWIZZLE_NONE;
    const int PROMO_W = CU_TENSOR_MAP_L2_PROMOTION_L2_128B, PROMO_KV = CU_TENSOR_MAP_L2_PROMOTION_L2_256B;
    make_map(enc, &T.m[M_K], d_in[1], 64, NB * HKV * SK, DH, 64, 32, 2, 2, 128, CU_TENSOR_MAP_SWIZZLE_128B, PROMO_KV);
    make_map(enc, &T.m[M_V], d_in[2], 64, NB * HKV * SK, DH, 64, 32, 2, 2, 128, CU_TENSOR_MAP_SWIZZLE_128B, PROMO_KV);
    make_map(enc, &T.m[M_WQ], d_in[3], HQ * DH, DM, HQ * DH, 32, 192, 1, 1, 16, CU_TENSOR_MAP_SWIZZLE_64B, PROMO_W);
    make_map(enc, &T.m[M_WM], d_in[11], 6 * DM, DM, 6 * DM, 32, 192, 1, 1, 16, CU_TENSOR_MAP_SWIZZLE_64B, PROMO_W);
    make_map(enc, &T.m[M_WA], d_in[11], DM, DM, 6 * DM, 16, 192, 2, 2, DM * 2, CU_TENSOR_MAP_SWIZZLE_32B, PROMO_W);
    make_map(enc, &T.m[M_GB], d_in[11], 6 * DM, DM, 6 * DM, 8, 192, 1, 1, 16, none, PROMO_W);
    char *wg = (char*)d_in[7], *wu = (char*)d_in[8], *wo = (char*)d_in[4], *wd = (char*)d_in[9];
    P.zg = wg > wu;
    P.zo = wo > wd;
    const size_t sg = P.zg ? wg - wu : wu - wg, so = P.zo ? wo - wd : wd - wo;
    make_map(enc, &T.m[M_GU], P.zg ? wu : wg, FF, DM, FF, 32, 64, 2, 2, sg, CU_TENSOR_MAP_SWIZZLE_64B, PROMO_W);
    make_map(enc, &T.m[M_GX], P.zg ? wu : wg, FF, DM, FF, 8, 64, 2, 2, sg, none, PROMO_W);
    make_map(enc, &T.m[M_OD], P.zo ? wd : wo, DM, FF, DM, 64, 64, 1, 2, so, CU_TENSOR_MAP_SWIZZLE_128B, PROMO_W);
    make_map(enc, &T.m[M_OX], P.zo ? wd : wo, DM, FF, DM, 8, 64, 1, 2, so, none, PROMO_W);
    P.x = (const __nv_bfloat16*)d_in[0];
    P.wr = (const __nv_bfloat16*)d_in[6];
    P.c = (const __nv_bfloat16*)d_in[10];
    P.k = (const __nv_bfloat16*)d_in[1];
    P.out = (__nv_bfloat16*)d_out;
    P.scratch = scratch;
    void* args[2] = {&P, &T};
    cudaLaunchCooperativeKernel((const void*)fused_kernel, dim3(NCTA), dim3(NTHREADS), args, SMEM_BYTES, cudaStreamPerThread);
}
```

```cpp
#include <cuda_runtime.h>
#include <cuda_bf16.h>
#include <cuda.h>
#include <stdint.h>

typedef unsigned long long u64;

#define GU_UNROLL 1
#define TAU 568
#define TAU_W 650
#define L_KV 3200
#define L_WO 2850
#define L_GU 2850
#define L_WD 2950
#define L_LAST 500
#define L_GB 2700
#define W_0 6
#define W_LO 2
#define W_HI 8
#define T_PACE 20
#define SMOOTH 1
#define NK0 3
#define NK1 2
#define PFK 2
#define T_CLEAR 116
#define NPING0 4
#define NPING1 16

namespace {

constexpr int NB = 8, DM = 576, HQ = 32, HKV = 16, SK = 8192, WIN = 2048, DH = 128, FF = 4608;
constexpr int NCTA = 128;
constexpr int NCW = 10;
constexpr int NTHREADS = (NCW + 2) * 32;
constexpr int TILE_BYTES = 8192, NT = 64;
constexpr int SPIN_LIMIT = 1 << 22;

constexpr int OFF_RING = 0;
constexpr int OFF_WM = 121856;
constexpr int OFF_WQ = OFF_WM + 36864;
constexpr int OFF_GU = 0;
constexpr int OFF_WD = 73728;
constexpr int OFF_GB = 114688;
constexpr int OFF_OX = 131072;
constexpr int OFF_DX = OFF_OX + 4096;
constexpr int OFF_GX = OFF_DX + 4608;
constexpr int OFF_WO = OFF_WQ;
constexpr int OFF_P = OFF_WQ + 36864;
constexpr int P_PITCH = 528;
constexpr int OFF_RED = OFF_P + 16 * P_PITCH;
constexpr int OFF_ORED = OFF_RED + 5 * 4608 - 8704;
constexpr int OFF_ST = OFF_RED + 5 * 4608;
constexpr int OFF_SM = OFF_ST + 640;
constexpr int OFF_RT = OFF_SM + 128;
constexpr int OFF_QS = OFF_RT + 384;
constexpr int OFF_WR = OFF_QS + 512;
constexpr int OFF_WIN = OFF_WR + 1152;
constexpr int OFF_BAR = OFF_WIN + 16;
constexpr int BAR_FULL = 6, BAR_WO = 22, BAR_GU = 26, BAR_WD = 35, BAR_EMPTY = 40, BAR_SYNC = 56, BAR_WMF = 59, BAR_GB = 60, NBAR = 70;
constexpr int SMEM_BYTES = OFF_BAR + NBAR * 8;

constexpr int D_X1 = 0;
constexpr int D_O = 3072;
constexpr int D_ACT = D_O + 512 * 32;
constexpr int D_H = D_ACT + 576 * 32;
constexpr int D_Q = D_H + 3072;
constexpr int G_M = 2 * (D_Q + NB * HQ * 64);
constexpr int G_SIDE = G_M + 216 * 32;
constexpr int G_CNT = G_SIDE + 72 * 8;
constexpr int G_SET = 1 << 18;
__device__ __forceinline__ int d_part(int unit) { return (64 + unit + (unit & 64)) * 1024; }
constexpr int D_PING = 200 * 1024;
constexpr int G_EPOCH = 201 * 2048;
static_assert(G_CNT < 64 * 2048, "scratch layout");
__device__ uint32_t g_scratch[4 * G_SET];
__device__ __forceinline__ int dual(int w) { return w + (w & ~1023); }
__device__ __forceinline__ int near(int w, int side) { return dual(w) + (((__popc(w & 0x16400) ^ side) & 1) << 10); }

#define TI(i)
#define TS(i)
#define TSL(i)

enum { M_K, M_V, M_GU, M_GX, M_OD, M_OX, M_WQ, M_WM, M_WA, M_GB, NMAP };
struct Params {
    const __nv_bfloat16 *c, *x, *k;
    __nv_bfloat16* out;
    uint32_t* scratch;
    const __nv_bfloat16* wr;
    int zg, zo;
};
struct Maps {
    CUtensorMap m[NMAP];
};

__device__ __forceinline__ void mbar_init(uint32_t bar, int cnt) {
    asm volatile("mbarrier.init.shared::cta.b64 [%0], %1;" ::"r"(bar), "r"(cnt));
}
__device__ __forceinline__ void mbar_expect(uint32_t bar, uint32_t bytes) {
    asm volatile("mbarrier.arrive.expect_tx.shared::cta.b64 _, [%0], %1;" ::"r"(bar), "r"(bytes) : "memory");
}
__device__ __forceinline__ void mbar_arrive(uint32_t bar) {
    asm volatile("mbarrier.arrive.shared::cta.b64 _, [%0];" ::"r"(bar) : "memory");
}
__device__ __forceinline__ void mbar_wait(uint32_t bar, uint32_t parity) {
    asm volatile("{\n.reg .pred p;\n.reg .u32 c;\n"
                 "mbarrier.try_wait.parity.shared::cta.b64 p, [%0], %1;\n@p bra DONE;\nmov.u32 c, %2;\n"
                 "AGAIN:\nmbarrier.try_wait.parity.shared::cta.b64 p, [%0], %1;\nsub.u32 c, c, 1;\n"
                 "setp.eq.or.u32 p, c, 0, p;\n@!p bra AGAIN;\nDONE:\n}"
                 ::"r"(bar), "r"(parity), "n"(SPIN_LIMIT) : "memory");
}
__device__ __forceinline__ bool mbar_test(uint32_t bar, uint32_t parity) {
    uint32_t ok;
    asm volatile("{\n.reg .pred p;\nmbarrier.test_wait.parity.shared::cta.b64 p, [%1], %2;\nselp.u32 %0, 1, 0, p;\n}"
                 : "=r"(ok) : "r"(bar), "r"(parity) : "memory");
    return ok;
}
__device__ __forceinline__ void tma3d_hint(uint32_t dst, const CUtensorMap* m, int x, int y, int z, uint32_t bar, u64 pol) {
    asm volatile("cp.async.bulk.tensor.3d.shared::cluster.global.mbarrier::complete_tx::bytes.L2::cache_hint"
                 " [%0], [%1, {%2, %3, %4}], [%5], %6;"
                 ::"r"(dst), "l"(m), "r"(x), "r"(y), "r"(z), "r"(bar), "l"(pol) : "memory");
}
__device__ __forceinline__ void tma3d(uint32_t dst, const CUtensorMap* m, int x, int y, int z, uint32_t bar) {
    asm volatile("cp.async.bulk.tensor.3d.shared::cluster.global.mbarrier::complete_tx::bytes [%0], [%1, {%2, %3, %4}], [%5];"
                 ::"r"(dst), "l"(m), "r"(x), "r"(y), "r"(z), "r"(bar) : "memory");
}
__device__ __forceinline__ void bar_sync(int id, int n) { asm volatile("bar.sync %0, %1;" ::"r"(id), "r"(n) : "memory"); }
__device__ __forceinline__ void bar_arrive(int id, int n) { asm volatile("bar.arrive %0, %1;" ::"r"(id), "r"(n) : "memory"); }
__device__ __forceinline__ void ldsm4(uint32_t (&r)[4], uint32_t a) {
    asm volatile("ldmatrix.sync.aligned.m8n8.x4.shared.b16 {%0,%1,%2,%3}, [%4];"
                 : "=r"(r[0]), "=r"(r[1]), "=r"(r[2]), "=r"(r[3]) : "r"(a) : "memory");
}
__device__ __forceinline__ void ldsm4t(uint32_t (&r)[4], uint32_t a) {
    asm volatile("ldmatrix.sync.aligned.m8n8.x4.trans.shared.b16 {%0,%1,%2,%3}, [%4];"
                 : "=r"(r[0]), "=r"(r[1]), "=r"(r[2]), "=r"(r[3]) : "r"(a) : "memory");
}
__device__ __forceinline__ void mma(float (&c)[4], uint32_t a0, uint32_t a1, uint32_t a2, uint32_t a3, uint32_t b0, uint32_t b1) {
    asm volatile("mma.sync.aligned.m16n8k16.row.col.f32.bf16.bf16.f32 {%0,%1,%2,%3}, {%4,%5,%6,%7}, {%8,%9}, {%0,%1,%2,%3};"
                 : "+f"(c[0]), "+f"(c[1]), "+f"(c[2]), "+f"(c[3])
                 : "r"(a0), "r"(a1), "r"(a2), "r"(a3), "r"(b0), "r"(b1));
}
__device__ __forceinline__ uint32_t movm(uint32_t a) {
    uint32_t d;
    asm volatile("movmatrix.sync.aligned.m8n8.trans.b16 %0, %1;" : "=r"(d) : "r"(a));
    return d;
}
__device__ __forceinline__ uint32_t lds32(uint32_t a) { uint32_t v; asm volatile("ld.volatile.shared.b32 %0, [%1];" : "=r"(v) : "r"(a) : "memory"); return v; }
__device__ __forceinline__ float2 lds64f(uint32_t a) { float2 v; asm volatile("ld.shared.v2.f32 {%0,%1}, [%2];" : "=f"(v.x), "=f"(v.y) : "r"(a) : "memory"); return v; }
__device__ __forceinline__ uint4 lds128(uint32_t a) { uint4 v; asm volatile("ld.shared.v4.b32 {%0,%1,%2,%3}, [%4];" : "=r"(v.x), "=r"(v.y), "=r"(v.z), "=r"(v.w) : "r"(a) : "memory"); return v; }
__device__ __forceinline__ void sts32(uint32_t a, uint32_t v) { asm volatile("st.shared.b32 [%0], %1;" ::"r"(a), "r"(v) : "memory"); }
__device__ __forceinline__ void sts16(uint32_t a, uint16_t v) { asm volatile("st.shared.b16 [%0], %1;" ::"r"(a), "h"(v) : "memory"); }
__device__ __forceinline__ void sts64(uint32_t a, uint32_t x, uint32_t y) { asm volatile("st.shared.v2.b32 [%0], {%1,%2};" ::"r"(a), "r"(x), "r"(y) : "memory"); }
__device__ __forceinline__ void sts128(uint32_t a, uint32_t x, uint32_t y, uint32_t z, uint32_t w) {
    asm volatile("st.shared.v4.b32 [%0], {%1,%2,%3,%4};" ::"r"(a), "r"(x), "r"(y), "r"(z), "r"(w) : "memory");
}
__device__ __forceinline__ void sts128f(uint32_t a, const float (&c)[4]) {
    sts128(a, __float_as_uint(c[0]), __float_as_uint(c[1]), __float_as_uint(c[2]), __float_as_uint(c[3]));
}

__device__ __forceinline__ float sel4(const float (&c)[4], int t) { return (t & 2) ? ((t & 1) ? c[3] : c[2]) : ((t & 1) ? c[1] : c[0]); }

template <int LUT>
__device__ __forceinline__ uint32_t lop3(uint32_t a, uint32_t b, uint32_t c) {
    uint32_t d;
    asm("lop3.b32 %0, %1, %2, %3, %4;" : "=r"(d) : "r"(a), "r"(b), "r"(c), "n"(LUT));
    return d;
}
__device__ __forceinline__ uint32_t pin(uint32_t v) { return __shfl_xor_sync(0xffffffffu, v, 0); }
template <typename T>
__device__ __forceinline__ T* at(T* base, uint32_t bytes) { return (T*)((const char*)base + bytes); }

__device__ __forceinline__ uint32_t clock32(uint32_t dep) {
    uint32_t t;
    asm volatile("{\n.reg .pred p;\nsetp.eq.u32 p, %1, 0x9e3779b9;\n@p nanosleep.u32 1;\nmov.u32 %0, %clock;\n}" : "=r"(t) : "r"(dep) : "memory");
    return t;
}

__device__ __forceinline__ uint32_t nz(uint32_t v) { return v ? v : 0x80000000u; }
__device__ __forceinline__ void st1(uint32_t* p, uint32_t a) { asm volatile("st.relaxed.gpu.global.b32 [%0], %1;" ::"l"(p), "r"(a) : "memory"); }
__device__ __forceinline__ void st2(uint32_t* p, uint32_t a, uint32_t b) {
    asm volatile("st.relaxed.gpu.global.v2.b32 [%0], {%1,%2};" ::"l"(p), "r"(a), "r"(b) : "memory");
}
__device__ __forceinline__ void zero4(uint32_t* p) { asm volatile("st.relaxed.gpu.global.v4.b32 [%0], {%1,%1,%1,%1};" ::"l"(p), "r"(0) : "memory"); }
__device__ __forceinline__ void put1d(uint32_t* p, uint32_t a) { a = nz(a), st1(p, a), st1(p + 1024, a); }
__device__ __forceinline__ void put2d(uint32_t* p, uint32_t a, uint32_t b) { a = nz(a), b = nz(b), st2(p, a, b), st2(p + 1024, a, b); }
__device__ __forceinline__ uint32_t ld1(const uint32_t* p) {
    uint32_t v;
    asm volatile("ld.relaxed.gpu.global.b32 %0, [%1];" : "=r"(v) : "l"(p) : "memory");
    return v;
}
template <int N, int V>
__device__ __forceinline__ void fetch(const uint32_t* p, int stride, uint32_t (&a)[N * V]) {
#pragma unroll
    for (int i = 0; i < N; i++) {
        if (V == 1)
            asm volatile("{\n.reg .pred p;\nsetp.eq.u32 p, %0, 0;\n@p ld.relaxed.gpu.global.b32 %0, [%1];\n}"
                         : "+r"(a[i]) : "l"(p + i * stride) : "memory");
        if (V == 4)
            asm volatile("{\n.reg .pred p;\nsetp.eq.u32 p, %4, 0;\n@p ld.relaxed.gpu.global.v4.b32 {%0,%1,%2,%3}, [%5];\n}"
                         : "+r"(a[V * i]), "+r"(a[V * i + V / 4]), "+r"(a[V * i + V / 2]), "+r"(a[V * i + V - 1])
                         : "r"(min(min(a[V * i], a[V * i + V / 4]), min(a[V * i + V / 2], a[V * i + V - 1]))), "l"(p + i * stride) : "memory");
    }
}
template <int N>
__device__ __forceinline__ bool missing(const uint32_t (&a)[N]) {
    uint32_t lo = a[0];
#pragma unroll
    for (int i = 1; i < N; i++) lo = min(lo, a[i]);
    return __any_sync(0xffffffffu, lo == 0);
}
template <int N, int V>
__device__ __forceinline__ void get(const uint32_t* p, int stride, uint32_t (&a)[N * V]) {
    int it = 0;
    do fetch<N, V>(p, stride, a);
    while (missing(a) & (++it < SPIN_LIMIT));
}
__device__ __forceinline__ void cp16(uint32_t dst, const void* src) {
    asm volatile("cp.async.cg.shared.global [%0], [%1], 16;" ::"r"(dst), "l"(src) : "memory");
}

__device__ __forceinline__ uint32_t pack2(float lo, float hi) {
    uint32_t r;
    asm("cvt.rn.bf16x2.f32 %0, %1, %2;" : "=r"(r) : "f"(hi), "f"(lo));
    return r;
}
__device__ __forceinline__ float rbf(float x) { return __uint_as_float(pack2(0.f, x)); }
__device__ __forceinline__ float blo(uint32_t v) { return __uint_as_float(v << 16); }
__device__ __forceinline__ float bhi(uint32_t v) { return __uint_as_float(v & 0xffff0000u); }
__device__ __forceinline__ uint32_t badd2(uint32_t a, uint32_t b) { uint32_t r; asm("add.rn.bf16x2 %0, %1, %2;" : "=r"(r) : "r"(a), "r"(b)); return r; }
__device__ __forceinline__ uint32_t bsub2(uint32_t a, uint32_t b) { uint32_t r; asm("sub.rn.bf16x2 %0, %1, %2;" : "=r"(r) : "r"(a), "r"(b)); return r; }
__device__ __forceinline__ uint32_t bmul2(uint32_t a, uint32_t b) { uint32_t r; asm("mul.rn.bf16x2 %0, %1, %2;" : "=r"(r) : "r"(a), "r"(b)); return r; }
__device__ __forceinline__ float ex2(float x) { float r; asm("ex2.approx.ftz.f32 %0, %1;" : "=f"(r) : "f"(x)); return r; }
__device__ __forceinline__ float rcp(float x) { float r; asm("rcp.approx.ftz.f32 %0, %1;" : "=f"(r) : "f"(x)); return r; }
__device__ __forceinline__ float sqrt_f(float x) { float r; asm("sqrt.approx.ftz.f32 %0, %1;" : "=f"(r) : "f"(x)); return r; }
constexpr float LOG2E = 1.4426950408889634f;
constexpr uint32_t ONE2 = 0x3f803f80u;
__device__ __forceinline__ float sigmoid_f(float x) { return rcp(1.0f + ex2(-LOG2E * x)); }
__device__ __forceinline__ uint32_t silu2(uint32_t v) {
    const float a = blo(v), b = bhi(v);
    return pack2(a * sigmoid_f(a), b * sigmoid_f(b));
}
__device__ __forceinline__ float quad_sum(float v) {
    v += __shfl_xor_sync(0xffffffffu, v, 1);
    return v + __shfl_xor_sync(0xffffffffu, v, 2);
}
__device__ __forceinline__ void ln_partial(const uint32_t (&v)[8], uint32_t dst, bool writer) {
    float s0 = 0.f, s1 = 0.f;
#pragma unroll
    for (int i = 0; i < 8; i++) {
        s0 += blo(v[i]);
        s1 += bhi(v[i]);
    }
    const float mean = quad_sum(s0 + s1) * (1.0f / 64);
    s0 = s1 = 0.f;
#pragma unroll
    for (int i = 0; i < 8; i++) {
        const float a = blo(v[i]) - mean, b = bhi(v[i]) - mean;
        s0 = fmaf(a, a, s0);
        s1 = fmaf(b, b, s1);
    }
    s0 = quad_sum(s0 + s1);
    if (writer) sts64(dst, __float_as_uint(mean), __float_as_uint(s0));
}
__device__ __forceinline__ void ln_combine(uint32_t src, uint32_t& mean2, float& inv) {
    float m[10], q0 = 0.f, q1 = 0.f, s = 0.f;
#pragma unroll
    for (int i = 0; i < 5; i++) {
        const uint4 v = lds128(src + i * 16);
        m[2 * i] = __uint_as_float(v.x);
        m[2 * i + 1] = __uint_as_float(v.z);
        q0 += __uint_as_float(v.y);
        if (i < 4) q1 += __uint_as_float(v.w);
    }
    const float mean = (((m[0] + m[1]) + (m[2] + m[3])) + ((m[4] + m[5]) + (m[6] + m[7])) + m[8]) * (1.0f / 9);
#pragma unroll
    for (int i = 0; i < 9; i++) s = fmaf(m[i] - mean, m[i] - mean, s);
    const float var = fmaf(s, 64.f, q0 + q1) * (1.0f / DM);
    mean2 = pack2(mean, mean);
    inv = rcp(rbf(sqrt_f(rbf(rbf(var) + 1e-5f))));
}
__device__ __forceinline__ uint32_t modulate2(uint32_t x, uint32_t mean2, float inv, uint32_t shift, uint32_t onep) {
    const uint32_t d = bsub2(x, mean2);
    return badd2(bmul2(pack2(blo(d) * inv, bhi(d) * inv), onep), shift);
}
template <int N>
__device__ __forceinline__ void sum_frags(float (&c)[4], uint32_t addr, int stride) {
#pragma unroll
    for (int w = 0; w < N; w++) {
        const uint4 v = lds128(addr + w * stride);
        c[0] += __uint_as_float(v.x); c[1] += __uint_as_float(v.y);
        c[2] += __uint_as_float(v.z); c[3] += __uint_as_float(v.w);
    }
}

template <int ST>
__device__ __forceinline__ void project(uint32_t sm, const uint32_t* src, uint32_t* dst, uint32_t rowoff, uint32_t reds, int nsync, int warp, int lane) {
    constexpr int NW = ST ? 9 : 8;
    const uint32_t red = sm + (ST ? OFF_WO : OFF_P);
    if (warp < NW) {
        const uint32_t wbar = sm + OFF_BAR + (ST ? BAR_WD + (warp < 8 ? ((warp >> 1) + 1) & 3 : 4) : BAR_WO + (warp >> 1)) * 8;
        const uint32_t ab = sm + (ST ? OFF_WD : OFF_WO) + rowoff;
        const uint32_t ax = sm + (ST ? OFF_DX : OFF_OX) + ((rowoff >> 7) << 4);
        uint32_t a[10][4] = {}, b[4] = {};
        bool have_w = false, need_b = true;
        int it = 0;
        do {
            if (!need_b) mbar_wait(wbar, 0);
            if (!need_b || (!have_w && __all_sync(0xffffffffu, mbar_test(wbar, 0)))) {
                have_w = true;
#pragma unroll
                for (int i = 0; i < 10; i++) ldsm4t(a[i], i % 5 < 4 ? (ab ^ ((i % 5) << 5)) + (i / 5) * 2048 : ax + (i / 5) * 256);
                if (!need_b) break;
            }
            if (ST) fetch<4, 1>(src, 32, b);
            else fetch<1, 4>(src, 0, b);
            need_b = missing(b) & (++it < SPIN_LIMIT);
        } while (need_b | !have_w);
        if (warp == 0) TSL(ST ? 24 : 21);
        float acc[5][4] = {};
#pragma unroll
        for (int i = 0; i < 10; i++) mma(acc[i % 5], a[i][0], a[i][1], a[i][2], a[i][3], b[2 * (i / 5)], b[2 * (i / 5) + 1]);
#pragma unroll
        for (int u = 0; u < 9; u++)
            sts64(red + u * 2304 + (reds & 0xffff), __float_as_uint(acc[u >> 1][2 * (u & 1)]), __float_as_uint(acc[u >> 1][2 * (u & 1) + 1]));
    }
    bar_sync(ST ? 6 : 3, nsync);
    float s[2][2] = {};
#pragma unroll
    for (int w = 0; w < NW; w++) {
        const float2 v = lds64f(red + (reds >> 16) + w * 256);
        s[w & 1][0] += v.x;
        s[w & 1][1] += v.y;
    }
    const uint32_t p0 = (__float_as_uint(s[0][0] + s[1][0]) | 1) ^ ST, p1 = (__float_as_uint(s[0][1] + s[1][1]) | 1) ^ ST;
    st2(dst, p0, p1);
}

template <int ST, typename F>
__device__ __forceinline__ uint32_t reduce16(const uint32_t* src, F arrived) {
    uint32_t a[32] = {}, bad[16], any;
    int it = 0;
#pragma unroll
    for (int i = 0; i < 16; i++) bad[i] = 1;
    do {
#pragma unroll
        for (int i = 0; i < 16; i++)
            asm volatile("{\n.reg .pred p;\nsetp.ne.u32 p, %2, 0;\n@p ld.relaxed.gpu.global.v2.b32 {%0,%1}, [%3];\n}"
                         : "+r"(a[2 * i]), "+r"(a[2 * i + 1]) : "r"(bad[i]), "l"(src + i * 64) : "memory");
#pragma unroll
        for (int i = 0; i < 16; i++) bad[i] = lop3<ST ? 0xa8 : 0x2a>(a[2 * i], a[2 * i + 1], 1);
        any = lop3<0xfe>(lop3<0xfe>(lop3<0xfe>(bad[0], bad[1], bad[2]), lop3<0xfe>(bad[3], bad[4], bad[5]), lop3<0xfe>(bad[6], bad[7], bad[8])),
                         lop3<0xfe>(lop3<0xfe>(bad[9], bad[10], bad[11]), lop3<0xfe>(bad[12], bad[13], bad[14]), bad[15]), 0);
    } while (__any_sync(0xffffffffu, any != 0) & (++it < SPIN_LIMIT));
    arrived();
    float f[8];
#pragma unroll
    for (int i = 0; i < 8; i++)
        f[i] = (__uint_as_float(a[i]) + __uint_as_float(a[i + 8])) + (__uint_as_float(a[i + 16]) + __uint_as_float(a[i + 24]));
    f[0] = (f[0] + f[2]) + (f[4] + f[6]);
    f[1] = (f[1] + f[3]) + (f[5] + f[7]);
    return movm(pack2(f[0], f[1]));
}

__global__ void __launch_bounds__(NTHREADS, 1) fused_kernel(const Params P, const __grid_constant__ Maps T) {
    extern __shared__ __align__(1024) char smem_raw[];
    constexpr uint32_t sm = 1024;
    const int tid = threadIdx.x, lane = tid & 31;
    const int cta = blockIdx.x, grp = cta >> 3, sub = cta & 7;
    const uint32_t bars = sm + OFF_BAR;
    const int row0 = (sub * HKV + grp) * SK + (SK - WIN);
    if (tid >> 5 == 9) {
#pragma unroll
        for (int i = 0; i < PFK; i++) asm volatile("prefetch.global.L2 [%0];" ::"l"(P.k + (size_t)row0 * DH + (lane + i * 32) * 64) : "memory");
    }
    u64 pol;
    asm volatile("createpolicy.fractional.L2::evict_first.b64 %0, 1.0;" : "=l"(pol));
    if (tid == NCW * 32) {
        TS(0);
        const int n0 = cta < 90 ? 0 : 3;
#pragma unroll
        for (int i = 0; i < 6; i++) mbar_init(bars + i * 8, 1);
        asm volatile("fence.mbarrier_init.release.cluster;" ::: "memory");
#pragma unroll
        for (int i = 0; i < 3; i++) {
            mbar_expect(bars + (n0 + i) * 8, 12288);
            tma3d(sm + OFF_WM + (n0 + i) * 12288, &T.m[cta < 36 ? M_WA : cta < 90 ? M_WM : M_WQ], cta < 36 ? 16 * cta : 32 * cta,
                  i * 192, 0, bars + (n0 + i) * 8);
            TI(n0 + i);
        }
        TS(26);
    }
    if (tid == NCW * 32 + 32) {
#pragma unroll
        for (int i = 0; i < 4; i++) mbar_init(bars + (BAR_FULL + i) * 8, 1);
        asm volatile("fence.mbarrier_init.release.cluster;" ::: "memory");
#pragma unroll
        for (int t = 0; t < NK0; t++) {
            mbar_expect(bars + (BAR_FULL + t) * 8, TILE_BYTES);
            tma3d_hint(sm + OFF_RING + t * TILE_BYTES, &T.m[M_K], 0, row0 + t * 32, 0, bars + (BAR_FULL + t) * 8, pol);
            TI(6 + t);
        }
    }
    if (tid < 288 && cta < 90) {
#pragma unroll
        for (int i = 0; i < 2; i++) {
            const int row = (lane >> 3) + 4 * i, so = row * DM + (tid >> 5) * 64 + (lane & 7) * 8;
            const uint32_t d = sm + OFF_RED + (tid >> 5) * 2048 + row * 128 + (((lane & 7) ^ row) << 4);
            cp16(d, P.c + so);
            if (cta < 36) cp16(d + 1024, P.x + so);
        }
    }
    uint32_t* const g0 = P.scratch;
    const uint32_t epoch = ld1(g0 + G_EPOCH);
    const int warp = __shfl_sync(0xffffffffu, tid >> 5, 0);

    if (warp >= NCW) {
        const int pw = warp - NCW;
        bar_arrive(1, (NCW + 1) * 32);
        if (pw && lane < M_WQ) asm volatile("prefetch.tensormap [%0];" ::"l"(&T.m[M_WQ - lane]) : "memory");
        if (tid == NCW * 32) sts32(sm + OFF_WIN, 0);
        __syncwarp();
        bar_sync(15, NTHREADS);
        if (lane == 0) {
            if (pw == 0 && cta < 90) {
#pragma unroll 1
                for (int n = 3; n < 6; n++) {
                    mbar_expect(bars + n * 8, 12288);
                    mbar_wait(bars + (n - 3) * 8, 0);
                    tma3d(sm + OFF_WM + n * 12288, &T.m[M_WQ], 32 * cta, (n - 3) * 192, 0, bars + n * 8);
                    TI(n);
                }
            }
#pragma unroll 1
            for (int t = NK0 + (1 - pw) * NK1; t < NK0 + NK1 + 3 * (1 - pw); t++) {
                mbar_expect(bars + (BAR_FULL + t) * 8, TILE_BYTES);
                mbar_wait(bars + (t + (pw ? BAR_FULL - NK1 : 3 - NK0 - NK1)) * 8, 0);
                tma3d_hint(sm + OFF_RING + t * TILE_BYTES, &T.m[M_K], 0, row0 + t * 32, 0, bars + (BAR_FULL + t) * 8, pol);
                TI(6 + t);
            }
            if (pw == 0) {
                auto on_time = [&](int due, uint32_t bar, uint32_t parity) {
                    uint32_t origin;
                    do origin = lds32(sm + OFF_WIN);
                    while (origin && (int)(clock32(0) - origin - due) < 0 && !mbar_test(bar, parity));
                };
#pragma unroll 1
                for (int t = NK0 + NK1 + 3; t < 2 * NT; t++) {
                    if (t == 14 && cta < 90) mbar_wait(bars + BAR_WMF * 8, 0);
                    if (t == 15) TS(30);
                    const uint32_t fb = bars + (BAR_FULL + (t & 15)) * 8;
                    const int hi = t - (lds32(sm + OFF_WIN) ? W_HI : W_0), lo = t - W_LO;
                    mbar_wait(fb + (BAR_EMPTY - BAR_FULL) * 8, (~t >> 4) & 1);
                    mbar_expect(fb, TILE_BYTES);
                    mbar_wait(bars + (BAR_FULL + (hi & 15)) * 8, (hi >> 4) & 1);
                    on_time(t * TAU - L_KV, bars + (BAR_FULL + (lo & 15)) * 8, (lo >> 4) & 1);
                    tma3d_hint(sm + OFF_RING + (t & 15) * TILE_BYTES, &T.m[t >> 6], 0, row0 + (t & (NT - 1)) * 32, 0, fb, pol);
                    TI(6 + t);
                    if (t == T_CLEAR) mbar_arrive(bars + (BAR_SYNC + 1) * 8);
                }
                mbar_wait(bars + BAR_SYNC * 8, 0);
                auto window = [&](int b, int lead) {
                    mbar_wait(bars + (b - W_HI) * 8, b - W_HI < BAR_WO);
                    on_time((2 * NT - 1) * TAU + (b - BAR_WO + 1) * TAU_W - lead, bars + (b - W_LO) * 8, b - W_LO < BAR_WO);
                };
#pragma unroll 1
                for (int i = 0; i < 4; i++) {
                    window(BAR_WO + i, L_WO);
                    tma3d(sm + OFF_WO + i * 8192, &T.m[M_OD], 64 * sub, grp * 256 + i * 64, P.zo, bars + (BAR_WO + i) * 8);
                    tma3d(sm + OFF_OX + i * 1024, &T.m[M_OX], 512 + 8 * sub, grp * 256 + i * 64, P.zo, bars + (BAR_WO + i) * 8);
                    TI(134 + i);
                }
                TS(28);
#pragma unroll 1
                for (int i = 0; i < 9; i++) {
                    mbar_wait(bars + (BAR_EMPTY + i) * 8, 1);
                    window(BAR_GU + i, L_GU);
                    tma3d(sm + OFF_GU + i * 8192, &T.m[M_GU], grp * 288 + 32 * sub, i * 64, 0, bars + (BAR_GU + i) * 8);
                    if (sub < 4) tma3d(sm + OFF_GX + i * 2048, &T.m[M_GX], grp * 288 + 256 + 8 * sub, i * 64, 0, bars + (BAR_GU + i) * 8);
                    TI(138 + i);
                }
                TS(29);
#pragma unroll 1
                for (int i = 0; i < 5; i++) {
                    const int blk = i < 4 ? (i + 3) & 3 : 4, r = min(blk * 64, 224);
                    mbar_wait(bars + (BAR_EMPTY + 9 + blk) * 8, 1);
                    window(BAR_WD + i, L_WD + (i == 4 ? L_LAST : 0));
                    tma3d(sm + OFF_WD + r * 128, &T.m[M_OD], 64 * sub, grp * 288 + r, P.zo ^ 1, bars + (BAR_WD + i) * 8);
                    tma3d(sm + OFF_DX + r * 16, &T.m[M_OX], 512 + 8 * sub, grp * 288 + r, P.zo ^ 1, bars + (BAR_WD + i) * 8);
                    TI(147 + i);
                }
                if (cta < 72) {
                    mbar_wait(bars + (BAR_EMPTY + 14) * 8, 1);
                    mbar_wait(bars + (BAR_EMPTY + 15) * 8, 1);
                    mbar_expect(bars + BAR_GB * 8, 9216);
                    window(BAR_WD + 5, L_GB);
#pragma unroll
                    for (int i = 0; i < 3; i++) tma3d(sm + OFF_GB + i * 3072, &T.m[M_GB], 5 * DM + 8 * cta, i * 192, 0, bars + BAR_GB * 8);
                }
            } else {
#pragma unroll 1
                for (int i = BAR_WO; i < BAR_WD + 5; i++) mbar_expect(bars + i * 8, i < BAR_GU || i >= BAR_WD ? 9216 : sub < 4 ? 10240 : 8192);
                mbar_arrive(bars + BAR_SYNC * 8);
                uint32_t* const cnt = g0 + (epoch & 1) * G_SET + G_CNT;
                uint32_t origin = 0;
#pragma unroll 1
                for (int t = cta & 3; t < 144; t += 4) {
                    const uint32_t bar = bars + (BAR_FULL + (t < 2 * NT ? t & 15 : t - 112)) * 8;
                    mbar_wait(bar, (t >> 4) & 1);
                    if (t < 2 * NT) mbar_arrive(bar + (BAR_EMPTY - BAR_FULL) * 8);
                    const uint32_t t0 = clock32(0);
                    const int c = (int)atomicAdd(cnt, 1u) - 16;
                    const uint32_t o = t0 + ((clock32(c) - t0) >> 1) - ((c * TAU + max(c - 32 * (2 * NT - 1), 0) * (TAU_W - TAU)) >> 5);
                    if (t < T_PACE) continue;
                    origin = (origin ? origin + ((int)(o - origin) >> SMOOTH) : o) | 1;
                    sts32(sm + OFF_WIN, origin);
                }
            }
        }
        return;
    }

    if (lane == 0) {
#pragma unroll
        for (int i = 0; i < 6; i++) {
            const int b = 10 + warp * 6 + i;
            mbar_init(bars + b * 8, b >= BAR_EMPTY && b < BAR_EMPTY + 16 && ((b ^ cta) & 3) == 0 ? 2 : 1);
        }
        asm volatile("fence.mbarrier_init.release.cluster;" ::: "memory");
    }
    __syncwarp();
    if (warp < 9) bar_arrive(15, NTHREADS);
    const int g = lane >> 2, t4 = lane & 3;
    uint32_t* const gs = g0 + (epoch & 1) * G_SET;

    uint32_t sc[8] = {};
    if (warp < 9) {
        const int off_h = (cta < 36 ? dual(D_H + 2 * cta * 32) : G_M + 4 * (cta - 36) * 32) + tid;
        const int off_h2 = off_h + (cta < 36 ? 1024 : 64);
        const int off_q = dual(D_Q + g * (HQ * 64) + cta * 16) + warp * 8 + t4 * 2;
        uint32_t bf[8] = {}, xp = 0, mean2 = 0;
        float inv = 0.f;
        if (cta < 36) xp = __ldg(reinterpret_cast<const uint32_t*>(P.x) + g * (DM / 2) + 8 * cta + 4 * (warp & 1) + t4);
        if (warp < 2) {
            st2(gs + off_q, 0, 0), st2(gs + off_q + 1024, 0, 0);
            if (cta < 36) st1(gs + off_h, 0), st1(gs + off_h2, 0);
        }
        if (cta < 90) {
            asm volatile("cp.async.wait_all;" ::: "memory");
            __syncwarp();
            const uint32_t fa = sm + OFF_RED + warp * 2048 + (lane & 7) * 128 + (((lane >> 3) ^ (lane & 7)) << 4);
            ldsm4(reinterpret_cast<uint32_t(&)[4]>(bf[0]), fa);
            ldsm4(reinterpret_cast<uint32_t(&)[4]>(bf[4]), fa ^ 64);
            if (cta < 36) {
                uint32_t xv[8];
                ldsm4(reinterpret_cast<uint32_t(&)[4]>(xv[0]), fa + 1024);
                ldsm4(reinterpret_cast<uint32_t(&)[4]>(xv[4]), (fa ^ 64) + 1024);
                ln_partial(xv, sm + OFF_ST + g * 80 + warp * 8, t4 == 0);
            }
#pragma unroll
            for (int i = 0; i < 8; i++) sc[i] = bf[i] = silu2(bf[i]);
        }
        if (warp == 0) TSL(18);
        bar_sync(1, (NCW + 1) * 32);
        if (cta < 36 && warp < 2) ln_combine(sm + OFF_ST + g * 80, mean2, inv);
        const int r = warp * 64 + (lane >> 4) * 8 + (lane & 7), hi8 = (lane >> 3) & 1, box = warp / 3;
#pragma unroll 1
        for (int pass = cta < 90 ? 0 : 1; pass < 2; pass++) {
            const bool pa = pass == 0 && cta < 36;
            const uint32_t ab = sm + OFF_WM + pass * 36864 +
                                (pa ? (box + hi8) * 6144 + r * 32 + ((lane & 4) << 2) : r * 64 + (((2 * hi8) ^ ((r >> 1) & 3)) << 4));
            const uint32_t as = pa ? 512 : 1024, red = sm + OFF_RED + pass * 9216;
            mbar_wait(bars + (pass * 3 + box) * 8, 0);
            if (warp == 8) TSL(pass ? 31 : 19);
            uint32_t a[4][2][4];
#pragma unroll
            for (int i = 0; i < 4; i++) {
                ldsm4t(a[i][0], ab + i * as);
                ldsm4t(a[i][1], (ab ^ 16) + i * as);
            }
            if (pass) {
                bar_sync(8, NCW * 32);
#pragma unroll
                for (int i = 0; i < 8; i++) bf[i] = 0;
                const uint32_t* const src_h = gs + near(D_H + warp * 256, lds32(sm + OFF_WIN + 4)) + lane;
                get<1, 1>(src_h, 0, reinterpret_cast<uint32_t(&)[1]>(bf[0]));
                get<8, 1>(src_h, 32, bf);
                if (warp == 0) TSL(3);
            }
            float acc[2][4] = {};
#pragma unroll
            for (int i = 0; i < 4; i++)
#pragma unroll
                for (int m = 0; m < 2; m++) mma(acc[m], a[i][m][0], a[i][m][1], a[i][m][2], a[i][m][3], bf[2 * i], bf[2 * i + 1]);
            sts128f(red + tid * 16, acc[0]);
            sts128f(red + 4608 + tid * 16, acc[1]);
            bar_sync(3, 288);
            if (warp < 2) {
                float c[4] = {};
                sum_frags<9>(c, red + warp * 4608 + lane * 16, 512);
                uint32_t lo = movm(pack2(c[0], c[1])), hi = movm(pack2(c[2], c[3]));
                if (pass) {
                    put2d(gs + off_q, lo, hi);
                    if (warp == 0) TSL(4);
                } else {
                    const uint32_t hi1 = badd2(hi, ONE2);
                    if (pa) hi = lo = modulate2(xp, mean2, inv, lo, hi1);
                    if (cta >= 72) lo = badd2(lo, ONE2), hi = hi1;
                    st1(gs + off_h, nz(lo));
                    st1(gs + off_h2, nz(hi));
                    if (warp == 0 && pa) TSL(2);
                }
            } else if (tid == 64 && pass == 0) {
                mbar_arrive(bars + BAR_WMF * 8);
            }
        }
    } else {
        if ((uint32_t)__cvta_generic_to_shared(smem_raw) != sm) __trap();
        uint32_t* const ping = g0 + dual(D_PING) + cta * 8;
        if (lane < 16) st1(ping + (lane >> 3) * 1024 + (lane & 7), 0);
        bar_sync(15, NTHREADS);
        uint32_t best[2] = {~0u, ~0u}, v = 0;
#pragma unroll 1
        for (int part = 0; part < 2; part++) {
            if (lane == 0) {
#pragma unroll 1
                for (int r = part ? NPING1 : NPING0; r > 0; r--) {
#pragma unroll
                    for (int k = 0; k < 2; k++) {
                        const uint32_t t0 = clock32(v);
                        v = atomicExch(ping + k * 1024, t0);
                        best[k] = min(best[k], clock32(v) - t0);
                    }
                }
                sts32(sm + OFF_WIN + 4 + 4 * part, ((best[1] < best[0]) ^ __popc(D_PING & 0x16400)) & 1);
            }
            __syncwarp();
            if (part) break;
            TSL(20);
            bar_arrive(8, NCW * 32);
            mbar_wait(bars + 5 * 8, 0);
            uint32_t a[4] = {};
            get<1, 4>(gs + near(D_Q + (sub * HQ + 2 * grp) * 64, lds32(sm + OFF_WIN + 4)) + lane * 4, 0, a);
            sts128(sm + OFF_QS + lane * 16, a[0], a[1], a[2], a[3]);
            __syncwarp();
            TSL(5);
            bar_arrive(4, 288);
        }
#pragma unroll
        for (int i = lane; i < 72; i += 32) cp16(sm + OFF_WR + i * 16, P.wr + i * 8);
        __syncwarp();
        if (cta < 72 && lane < 16) st1(g0 + ((epoch ^ lane >> 3) & 1) * G_SET + G_SIDE + cta * 8 + (lane & 7), lane < 8 ? 1 + lds32(sm + OFF_WIN + 8) : 0);
        asm volatile("cp.async.wait_all;" ::: "memory");
        __syncwarp();
        bar_arrive(2, NCW * 32);
        if (cta == 0 && lane == 0) st1(g0 + (~epoch & 1) * G_SET + G_CNT, 0);
        mbar_wait(bars + (BAR_SYNC + 1) * 8, 0);
#pragma unroll 1
        for (int c = 0; c < 4; c++) {
            uint32_t* const pg = g0 + (c >> 1) * G_SET + (c & 1) * 1024;
            zero4(pg + dual(D_O + cta * 128) + lane * 4);
            zero4(pg + dual(D_ACT + (grp * 36 + 4 * sub) * 32) + lane * 4);
            if (lane < 8 ? sub < 4 : lane < 16 && cta < 72)
                zero4(pg + dual(lane < 8 ? D_ACT + (grp * 36 + 32 + sub) * 32 : D_X1 + cta * 32) + (lane & 7) * 4);
        }
#pragma unroll 1
        for (int u = 0; u < 9; u++) zero4(g0 + dual(d_part(u < 8 ? 8 * sub + u : 64 + sub)) + (lane >> 4) * 1024 + grp * 64 + (lane & 15) * 4);
        {
            uint32_t* const nx = g0 + (~epoch & 1) * G_SET;
            uint32_t* const q = nx + dual(D_Q + g * (HQ * 64) + cta * 16) + t4 * 4;
            zero4(q), zero4(q + 1024);
            if (cta < 90) zero4(nx + (cta < 36 ? dual(D_H + 2 * cta * 32) + (lane >> 4) * (1024 - 64) : G_M + 4 * (cta - 36) * 32) + lane * 4);
        }
        if (cta >= 72) {
            bar_arrive(5, NCW * 32);
            return;
        }
        const uint32_t io = pin(4 * (g * (DM / 2) + 4 * cta + t4));
        uint32_t x = __ldg(at(reinterpret_cast<const uint32_t*>(P.x), io)), ga[1] = {};
        get<1, 1>(gs + G_M + cta * 32 + lane, 0, ga);
        const uint32_t src_p = pin(4 * (near(d_part(cta), lds32(sm + OFF_WIN + 8)) + lane * 2));
        const uint32_t dst_x = pin(4 * ((epoch & 1) * G_SET + dual(D_X1 + cta * 32) + lane));
        bar_sync(5, NCW * 32);
        x = badd2(x, bmul2(ga[0], reduce16<0>(at(g0, src_p), [] {})));
        put1d(at(g0, dst_x), x);
        TSL(10);
        bar_sync(6, NCW * 32);
        const uint4 r0 = lds128(sm + OFF_RT + g * 48), r1 = lds128(sm + OFF_RT + g * 48 + 16);
        float r = __uint_as_float(lds32(sm + OFF_RT + g * 48 + 32));
        r += ((__uint_as_float(r0.x) + __uint_as_float(r0.y)) + (__uint_as_float(r0.z) + __uint_as_float(r0.w))) +
             ((__uint_as_float(r1.x) + __uint_as_float(r1.y)) + (__uint_as_float(r1.z) + __uint_as_float(r1.w)));
        r = sigmoid_f(rbf(r));
        const uint32_t h = lds32(sm + OFF_RED + (cta >> 2) * 512 + lane * 16 + (cta & 3) * 4), rs = pack2(r, r);
        uint32_t gb;
        const uint32_t y = reduce16<1>(at(g0, src_p), [&] {
            TSL(23);
            bar_sync(9, 64);
            gb = lds32(sm + OFF_QS + lane * 4);
        });
        *at(reinterpret_cast<uint32_t*>(P.out), io) = badd2(x, bmul2(gb, badd2(h, bmul2(y, rs))));
        if (cta == 0 && lane == 0) g0[G_EPOCH] = epoch + 1;
        TSL(15);
        return;
    }

    const uint32_t tile = sm + OFF_RING + warp * TILE_BYTES;
    const uint32_t fullb = bars + (BAR_FULL + warp) * 8;
    const uint32_t pw = sm + OFF_P + warp * (2 * P_PITCH);
    if (warp < 8) {
        {
            uint32_t q0[8], q1[8];
            bar_sync(4, 288);
#pragma unroll
            for (int i = 0; i < 8; i++) {
                const float2 v = lds64f(sm + OFF_QS + (g & 1) * 256 + i * 32 + t4 * 8);
                q0[i] = __float_as_uint(v.x), q1[i] = __float_as_uint(v.y);
            }
            uint32_t sp = pw + (t4 & 1) * P_PITCH + ((t4 >> 1) * 8 + g) * 2;
#pragma unroll 1
            for (int it = 0; it < 8; it++, sp += 64) {
                const uint32_t ab = tile + (it & 1) * (8 * TILE_BYTES) + (lane & 15) * 128 + (((lane >> 4) ^ (lane & 7)) << 4);
                mbar_wait(fullb + (it & 1) * 64, (it >> 1) & 1);
                float acc[2][2][4] = {};
#pragma unroll
                for (int ks = 0; ks < 8; ks++)
#pragma unroll
                    for (int m = 0; m < 2; m++) {
                        uint32_t a[4];
                        ldsm4(a, (ab ^ ((ks & 3) << 5)) + (ks >> 2) * 4096 + m * 2048);
                        mma(acc[m][ks & 1], a[0], a[1], a[2], a[3], (ks & 1) ? q1[ks - 1] : q0[ks], (ks & 1) ? q1[ks] : q0[ks + 1]);
                    }
                __syncwarp();
                if (lane == 0) mbar_arrive(fullb + (it & 1) * 64 + (BAR_EMPTY - BAR_FULL) * 8);
#pragma unroll
                for (int m = 0; m < 2; m++) {
                    const float s = sel4(acc[m][0], t4) + sel4(acc[m][1], t4);
                    sts16(sp + m * 32, (uint16_t)pack2(rbf(s) * 0.08838834764831845f, 0.f));
                }
            }
        }
        __syncwarp();
        if (warp == 7) TSL(6);
        const uint32_t pa = pw + (lane >> 4) * P_PITCH + (lane & 15) * 32;
        const uint32_t sa = sm + OFF_SM + (lane >> 4) * 64;
        const uint4 v0 = lds128(pa), v1 = lds128(pa + 16);
        const uint32_t sv[8] = {v0.x, v0.y, v0.z, v0.w, v1.x, v1.y, v1.z, v1.w};
        float e[16];
        float m = -INFINITY;
#pragma unroll
        for (int i = 0; i < 8; i++) {
            e[2 * i] = blo(sv[i]);
            e[2 * i + 1] = bhi(sv[i]);
            m = fmaxf(m, fmaxf(e[2 * i], e[2 * i + 1]));
        }
#pragma unroll
        for (int o = 8; o; o >>= 1) m = fmaxf(m, __shfl_xor_sync(0xffffffffu, m, o));
        float l = 0.f;
#pragma unroll
        for (int i = 0; i < 16; i++) {
            e[i] = ex2((e[i] - m) * LOG2E);
            l += e[i];
        }
#pragma unroll
        for (int o = 8; o; o >>= 1) l += __shfl_xor_sync(0xffffffffu, l, o);
        if ((lane & 15) == 0) sts64(sa + warp * 8, __float_as_uint(m), __float_as_uint(l));
        bar_sync(2, NCW * 32);
        const float2 v = lds64f(sa + (lane & 7) * 8);
        float M = v.x;
#pragma unroll
        for (int o = 4; o; o >>= 1) M = fmaxf(M, __shfl_xor_sync(0xffffffffu, M, o));
        float L = v.y * ex2((v.x - M) * LOG2E);
#pragma unroll
        for (int o = 4; o; o >>= 1) L += __shfl_xor_sync(0xffffffffu, L, o);
        const float sc = ex2((m - M) * LOG2E) * rcp(L);
        sts128(pa, pack2(e[0] * sc, e[1] * sc), pack2(e[2] * sc, e[3] * sc), pack2(e[4] * sc, e[5] * sc), pack2(e[6] * sc, e[7] * sc));
        sts128(pa + 16, pack2(e[8] * sc, e[9] * sc), pack2(e[10] * sc, e[11] * sc), pack2(e[12] * sc, e[13] * sc), pack2(e[14] * sc, e[15] * sc));
        __syncwarp();
    } else {
        bar_sync(2, NCW * 32);
    }

    uint32_t sh[8] = {}, op[8] = {};
    {
        const uint32_t* const src_m = gs + G_M + (72 + warp * 8) * 32 + lane;
        fetch<8, 1>(src_m + 72 * 32, 32, op);
        get<8, 1>(src_m, 32, sh);
        get<8, 1>(src_m + 72 * 32, 32, op);
    }
    const int side = lds32(sm + OFF_WIN + 8), set = (epoch & 1) * G_SET, rr = (lane >> 4) * 8 + (lane & 7);
    const uint32_t dst_o = pin(4 * (set + dual(D_O + cta * 128) + (tid & 0x70) + (tid & 3) * 4 + ((tid >> 2) & 3)));
    const uint32_t src_o = pin(4 * (set + near(D_O + grp * 1024, side) + g * 128 + warp * 16 + t4 * 4));
    const int unit = warp < 8 ? 8 * sub + warp : 64 + sub;
    uint32_t rside[1] = {};
    get<1, 1>(gs + G_SIDE + unit * 8, 0, rside);
    const uint32_t dst_p = pin(4 * (near(d_part(unit), rside[0] - 1) + grp * 64 + lane * 2));
    const uint32_t src_x = pin(4 * (set + near(D_X1 + warp * 256, side) + lane));
    const uint32_t dst_a = pin(4 * (set + dual(D_ACT + (grp * 36 + (warp < 4 ? 4 * sub + warp : 32 + sub)) * 32) + lane));
    const uint32_t src_a = pin(4 * (set + near(D_ACT + (grp * 36 + 4 * warp) * 32, side) + lane));
    const uint32_t rowoff = pin((warp * 32 + rr) * 128 + ((((lane >> 3) & 1) ^ (lane & 7)) << 4));
    const uint32_t reds = pin((tid * 8) | (warp * 2304 + lane * 8) << 16);
    const uint32_t ored = pin((warp * 1088 + (t4 & 1) * 576 + ((t4 >> 1) * 8 + g) * 4) | ((tid >> 6) * 64 + tid * 8) << 16);

    if (warp < 8) {
        float acc[8][4] = {};
        uint32_t pp = pw + (lane & 1) * P_PITCH + (lane >> 3) * 16;
#pragma unroll 1
        for (int it = 0; it < 8; it++, pp += 64) {
            const uint32_t ab = tile + (it & 1) * (8 * TILE_BYTES) + ((lane & 7) + (lane >> 4) * 8) * 128 + ((((lane >> 3) & 1) ^ (lane & 7)) << 4);
            uint32_t pb[4];
            ldsm4(pb, pp);
            mbar_wait(fullb + (it & 1) * 64, (it >> 1) & 1);
#pragma unroll
            for (int ks = 0; ks < 2; ks++)
#pragma unroll
                for (int m = 0; m < 8; m++) {
                    uint32_t a[4];
                    ldsm4t(a, (ab ^ ((m & 3) << 5)) + (m >> 2) * 4096 + ks * 2048);
                    mma(acc[m], a[0], a[1], a[2], a[3], pb[2 * ks], pb[2 * ks + 1]);
                }
            __syncwarp();
            if (lane == 0) mbar_arrive(fullb + (it & 1) * 64 + (BAR_EMPTY - BAR_FULL) * 8);
        }
        if (warp == 7) TSL(7);
        const uint32_t ra = sm + OFF_ORED + (ored & 0xffff);
#pragma unroll
        for (int m = 0; m < 8; m++) sts32(ra + m * 64, __float_as_uint(sel4(acc[m], t4)));
    }
    bar_sync(5, NCW * 32);
    if (warp < 4) {
        float s[2][2] = {};
#pragma unroll
        for (int w = 0; w < 8; w++) {
            const float2 v = lds64f(sm + OFF_ORED + w * 1088 + (ored >> 16));
            s[w & 1][0] += v.x;
            s[w & 1][1] += v.y;
        }
        put1d(at(g0, dst_o), pack2(s[0][0] + s[1][0], s[0][1] + s[1][1]));
        if (warp == 0) TSL(8);
    }

    project<0>(sm, at(g0, src_o), at(g0, dst_p), rowoff, reds, 288, warp, lane);
    if (warp == 0) TSL(9);

    {
        uint32_t h[8] = {}, mean2;
        float inv;
        get<1, 1>(at(g0, src_x), 0, reinterpret_cast<uint32_t(&)[1]>(h[0]));
        get<8, 1>(at(g0, src_x), 32, h);
        if (warp == 0) TSL(11);
        ln_partial(h, sm + OFF_ST + g * 80 + warp * 8, t4 == 0);
        bar_sync(3, 288);
        ln_combine(sm + OFF_ST + g * 80, mean2, inv);
#pragma unroll
        for (int i = 0; i < 8; i++) h[i] = modulate2(h[i], mean2, inv, sh[i], op[i]);
        sts128(sm + OFF_RED + warp * 1024 + lane * 16, h[0], h[1], h[2], h[3]);
        sts128(sm + OFF_RED + warp * 1024 + 512 + lane * 16, h[4], h[5], h[6], h[7]);
        if (warp == 0) TSL(12);
        if (cta < 72) {
            float r = 0.f;
#pragma unroll
            for (int i = 0; i < 8; i++) {
                const uint32_t wr = lds32(sm + OFF_WR + (warp * 32 + i * 4 + t4) * 4);
                r = fmaf(blo(h[i]), blo(wr), fmaf(bhi(h[i]), bhi(wr), r));
            }
            r = quad_sum(r);
            if (t4 == 0) sts32(sm + OFF_RT + g * 48 + warp * 4, __float_as_uint(r));
        }
    }
    bar_sync(3, 288);

    if (warp < (sub < 4 ? 5 : 4)) {
        const int pl = ((lane >> 3) & 1) ^ P.zg;
        const uint32_t ks = warp < 4 ? 1024 : 256;
        uint32_t aa = sm + (warp < 4 ? OFF_GU + rr * 64 + (((lane & 6) << 3) ^ (warp << 4)) : OFF_GX + rr * 16) + pl * 4 * ks;
        float acc[2][4] = {};
        constexpr int UN = GU_UNROLL;
#pragma unroll UN
        for (int i = 0; i < 9; i++, aa += 8 * ks) {
            const uint4 b0 = lds128(sm + OFF_RED + i * 1024 + lane * 16), b1 = lds128(sm + OFF_RED + i * 1024 + 512 + lane * 16);
            uint32_t a[4][4];
            mbar_wait(bars + (BAR_GU + i) * 8, 0);
#pragma unroll
            for (int k = 0; k < 4; k++) ldsm4t(a[k], aa + k * ks);
            mma(acc[0], a[0][0], a[0][1], a[0][2], a[0][3], b0.x, b0.y);
            mma(acc[1], a[1][0], a[1][1], a[1][2], a[1][3], b0.z, b0.w);
            mma(acc[0], a[2][0], a[2][1], a[2][2], a[2][3], b1.x, b1.y);
            mma(acc[1], a[3][0], a[3][1], a[3][2], a[3][3], b1.z, b1.w);
        }
        if (warp == 1) TSL(17);
        const uint32_t gate = pack2(acc[0][0] + acc[1][0], acc[0][1] + acc[1][1]), up = pack2(acc[0][2] + acc[1][2], acc[0][3] + acc[1][3]);
        put1d(at(g0, dst_a), movm(bmul2(silu2(gate), up)));
        if (warp == 1) TSL(13);
    } else {
        mbar_wait(bars + (BAR_GU + 8) * 8, 0);
    }

    project<1>(sm, at(g0, src_a), at(g0, dst_p), rowoff, reds, cta < 72 ? 320 : 288, warp, lane);
    if (warp == 0) TSL(14);
    if (warp == 8) TSL(27);

    if (cta < 72) {
        const uint32_t ga = sm + OFF_GB + warp * 1024 + ((lane >> 3) & 1) * 256 + (lane >> 4) * 128 + (lane & 7) * 16;
        float acc[2][4] = {};
        mbar_wait(bars + BAR_GB * 8, 0);
        if (warp == 0) TSL(22);
#pragma unroll
        for (int i = 0; i < 2; i++) {
            uint32_t w[4];
            ldsm4t(w, ga + i * 512);
            mma(acc[0], w[0], w[1], w[2], w[3], sc[4 * i], sc[4 * i + 1]);
            mma(acc[1], w[0], w[1], w[2], w[3], sc[4 * i + 2], sc[4 * i + 3]);
        }
        sts64(sm + OFF_RED + 9216 + (reds & 0xffff), __float_as_uint(acc[0][0] + acc[1][2]), __float_as_uint(acc[0][1] + acc[1][3]));
        if (warp) {
            bar_arrive(7, 288);
        } else {
            bar_sync(7, 288);
            float s[2][2] = {};
#pragma unroll
            for (int w = 0; w < 9; w++) {
                const float2 v = lds64f(sm + OFF_RED + 9216 + (reds & 0xffff) + w * 256);
                s[w & 1][0] += v.x;
                s[w & 1][1] += v.y;
            }
            sts32(sm + OFF_QS + lane * 4, movm(pack2(s[0][0] + s[1][0], s[0][1] + s[1][1])));
            __syncwarp();
            bar_arrive(9, 64);
            TSL(25);
        }
    }
}

typedef CUresult (*EncodeFn)(CUtensorMap*, CUtensorMapDataType, cuuint32_t, void*, const cuuint64_t*, const cuuint64_t*,
                             const cuuint32_t*, const cuuint32_t*, CUtensorMapInterleave, CUtensorMapSwizzle,
                             CUtensorMapL2promotion, CUtensorMapFloatOOBfill);

void make_map(EncodeFn enc, CUtensorMap* m, void* p, int cols, int rows, int pitch, int bc, int br, int bp, int planes, size_t pstride,
              CUtensorMapSwizzle sw, int promo) {
    cuuint64_t dims[3] = {(cuuint64_t)cols, (cuuint64_t)rows, (cuuint64_t)planes};
    cuuint64_t strides[2] = {(cuuint64_t)pitch * 2, (cuuint64_t)pstride};
    cuuint32_t box[3] = {(cuuint32_t)bc, (cuuint32_t)br, (cuuint32_t)bp};
    cuuint32_t es[3] = {1, 1, 1};
    enc(m, CU_TENSOR_MAP_DATA_TYPE_BFLOAT16, 3, p, dims, strides, box, es, CU_TENSOR_MAP_INTERLEAVE_NONE, sw,
        (CUtensorMapL2promotion)promo, CU_TENSOR_MAP_FLOAT_OOB_FILL_NONE);
}

}

extern "C" void kernel_launch(void* const* d_in, const int* in_sizes, int n_in, void* d_out, int out_size) {
    static EncodeFn enc = nullptr;
    static uint32_t* scratch = nullptr;
    if (!enc) {
        void* fn = nullptr;
        cudaDriverEntryPointQueryResult st;
        cudaGetDriverEntryPoint("cuTensorMapEncodeTiled", &fn, cudaEnableDefault, &st);
        enc = (EncodeFn)fn;
        cudaGetSymbolAddress(&fn, g_scratch);
        scratch = (uint32_t*)(((uintptr_t)fn + 8 * G_SET - 1) & ~(uintptr_t)(8 * G_SET - 1));
        cudaFuncSetAttribute(fused_kernel, cudaFuncAttributeMaxDynamicSharedMemorySize, SMEM_BYTES);
    }
    Params P;
    Maps T;
    const CUtensorMapSwizzle none = CU_TENSOR_MAP_SWIZZLE_NONE;
    const int PROMO_W = CU_TENSOR_MAP_L2_PROMOTION_L2_128B, PROMO_KV = CU_TENSOR_MAP_L2_PROMOTION_L2_256B;
    make_map(enc, &T.m[M_K], d_in[1], 64, NB * HKV * SK, DH, 64, 32, 2, 2, 128, CU_TENSOR_MAP_SWIZZLE_128B, PROMO_KV);
    make_map(enc, &T.m[M_V], d_in[2], 64, NB * HKV * SK, DH, 64, 32, 2, 2, 128, CU_TENSOR_MAP_SWIZZLE_128B, PROMO_KV);
    make_map(enc, &T.m[M_WQ], d_in[3], HQ * DH, DM, HQ * DH, 32, 192, 1, 1, 16, CU_TENSOR_MAP_SWIZZLE_64B, PROMO_W);
    make_map(enc, &T.m[M_WM], d_in[11], 6 * DM, DM, 6 * DM, 32, 192, 1, 1, 16, CU_TENSOR_MAP_SWIZZLE_64B, PROMO_W);
    make_map(enc, &T.m[M_WA], d_in[11], DM, DM, 6 * DM, 16, 192, 2, 2, DM * 2, CU_TENSOR_MAP_SWIZZLE_32B, PROMO_W);
    make_map(enc, &T.m[M_GB], d_in[11], 6 * DM, DM, 6 * DM, 8, 192, 1, 1, 16, none, PROMO_W);
    char *wg = (char*)d_in[7], *wu = (char*)d_in[8], *wo = (char*)d_in[4], *wd = (char*)d_in[9];
    P.zg = wg > wu;
    P.zo = wo > wd;
    const size_t sg = P.zg ? wg - wu : wu - wg, so = P.zo ? wo - wd : wd - wo;
    make_map(enc, &T.m[M_GU], P.zg ? wu : wg, FF, DM, FF, 32, 64, 2, 2, sg, CU_TENSOR_MAP_SWIZZLE_64B, PROMO_W);
    make_map(enc, &T.m[M_GX], P.zg ? wu : wg, FF, DM, FF, 8, 64, 2, 2, sg, none, PROMO_W);
    make_map(enc, &T.m[M_OD], P.zo ? wd : wo, DM, FF, DM, 64, 64, 1, 2, so, CU_TENSOR_MAP_SWIZZLE_128B, PROMO_W);
    make_map(enc, &T.m[M_OX], P.zo ? wd : wo, DM, FF, DM, 8, 64, 1, 2, so, none, PROMO_W);
    P.x = (const __nv_bfloat16*)d_in[0];
    P.wr = (const __nv_bfloat16*)d_in[6];
    P.c = (const __nv_bfloat16*)d_in[10];
    P.k = (const __nv_bfloat16*)d_in[1];
    P.out = (__nv_bfloat16*)d_out;
    P.scratch = scratch;
    void* args[2] = {&P, &T};
    cudaLaunchCooperativeKernel((const void*)fused_kernel, dim3(NCTA), dim3(NTHREADS), args, SMEM_BYTES, cudaStreamPerThread);
}
```

```cpp
#include <cuda_runtime.h>
#include <cuda_bf16.h>
#include <cuda.h>
#include <stdint.h>

typedef unsigned long long u64;

#define GU_UNROLL 1
#define LATE_ITEMS 2
#define TAU 568
#define TAU_W 650
#define L_KV 3200
#define L_WO 2850
#define L_GU 2850
#define L_WD 3100
#define L_LAST 250
#define L_GB 3000
#define W_0 6
#define W_LO 2
#define W_HI 8
#define T_PACE 20
#define SMOOTH 1
#define NK0 3
#define NK1 2
#define PFK 2
#define T_CLEAR 116
#define NPING0 4
#define NPING1 16

namespace {

constexpr int NB = 8, DM = 576, HQ = 32, HKV = 16, SK = 8192, WIN = 2048, DH = 128, FF = 4608;
constexpr int NCTA = 128;
constexpr int NCW = 10;
constexpr int NTHREADS = (NCW + 2) * 32;
constexpr int TILE_BYTES = 8192, NT = 64;
constexpr int SPIN_LIMIT = 1 << 22;

constexpr int OFF_RING = 0;
constexpr int OFF_WM = 121856;
constexpr int OFF_WQ = OFF_WM + 36864;
constexpr int OFF_GU = 0;
constexpr int OFF_WD = 73728;
constexpr int OFF_GB = 114688;
constexpr int OFF_OX = 131072;
constexpr int OFF_DX = OFF_OX + 4096;
constexpr int OFF_GX = OFF_DX + 4608;
constexpr int OFF_WO = OFF_WQ;
constexpr int OFF_P = OFF_WQ + 36864;
constexpr int P_PITCH = 528;
constexpr int OFF_RED = OFF_P + 16 * P_PITCH;
constexpr int OFF_ORED = OFF_RED + 5 * 4608 - 8704;
constexpr int OFF_ST = OFF_RED + 5 * 4608;
constexpr int OFF_SM = OFF_ST + 640;
constexpr int OFF_RT = OFF_SM + 128;
constexpr int OFF_QS = OFF_RT + 384;
constexpr int OFF_WR = OFF_QS + 512;
constexpr int OFF_WIN = OFF_WR + 1152;
constexpr int OFF_BAR = OFF_WIN + 16;
constexpr int BAR_FULL = 6, BAR_WO = 22, BAR_GU = 26, BAR_WD = 35, BAR_EMPTY = 40, BAR_SYNC = 56, BAR_WMF = 59, BAR_GB = 60, NBAR = 70;
constexpr int SMEM_BYTES = OFF_BAR + NBAR * 8;

constexpr int D_X1 = 0;
constexpr int D_O = 3072;
constexpr int D_ACT = D_O + 512 * 32;
constexpr int D_H = D_ACT + 576 * 32;
constexpr int D_Q = D_H + 3072;
constexpr int G_M = 2 * (D_Q + NB * HQ * 64);
constexpr int G_SIDE = G_M + 216 * 32;
constexpr int G_CNT = G_SIDE + 72 * 8;
constexpr int G_SET = 1 << 18;
__device__ __forceinline__ int d_part(int unit) { return (64 + unit + (unit & 64)) * 1024; }
constexpr int D_PING = 200 * 1024;
constexpr int G_EPOCH = 201 * 2048;
static_assert(G_CNT < 64 * 2048, "scratch layout");
__device__ uint32_t g_scratch[4 * G_SET];
__device__ __forceinline__ int dual(int w) { return w + (w & ~1023); }
__device__ __forceinline__ int near(int w, int side) { return dual(w) + (((__popc(w & 0x16400) ^ side) & 1) << 10); }

#define TI(i)
#define TS(i)
#define TSL(i)

enum { M_K, M_V, M_GU, M_GX, M_OD, M_OX, M_WQ, M_WM, M_WA, M_GB, NMAP };
struct Params {
    const __nv_bfloat16 *c, *x, *k;
    __nv_bfloat16* out;
    uint32_t* scratch;
    const __nv_bfloat16* wr;
    int zg, zo;
};
struct Maps {
    CUtensorMap m[NMAP];
};

__device__ __forceinline__ void mbar_init(uint32_t bar, int cnt) {
    asm volatile("mbarrier.init.shared::cta.b64 [%0], %1;" ::"r"(bar), "r"(cnt));
}
__device__ __forceinline__ void mbar_expect(uint32_t bar, uint32_t bytes) {
    asm volatile("mbarrier.arrive.expect_tx.shared::cta.b64 _, [%0], %1;" ::"r"(bar), "r"(bytes) : "memory");
}
__device__ __forceinline__ void mbar_arrive(uint32_t bar) {
    asm volatile("mbarrier.arrive.shared::cta.b64 _, [%0];" ::"r"(bar) : "memory");
}
__device__ __forceinline__ void mbar_wait(uint32_t bar, uint32_t parity) {
    asm volatile("{\n.reg .pred p;\n.reg .u32 c;\n"
                 "mbarrier.try_wait.parity.shared::cta.b64 p, [%0], %1;\n@p bra DONE;\nmov.u32 c, %2;\n"
                 "AGAIN:\nmbarrier.try_wait.parity.shared::cta.b64 p, [%0], %1;\nsub.u32 c, c, 1;\n"
                 "setp.eq.or.u32 p, c, 0, p;\n@!p bra AGAIN;\nDONE:\n}"
                 ::"r"(bar), "r"(parity), "n"(SPIN_LIMIT) : "memory");
}
__device__ __forceinline__ bool mbar_test(uint32_t bar, uint32_t parity) {
    uint32_t ok;
    asm volatile("{\n.reg .pred p;\nmbarrier.test_wait.parity.shared::cta.b64 p, [%1], %2;\nselp.u32 %0, 1, 0, p;\n}"
                 : "=r"(ok) : "r"(bar), "r"(parity) : "memory");
    return ok;
}
__device__ __forceinline__ void tma3d_hint(uint32_t dst, const CUtensorMap* m, int x, int y, int z, uint32_t bar, u64 pol) {
    asm volatile("cp.async.bulk.tensor.3d.shared::cluster.global.mbarrier::complete_tx::bytes.L2::cache_hint"
                 " [%0], [%1, {%2, %3, %4}], [%5], %6;"
                 ::"r"(dst), "l"(m), "r"(x), "r"(y), "r"(z), "r"(bar), "l"(pol) : "memory");
}
__device__ __forceinline__ void tma3d(uint32_t dst, const CUtensorMap* m, int x, int y, int z, uint32_t bar) {
    asm volatile("cp.async.bulk.tensor.3d.shared::cluster.global.mbarrier::complete_tx::bytes [%0], [%1, {%2, %3, %4}], [%5];"
                 ::"r"(dst), "l"(m), "r"(x), "r"(y), "r"(z), "r"(bar) : "memory");
}
__device__ __forceinline__ void bar_sync(int id, int n) { asm volatile("bar.sync %0, %1;" ::"r"(id), "r"(n) : "memory"); }
__device__ __forceinline__ void bar_arrive(int id, int n) { asm volatile("bar.arrive %0, %1;" ::"r"(id), "r"(n) : "memory"); }
__device__ __forceinline__ void ldsm4(uint32_t (&r)[4], uint32_t a) {
    asm volatile("ldmatrix.sync.aligned.m8n8.x4.shared.b16 {%0,%1,%2,%3}, [%4];"
                 : "=r"(r[0]), "=r"(r[1]), "=r"(r[2]), "=r"(r[3]) : "r"(a) : "memory");
}
__device__ __forceinline__ void ldsm4t(uint32_t (&r)[4], uint32_t a) {
    asm volatile("ldmatrix.sync.aligned.m8n8.x4.trans.shared.b16 {%0,%1,%2,%3}, [%4];"
                 : "=r"(r[0]), "=r"(r[1]), "=r"(r[2]), "=r"(r[3]) : "r"(a) : "memory");
}
__device__ __forceinline__ void mma(float (&c)[4], uint32_t a0, uint32_t a1, uint32_t a2, uint32_t a3, uint32_t b0, uint32_t b1) {
    asm volatile("mma.sync.aligned.m16n8k16.row.col.f32.bf16.bf16.f32 {%0,%1,%2,%3}, {%4,%5,%6,%7}, {%8,%9}, {%0,%1,%2,%3};"
                 : "+f"(c[0]), "+f"(c[1]), "+f"(c[2]), "+f"(c[3])
                 : "r"(a0), "r"(a1), "r"(a2), "r"(a3), "r"(b0), "r"(b1));
}
__device__ __forceinline__ uint32_t movm(uint32_t a) {
    uint32_t d;
    asm volatile("movmatrix.sync.aligned.m8n8.trans.b16 %0, %1;" : "=r"(d) : "r"(a));
    return d;
}
__device__ __forceinline__ uint32_t lds32(uint32_t a) { uint32_t v; asm volatile("ld.volatile.shared.b32 %0, [%1];" : "=r"(v) : "r"(a) : "memory"); return v; }
__device__ __forceinline__ float2 lds64f(uint32_t a) { float2 v; asm volatile("ld.shared.v2.f32 {%0,%1}, [%2];" : "=f"(v.x), "=f"(v.y) : "r"(a) : "memory"); return v; }
__device__ __forceinline__ uint4 lds128(uint32_t a) { uint4 v; asm volatile("ld.shared.v4.b32 {%0,%1,%2,%3}, [%4];" : "=r"(v.x), "=r"(v.y), "=r"(v.z), "=r"(v.w) : "r"(a) : "memory"); return v; }
__device__ __forceinline__ void sts32(uint32_t a, uint32_t v) { asm volatile("st.shared.b32 [%0], %1;" ::"r"(a), "r"(v) : "memory"); }
__device__ __forceinline__ void sts16(uint32_t a, uint16_t v) { asm volatile("st.shared.b16 [%0], %1;" ::"r"(a), "h"(v) : "memory"); }
__device__ __forceinline__ void sts64(uint32_t a, uint32_t x, uint32_t y) { asm volatile("st.shared.v2.b32 [%0], {%1,%2};" ::"r"(a), "r"(x), "r"(y) : "memory"); }
__device__ __forceinline__ void sts128(uint32_t a, uint32_t x, uint32_t y, uint32_t z, uint32_t w) {
    asm volatile("st.shared.v4.b32 [%0], {%1,%2,%3,%4};" ::"r"(a), "r"(x), "r"(y), "r"(z), "r"(w) : "memory");
}
__device__ __forceinline__ void sts128f(uint32_t a, const float (&c)[4]) {
    sts128(a, __float_as_uint(c[0]), __float_as_uint(c[1]), __float_as_uint(c[2]), __float_as_uint(c[3]));
}

__device__ __forceinline__ float sel4(const float (&c)[4], int t) { return (t & 2) ? ((t & 1) ? c[3] : c[2]) : ((t & 1) ? c[1] : c[0]); }

template <int LUT>
__device__ __forceinline__ uint32_t lop3(uint32_t a, uint32_t b, uint32_t c) {
    uint32_t d;
    asm("lop3.b32 %0, %1, %2, %3, %4;" : "=r"(d) : "r"(a), "r"(b), "r"(c), "n"(LUT));
    return d;
}
__device__ __forceinline__ uint32_t pin(uint32_t v) { return __shfl_xor_sync(0xffffffffu, v, 0); }
template <typename T>
__device__ __forceinline__ T* at(T* base, uint32_t bytes) { return (T*)((const char*)base + bytes); }

__device__ __forceinline__ uint32_t clock32(uint32_t dep) {
    uint32_t t;
    asm volatile("{\n.reg .pred p;\nsetp.eq.u32 p, %1, 0x9e3779b9;\n@p nanosleep.u32 1;\nmov.u32 %0, %clock;\n}" : "=r"(t) : "r"(dep) : "memory");
    return t;
}

__device__ __forceinline__ uint32_t nz(uint32_t v) { return v ? v : 0x80000000u; }
__device__ __forceinline__ void st1(uint32_t* p, uint32_t a) { asm volatile("st.relaxed.gpu.global.b32 [%0], %1;" ::"l"(p), "r"(a) : "memory"); }
__device__ __forceinline__ void st2(uint32_t* p, uint32_t a, uint32_t b) {
    asm volatile("st.relaxed.gpu.global.v2.b32 [%0], {%1,%2};" ::"l"(p), "r"(a), "r"(b) : "memory");
}
__device__ __forceinline__ void zero4(uint32_t* p) { asm volatile("st.relaxed.gpu.global.v4.b32 [%0], {%1,%1,%1,%1};" ::"l"(p), "r"(0) : "memory"); }
__device__ __forceinline__ void put1d(uint32_t* p, uint32_t a) { a = nz(a), st1(p, a), st1(p + 1024, a); }
__device__ __forceinline__ void put2d(uint32_t* p, uint32_t a, uint32_t b) { a = nz(a), b = nz(b), st2(p, a, b), st2(p + 1024, a, b); }
__device__ __forceinline__ uint32_t ld1(const uint32_t* p) {
    uint32_t v;
    asm volatile("ld.relaxed.gpu.global.b32 %0, [%1];" : "=r"(v) : "l"(p) : "memory");
    return v;
}
template <int N, int V>
__device__ __forceinline__ void fetch(const uint32_t* p, int stride, uint32_t (&a)[N * V]) {
#pragma unroll
    for (int i = 0; i < N; i++) {
        if (V == 1)
            asm volatile("{\n.reg .pred p;\nsetp.eq.u32 p, %0, 0;\n@p ld.relaxed.gpu.global.b32 %0, [%1];\n}"
                         : "+r"(a[i]) : "l"(p + i * stride) : "memory");
        if (V == 4)
            asm volatile("{\n.reg .pred p;\nsetp.eq.u32 p, %4, 0;\n@p ld.relaxed.gpu.global.v4.b32 {%0,%1,%2,%3}, [%5];\n}"
                         : "+r"(a[V * i]), "+r"(a[V * i + V / 4]), "+r"(a[V * i + V / 2]), "+r"(a[V * i + V - 1])
                         : "r"(min(min(a[V * i], a[V * i + V / 4]), min(a[V * i + V / 2], a[V * i + V - 1]))), "l"(p + i * stride) : "memory");
    }
}
template <int N>
__device__ __forceinline__ bool missing(const uint32_t (&a)[N]) {
    uint32_t lo = a[0];
#pragma unroll
    for (int i = 1; i < N; i++) lo = min(lo, a[i]);
    return __any_sync(0xffffffffu, lo == 0);
}
template <int N, int V>
__device__ __forceinline__ void get(const uint32_t* p, int stride, uint32_t (&a)[N * V]) {
    int it = 0;
    do fetch<N, V>(p, stride, a);
    while (missing(a) & (++it < SPIN_LIMIT));
}
__device__ __forceinline__ void cp16(uint32_t dst, const void* src) {
    asm volatile("cp.async.cg.shared.global [%0], [%1], 16;" ::"r"(dst), "l"(src) : "memory");
}

__device__ __forceinline__ uint32_t pack2(float lo, float hi) {
    uint32_t r;
    asm("cvt.rn.bf16x2.f32 %0, %1, %2;" : "=r"(r) : "f"(hi), "f"(lo));
    return r;
}
__device__ __forceinline__ float rbf(float x) { return __uint_as_float(pack2(0.f, x)); }
__device__ __forceinline__ float blo(uint32_t v) { return __uint_as_float(v << 16); }
__device__ __forceinline__ float bhi(uint32_t v) { return __uint_as_float(v & 0xffff0000u); }
__device__ __forceinline__ uint32_t badd2(uint32_t a, uint32_t b) { uint32_t r; asm("add.rn.bf16x2 %0, %1, %2;" : "=r"(r) : "r"(a), "r"(b)); return r; }
__device__ __forceinline__ uint32_t bsub2(uint32_t a, uint32_t b) { uint32_t r; asm("sub.rn.bf16x2 %0, %1, %2;" : "=r"(r) : "r"(a), "r"(b)); return r; }
__device__ __forceinline__ uint32_t bmul2(uint32_t a, uint32_t b) { uint32_t r; asm("mul.rn.bf16x2 %0, %1, %2;" : "=r"(r) : "r"(a), "r"(b)); return r; }
__device__ __forceinline__ float ex2(float x) { float r; asm("ex2.approx.ftz.f32 %0, %1;" : "=f"(r) : "f"(x)); return r; }
__device__ __forceinline__ float rcp(float x) { float r; asm("rcp.approx.ftz.f32 %0, %1;" : "=f"(r) : "f"(x)); return r; }
__device__ __forceinline__ float sqrt_f(float x) { float r; asm("sqrt.approx.ftz.f32 %0, %1;" : "=f"(r) : "f"(x)); return r; }
constexpr float LOG2E = 1.4426950408889634f;
constexpr uint32_t ONE2 = 0x3f803f80u;
__device__ __forceinline__ float sigmoid_f(float x) { return rcp(1.0f + ex2(-LOG2E * x)); }
__device__ __forceinline__ uint32_t silu2(uint32_t v) {
    const float a = blo(v), b = bhi(v);
    return pack2(a * sigmoid_f(a), b * sigmoid_f(b));
}
__device__ __forceinline__ float quad_sum(float v) {
    v += __shfl_xor_sync(0xffffffffu, v, 1);
    return v + __shfl_xor_sync(0xffffffffu, v, 2);
}
__device__ __forceinline__ void ln_partial(const uint32_t (&v)[8], uint32_t dst, bool writer) {
    float s0 = 0.f, s1 = 0.f;
#pragma unroll
    for (int i = 0; i < 8; i++) {
        s0 += blo(v[i]);
        s1 += bhi(v[i]);
    }
    const float mean = quad_sum(s0 + s1) * (1.0f / 64);
    s0 = s1 = 0.f;
#pragma unroll
    for (int i = 0; i < 8; i++) {
        const float a = blo(v[i]) - mean, b = bhi(v[i]) - mean;
        s0 = fmaf(a, a, s0);
        s1 = fmaf(b, b, s1);
    }
    s0 = quad_sum(s0 + s1);
    if (writer) sts64(dst, __float_as_uint(mean), __float_as_uint(s0));
}
__device__ __forceinline__ void ln_combine(uint32_t src, uint32_t& mean2, float& inv) {
    float m[10], q0 = 0.f, q1 = 0.f, s = 0.f;
#pragma unroll
    for (int i = 0; i < 5; i++) {
        const uint4 v = lds128(src + i * 16);
        m[2 * i] = __uint_as_float(v.x);
        m[2 * i + 1] = __uint_as_float(v.z);
        q0 += __uint_as_float(v.y);
        if (i < 4) q1 += __uint_as_float(v.w);
    }
    const float mean = (((m[0] + m[1]) + (m[2] + m[3])) + ((m[4] + m[5]) + (m[6] + m[7])) + m[8]) * (1.0f / 9);
#pragma unroll
    for (int i = 0; i < 9; i++) s = fmaf(m[i] - mean, m[i] - mean, s);
    const float var = fmaf(s, 64.f, q0 + q1) * (1.0f / DM);
    mean2 = pack2(mean, mean);
    inv = rcp(rbf(sqrt_f(rbf(rbf(var) + 1e-5f))));
}
__device__ __forceinline__ uint32_t modulate2(uint32_t x, uint32_t mean2, float inv, uint32_t shift, uint32_t onep) {
    const uint32_t d = bsub2(x, mean2);
    return badd2(bmul2(pack2(blo(d) * inv, bhi(d) * inv), onep), shift);
}
template <int N>
__device__ __forceinline__ void sum_frags(float (&c)[4], uint32_t addr, int stride) {
#pragma unroll
    for (int w = 0; w < N; w++) {
        const uint4 v = lds128(addr + w * stride);
        c[0] += __uint_as_float(v.x); c[1] += __uint_as_float(v.y);
        c[2] += __uint_as_float(v.z); c[3] += __uint_as_float(v.w);
    }
}

template <int ST>
__device__ __forceinline__ void project(uint32_t sm, const uint32_t* src, uint32_t* dst, uint32_t wa, uint32_t ws, uint32_t l16, int nsync, int warp, int lane) {
    constexpr int NW = ST ? 9 : 8, NI = ST ? 5 : 4, NP = NI - LATE_ITEMS;
    const uint32_t wbar = sm + OFF_BAR + (ST ? BAR_WD : BAR_WO) * 8, stage = sm + (ST ? OFF_WO : OFF_P) + l16;
    uint32_t w[NW][4] = {}, f[NW][4], b[4] = {};
    auto load_w = [&](int j) {
        const int i0 = j == 4 ? 8 : ST ? 2 * ((j + 3) & 3) : 2 * j;
        ldsm4t(w[i0], wa + i0 * ws);
        if (j < 4) ldsm4t(w[i0 + 1], wa + (i0 + 1) * ws);
    };
    bool have_w = false;
    int it = 0;
    do {
        if (!have_w && __all_sync(0xffffffffu, lane >= NP || mbar_test(wbar + lane * 8, 0))) {
            have_w = true;
#pragma unroll
            for (int j = 0; j < NP; j++) load_w(j);
        }
        if (warp >= NW) break;
        if (ST) fetch<4, 1>(src, 32, b);
        else fetch<1, 4>(src, 0, b);
    } while (missing(b) & (++it < SPIN_LIMIT));
    if (warp == 0) TSL(ST ? 24 : 21);
    if (warp < NW) sts128(stage + warp * 512, b[0], b[2], b[1], b[3]);
    bar_sync(ST ? 6 : 3, nsync);
#pragma unroll
    for (int i = 0; i < NW; i++) {
        const int k = ST && i < 8 ? (i + 6) & 7 : i;
        const uint4 v = lds128(stage + k * 512);
        f[k][0] = v.x, f[k][1] = v.y, f[k][2] = v.z, f[k][3] = v.w;
    }
    float acc[4][4] = {};
#pragma unroll
    for (int j = 0; j < NI; j++) {
        const int i0 = j == 4 ? 8 : ST ? 2 * ((j + 3) & 3) : 2 * j, n = j == 4 ? 1 : 2;
        if (j >= NP || !have_w) {
            mbar_wait(wbar + j * 8, 0);
            load_w(j);
        }
#pragma unroll
        for (int i = i0; i < i0 + n; i++) {
            mma(acc[2 * (i & 1)], f[i][0], f[i][1], f[i][2], f[i][3], w[i][0], w[i][1]);
            mma(acc[2 * (i & 1) + 1], f[i][0], f[i][1], f[i][2], f[i][3], w[i][2], w[i][3]);
        }
    }
    const float s0 = (acc[2][0] + acc[3][2]) + (acc[0][0] + acc[1][2]), s1 = (acc[2][1] + acc[3][3]) + (acc[0][1] + acc[1][3]);
    st2(dst, (__float_as_uint(s0) | 1) ^ ST, (__float_as_uint(s1) | 1) ^ ST);
}

template <int ST, typename F>
__device__ __forceinline__ uint32_t reduce16(const uint32_t* src, F arrived) {
    uint32_t a[32] = {}, bad[16], any;
    int it = 0;
#pragma unroll
    for (int i = 0; i < 16; i++) bad[i] = 1;
    do {
#pragma unroll
        for (int i = 0; i < 16; i++)
            asm volatile("{\n.reg .pred p;\nsetp.ne.u32 p, %2, 0;\n@p ld.relaxed.gpu.global.v2.b32 {%0,%1}, [%3];\n}"
                         : "+r"(a[2 * i]), "+r"(a[2 * i + 1]) : "r"(bad[i]), "l"(src + i * 64) : "memory");
#pragma unroll
        for (int i = 0; i < 16; i++) bad[i] = lop3<ST ? 0xa8 : 0x2a>(a[2 * i], a[2 * i + 1], 1);
        any = lop3<0xfe>(lop3<0xfe>(lop3<0xfe>(bad[0], bad[1], bad[2]), lop3<0xfe>(bad[3], bad[4], bad[5]), lop3<0xfe>(bad[6], bad[7], bad[8])),
                         lop3<0xfe>(lop3<0xfe>(bad[9], bad[10], bad[11]), lop3<0xfe>(bad[12], bad[13], bad[14]), bad[15]), 0);
    } while (__any_sync(0xffffffffu, any != 0) & (++it < SPIN_LIMIT));
    arrived();
    float f[8];
#pragma unroll
    for (int i = 0; i < 8; i++)
        f[i] = (__uint_as_float(a[i]) + __uint_as_float(a[i + 8])) + (__uint_as_float(a[i + 16]) + __uint_as_float(a[i + 24]));
    f[0] = (f[0] + f[2]) + (f[4] + f[6]);
    f[1] = (f[1] + f[3]) + (f[5] + f[7]);
    return pack2(f[0], f[1]);
}

__global__ void __launch_bounds__(NTHREADS, 1) fused_kernel(const Params P, const __grid_constant__ Maps T) {
    extern __shared__ __align__(1024) char smem_raw[];
    constexpr uint32_t sm = 1024;
    const int tid = threadIdx.x, lane = tid & 31;
    const int cta = blockIdx.x, grp = cta >> 3, sub = cta & 7;
    const uint32_t bars = sm + OFF_BAR;
    const int row0 = (sub * HKV + grp) * SK + (SK - WIN);
    if (tid >> 5 == 9) {
#pragma unroll
        for (int i = 0; i < PFK; i++) asm volatile("prefetch.global.L2 [%0];" ::"l"(P.k + (size_t)row0 * DH + (lane + i * 32) * 64) : "memory");
    }
    u64 pol;
    asm volatile("createpolicy.fractional.L2::evict_first.b64 %0, 1.0;" : "=l"(pol));
    if (tid == NCW * 32) {
        TS(0);
        const int n0 = cta < 90 ? 0 : 3;
#pragma unroll
        for (int i = 0; i < 6; i++) mbar_init(bars + i * 8, 1);
        asm volatile("fence.mbarrier_init.release.cluster;" ::: "memory");
#pragma unroll
        for (int i = 0; i < 3; i++) {
            mbar_expect(bars + (n0 + i) * 8, 12288);
            tma3d(sm + OFF_WM + (n0 + i) * 12288, &T.m[cta < 36 ? M_WA : cta < 90 ? M_WM : M_WQ], cta < 36 ? 16 * cta : 32 * cta,
                  i * 192, 0, bars + (n0 + i) * 8);
            TI(n0 + i);
        }
        TS(26);
    }
    if (tid == NCW * 32 + 32) {
#pragma unroll
        for (int i = 0; i < 4; i++) mbar_init(bars + (BAR_FULL + i) * 8, 1);
        asm volatile("fence.mbarrier_init.release.cluster;" ::: "memory");
#pragma unroll
        for (int t = 0; t < NK0; t++) {
            mbar_expect(bars + (BAR_FULL + t) * 8, TILE_BYTES);
            tma3d_hint(sm + OFF_RING + t * TILE_BYTES, &T.m[M_K], 0, row0 + t * 32, 0, bars + (BAR_FULL + t) * 8, pol);
            TI(6 + t);
        }
    }
    if (tid < 288 && cta < 90) {
#pragma unroll
        for (int i = 0; i < 2; i++) {
            const int row = (lane >> 3) + 4 * i, so = row * DM + (tid >> 5) * 64 + (lane & 7) * 8;
            const uint32_t d = sm + OFF_RED + (tid >> 5) * 2048 + row * 128 + (((lane & 7) ^ row) << 4);
            cp16(d, P.c + so);
            if (cta < 36) cp16(d + 1024, P.x + so);
        }
    }
    uint32_t* const g0 = P.scratch;
    const uint32_t epoch = ld1(g0 + G_EPOCH);
    const int warp = __shfl_sync(0xffffffffu, tid >> 5, 0);

    if (warp >= NCW) {
        const int pw = warp - NCW;
        bar_arrive(1, (NCW + 1) * 32);
        if (pw && lane < M_WQ) asm volatile("prefetch.tensormap [%0];" ::"l"(&T.m[M_WQ - lane]) : "memory");
        if (tid == NCW * 32) sts32(sm + OFF_WIN, 0);
        __syncwarp();
        bar_sync(15, NTHREADS);
        if (lane == 0) {
            if (pw == 0 && cta < 90) {
#pragma unroll 1
                for (int n = 3; n < 6; n++) {
                    mbar_expect(bars + n * 8, 12288);
                    mbar_wait(bars + (n - 3) * 8, 0);
                    tma3d(sm + OFF_WM + n * 12288, &T.m[M_WQ], 32 * cta, (n - 3) * 192, 0, bars + n * 8);
                    TI(n);
                }
            }
#pragma unroll 1
            for (int t = NK0 + (1 - pw) * NK1; t < NK0 + NK1 + 3 * (1 - pw); t++) {
                mbar_expect(bars + (BAR_FULL + t) * 8, TILE_BYTES);
                mbar_wait(bars + (t + (pw ? BAR_FULL - NK1 : 3 - NK0 - NK1)) * 8, 0);
                tma3d_hint(sm + OFF_RING + t * TILE_BYTES, &T.m[M_K], 0, row0 + t * 32, 0, bars + (BAR_FULL + t) * 8, pol);
                TI(6 + t);
            }
            if (pw == 0) {
                auto on_time = [&](int due, uint32_t bar, uint32_t parity) {
                    uint32_t origin;
                    do origin = lds32(sm + OFF_WIN);
                    while (origin && (int)(clock32(0) - origin - due) < 0 && !mbar_test(bar, parity));
                };
#pragma unroll 1
                for (int t = NK0 + NK1 + 3; t < 2 * NT; t++) {
                    if (t == 14 && cta < 90) mbar_wait(bars + BAR_WMF * 8, 0);
                    if (t == 15) TS(30);
                    const uint32_t fb = bars + (BAR_FULL + (t & 15)) * 8;
                    const int hi = t - (lds32(sm + OFF_WIN) ? W_HI : W_0), lo = t - W_LO;
                    mbar_wait(fb + (BAR_EMPTY - BAR_FULL) * 8, (~t >> 4) & 1);
                    mbar_expect(fb, TILE_BYTES);
                    mbar_wait(bars + (BAR_FULL + (hi & 15)) * 8, (hi >> 4) & 1);
                    on_time(t * TAU - L_KV, bars + (BAR_FULL + (lo & 15)) * 8, (lo >> 4) & 1);
                    tma3d_hint(sm + OFF_RING + (t & 15) * TILE_BYTES, &T.m[t >> 6], 0, row0 + (t & (NT - 1)) * 32, 0, fb, pol);
                    TI(6 + t);
                    if (t == T_CLEAR) mbar_arrive(bars + (BAR_SYNC + 1) * 8);
                }
                mbar_wait(bars + BAR_SYNC * 8, 0);
                auto window = [&](int b, int lead) {
                    mbar_wait(bars + (b - W_HI) * 8, b - W_HI < BAR_WO);
                    on_time((2 * NT - 1) * TAU + (b - BAR_WO + 1) * TAU_W - lead, bars + (b - W_LO) * 8, b - W_LO < BAR_WO);
                };
#pragma unroll 1
                for (int i = 0; i < 4; i++) {
                    window(BAR_WO + i, L_WO);
                    tma3d(sm + OFF_WO + i * 8192, &T.m[M_OD], 64 * sub, grp * 256 + i * 64, P.zo, bars + (BAR_WO + i) * 8);
                    tma3d(sm + OFF_OX + i * 1024, &T.m[M_OX], 512 + 8 * sub, grp * 256 + i * 64, P.zo, bars + (BAR_WO + i) * 8);
                    TI(134 + i);
                }
                TS(28);
#pragma unroll 1
                for (int i = 0; i < 9; i++) {
                    mbar_wait(bars + (BAR_EMPTY + i) * 8, 1);
                    window(BAR_GU + i, L_GU);
                    tma3d(sm + OFF_GU + i * 8192, &T.m[M_GU], grp * 288 + 32 * sub, i * 64, 0, bars + (BAR_GU + i) * 8);
                    if (sub < 4) tma3d(sm + OFF_GX + i * 2048, &T.m[M_GX], grp * 288 + 256 + 8 * sub, i * 64, 0, bars + (BAR_GU + i) * 8);
                    TI(138 + i);
                }
                TS(29);
#pragma unroll 1
                for (int i = 0; i < 5; i++) {
                    const int blk = i < 4 ? (i + 3) & 3 : 4, r = min(blk * 64, 224);
                    mbar_wait(bars + (BAR_EMPTY + 9 + blk) * 8, 1);
                    window(BAR_WD + i, L_WD + (i == 4 ? L_LAST : 0));
                    tma3d(sm + OFF_WD + r * 128, &T.m[M_OD], 64 * sub, grp * 288 + r, P.zo ^ 1, bars + (BAR_WD + i) * 8);
                    tma3d(sm + OFF_DX + r * 16, &T.m[M_OX], 512 + 8 * sub, grp * 288 + r, P.zo ^ 1, bars + (BAR_WD + i) * 8);
                    TI(147 + i);
                }
                if (cta < 72) {
                    mbar_wait(bars + (BAR_EMPTY + 14) * 8, 1);
                    mbar_wait(bars + (BAR_EMPTY + 15) * 8, 1);
                    mbar_expect(bars + BAR_GB * 8, 9216);
                    window(BAR_WD + 5, L_GB);
#pragma unroll
                    for (int i = 0; i < 3; i++) tma3d(sm + OFF_GB + i * 3072, &T.m[M_GB], 5 * DM + 8 * cta, i * 192, 0, bars + BAR_GB * 8);
                }
            } else {
#pragma unroll 1
                for (int i = BAR_WO; i < BAR_WD + 5; i++) mbar_expect(bars + i * 8, i < BAR_GU || i >= BAR_WD ? 9216 : sub < 4 ? 10240 : 8192);
                mbar_arrive(bars + BAR_SYNC * 8);
                uint32_t* const cnt = g0 + (epoch & 1) * G_SET + G_CNT;
                uint32_t origin = 0;
#pragma unroll 1
                for (int t = cta & 3; t < 144; t += 4) {
                    const uint32_t bar = bars + (BAR_FULL + (t < 2 * NT ? t & 15 : t - 112)) * 8;
                    mbar_wait(bar, (t >> 4) & 1);
                    if (t < 2 * NT) mbar_arrive(bar + (BAR_EMPTY - BAR_FULL) * 8);
                    const uint32_t t0 = clock32(0);
                    const int c = (int)atomicAdd(cnt, 1u) - 16;
                    const uint32_t o = t0 + ((clock32(c) - t0) >> 1) - ((c * TAU + max(c - 32 * (2 * NT - 1), 0) * (TAU_W - TAU)) >> 5);
                    if (t < T_PACE) continue;
                    origin = (origin ? origin + ((int)(o - origin) >> SMOOTH) : o) | 1;
                    sts32(sm + OFF_WIN, origin);
                }
            }
        }
        return;
    }

    if (lane == 0) {
#pragma unroll
        for (int i = 0; i < 6; i++) {
            const int b = 10 + warp * 6 + i;
            mbar_init(bars + b * 8, b >= BAR_EMPTY && b < BAR_EMPTY + 16 && ((b ^ cta) & 3) == 0 ? 2 : 1);
        }
        asm volatile("fence.mbarrier_init.release.cluster;" ::: "memory");
    }
    __syncwarp();
    if (warp < 9) bar_arrive(15, NTHREADS);
    const int g = lane >> 2, t4 = lane & 3;
    uint32_t* const gs = g0 + (epoch & 1) * G_SET;

    uint32_t sc[8] = {};
    if (warp < 9) {
        const int off_h = (cta < 36 ? dual(D_H + 2 * cta * 32) : G_M + 4 * (cta - 36) * 32) + tid;
        const int off_h2 = off_h + (cta < 36 ? 1024 : 64);
        const int off_q = dual(D_Q + g * (HQ * 64) + cta * 16) + warp * 8 + t4 * 2;
        uint32_t bf[8] = {}, xp = 0, mean2 = 0;
        float inv = 0.f;
        if (cta < 36) xp = __ldg(reinterpret_cast<const uint32_t*>(P.x) + g * (DM / 2) + 8 * cta + 4 * (warp & 1) + t4);
        if (warp < 2) {
            st2(gs + off_q, 0, 0), st2(gs + off_q + 1024, 0, 0);
            if (cta < 36) st1(gs + off_h, 0), st1(gs + off_h2, 0);
        }
        if (cta < 90) {
            asm volatile("cp.async.wait_all;" ::: "memory");
            __syncwarp();
            const uint32_t fa = sm + OFF_RED + warp * 2048 + (lane & 7) * 128 + (((lane >> 3) ^ (lane & 7)) << 4);
            ldsm4(reinterpret_cast<uint32_t(&)[4]>(bf[0]), fa);
            ldsm4(reinterpret_cast<uint32_t(&)[4]>(bf[4]), fa ^ 64);
            if (cta < 36) {
                uint32_t xv[8];
                ldsm4(reinterpret_cast<uint32_t(&)[4]>(xv[0]), fa + 1024);
                ldsm4(reinterpret_cast<uint32_t(&)[4]>(xv[4]), (fa ^ 64) + 1024);
                ln_partial(xv, sm + OFF_ST + g * 80 + warp * 8, t4 == 0);
            }
#pragma unroll
            for (int i = 0; i < 8; i++) sc[i] = bf[i] = silu2(bf[i]);
        }
        if (warp == 0) TSL(18);
        bar_sync(1, (NCW + 1) * 32);
        if (cta < 36 && warp < 2) ln_combine(sm + OFF_ST + g * 80, mean2, inv);
        const int r = warp * 64 + (lane >> 4) * 8 + (lane & 7), hi8 = (lane >> 3) & 1, box = warp / 3;
#pragma unroll 1
        for (int pass = cta < 90 ? 0 : 1; pass < 2; pass++) {
            const bool pa = pass == 0 && cta < 36;
            const uint32_t ab = sm + OFF_WM + pass * 36864 +
                                (pa ? (box + hi8) * 6144 + r * 32 + ((lane & 4) << 2) : r * 64 + (((2 * hi8) ^ ((r >> 1) & 3)) << 4));
            const uint32_t as = pa ? 512 : 1024, red = sm + OFF_RED + pass * 9216;
            mbar_wait(bars + (pass * 3 + box) * 8, 0);
            if (warp == 8) TSL(pass ? 31 : 19);
            uint32_t a[4][2][4];
#pragma unroll
            for (int i = 0; i < 4; i++) {
                ldsm4t(a[i][0], ab + i * as);
                ldsm4t(a[i][1], (ab ^ 16) + i * as);
            }
            if (pass) {
                bar_sync(8, NCW * 32);
#pragma unroll
                for (int i = 0; i < 8; i++) bf[i] = 0;
                const uint32_t* const src_h = gs + near(D_H + warp * 256, lds32(sm + OFF_WIN + 4)) + lane;
                get<1, 1>(src_h, 0, reinterpret_cast<uint32_t(&)[1]>(bf[0]));
                get<8, 1>(src_h, 32, bf);
                if (warp == 0) TSL(3);
            }
            float acc[2][4] = {};
#pragma unroll
            for (int i = 0; i < 4; i++)
#pragma unroll
                for (int m = 0; m < 2; m++) mma(acc[m], a[i][m][0], a[i][m][1], a[i][m][2], a[i][m][3], bf[2 * i], bf[2 * i + 1]);
            sts128f(red + tid * 16, acc[0]);
            sts128f(red + 4608 + tid * 16, acc[1]);
            bar_sync(3, 288);
            if (warp < 2) {
                float c[4] = {};
                sum_frags<9>(c, red + warp * 4608 + lane * 16, 512);
                uint32_t lo = movm(pack2(c[0], c[1])), hi = movm(pack2(c[2], c[3]));
                if (pass) {
                    put2d(gs + off_q, lo, hi);
                    if (warp == 0) TSL(4);
                } else {
                    const uint32_t hi1 = badd2(hi, ONE2);
                    if (pa) hi = lo = modulate2(xp, mean2, inv, lo, hi1);
                    if (cta >= 72) lo = badd2(lo, ONE2), hi = hi1;
                    st1(gs + off_h, nz(lo));
                    st1(gs + off_h2, nz(hi));
                    if (warp == 0 && pa) TSL(2);
                }
            } else if (tid == 64 && pass == 0) {
                mbar_arrive(bars + BAR_WMF * 8);
            }
        }
    } else {
        if ((uint32_t)__cvta_generic_to_shared(smem_raw) != sm) __trap();
        uint32_t* const ping = g0 + dual(D_PING) + cta * 8;
        if (lane < 16) st1(ping + (lane >> 3) * 1024 + (lane & 7), 0);
        bar_sync(15, NTHREADS);
        uint32_t best[2] = {~0u, ~0u}, v = 0;
#pragma unroll 1
        for (int part = 0; part < 2; part++) {
            if (lane == 0) {
#pragma unroll 1
                for (int r = part ? NPING1 : NPING0; r > 0; r--) {
#pragma unroll
                    for (int k = 0; k < 2; k++) {
                        const uint32_t t0 = clock32(v);
                        v = atomicExch(ping + k * 1024, t0);
                        best[k] = min(best[k], clock32(v) - t0);
                    }
                }
                sts32(sm + OFF_WIN + 4 + 4 * part, ((best[1] < best[0]) ^ __popc(D_PING & 0x16400)) & 1);
            }
            __syncwarp();
            if (part) break;
            TSL(20);
            bar_arrive(8, NCW * 32);
            mbar_wait(bars + 5 * 8, 0);
            uint32_t a[4] = {};
            get<1, 4>(gs + near(D_Q + (sub * HQ + 2 * grp) * 64, lds32(sm + OFF_WIN + 4)) + lane * 4, 0, a);
            sts128(sm + OFF_QS + lane * 16, a[0], a[1], a[2], a[3]);
            __syncwarp();
            TSL(5);
            bar_arrive(4, 288);
        }
#pragma unroll
        for (int i = lane; i < 72; i += 32) cp16(sm + OFF_WR + i * 16, P.wr + i * 8);
        __syncwarp();
        if (cta < 72 && lane < 16) st1(g0 + ((epoch ^ lane >> 3) & 1) * G_SET + G_SIDE + cta * 8 + (lane & 7), lane < 8 ? 1 + lds32(sm + OFF_WIN + 8) : 0);
        asm volatile("cp.async.wait_all;" ::: "memory");
        __syncwarp();
        bar_arrive(2, NCW * 32);
        if (cta == 0 && lane == 0) st1(g0 + (~epoch & 1) * G_SET + G_CNT, 0);
        mbar_wait(bars + (BAR_SYNC + 1) * 8, 0);
#pragma unroll 1
        for (int c = 0; c < 4; c++) {
            uint32_t* const pg = g0 + (c >> 1) * G_SET + (c & 1) * 1024;
            zero4(pg + dual(D_O + cta * 128) + lane * 4);
            zero4(pg + dual(D_ACT + (grp * 36 + 4 * sub) * 32) + lane * 4);
            if (lane < 8 ? sub < 4 : lane < 16 && cta < 72)
                zero4(pg + dual(lane < 8 ? D_ACT + (grp * 36 + 32 + sub) * 32 : D_X1 + cta * 32) + (lane & 7) * 4);
        }
#pragma unroll 1
        for (int u = 0; u < 9; u++) zero4(g0 + dual(d_part(u < 8 ? 8 * sub + u : 64 + sub)) + (lane >> 4) * 1024 + grp * 64 + (lane & 15) * 4);
        {
            uint32_t* const nx = g0 + (~epoch & 1) * G_SET;
            uint32_t* const q = nx + dual(D_Q + g * (HQ * 64) + cta * 16) + t4 * 4;
            zero4(q), zero4(q + 1024);
            if (cta < 90) zero4(nx + (cta < 36 ? dual(D_H + 2 * cta * 32) + (lane >> 4) * (1024 - 64) : G_M + 4 * (cta - 36) * 32) + lane * 4);
        }
        if (cta >= 72) {
            bar_arrive(5, NCW * 32);
            return;
        }
        const uint32_t io = pin(4 * (g * (DM / 2) + 4 * cta + t4));
        uint32_t x = __ldg(at(reinterpret_cast<const uint32_t*>(P.x), io)), ga[1] = {};
        get<1, 1>(gs + G_M + cta * 32 + lane, 0, ga);
        const uint32_t src_p = pin(4 * (near(d_part(cta), lds32(sm + OFF_WIN + 8)) + lane * 2));
        const uint32_t dst_x = pin(4 * ((epoch & 1) * G_SET + dual(D_X1 + cta * 32) + lane));
        bar_sync(5, NCW * 32);
        x = badd2(x, bmul2(ga[0], reduce16<0>(at(g0, src_p), [] {})));
        put1d(at(g0, dst_x), x);
        TSL(10);
        bar_sync(6, NCW * 32);
        const uint4 r0 = lds128(sm + OFF_RT + g * 48), r1 = lds128(sm + OFF_RT + g * 48 + 16);
        float r = __uint_as_float(lds32(sm + OFF_RT + g * 48 + 32));
        r += ((__uint_as_float(r0.x) + __uint_as_float(r0.y)) + (__uint_as_float(r0.z) + __uint_as_float(r0.w))) +
             ((__uint_as_float(r1.x) + __uint_as_float(r1.y)) + (__uint_as_float(r1.z) + __uint_as_float(r1.w)));
        r = sigmoid_f(rbf(r));
        const uint32_t h = lds32(sm + OFF_RED + (cta >> 2) * 512 + lane * 16 + (cta & 3) * 4), rs = pack2(r, r);
        uint32_t gb;
        const uint32_t y = reduce16<1>(at(g0, src_p), [&] {
            TSL(23);
            bar_sync(9, 64);
            gb = lds32(sm + OFF_QS + lane * 4);
        });
        *at(reinterpret_cast<uint32_t*>(P.out), io) = badd2(x, bmul2(gb, badd2(h, bmul2(y, rs))));
        if (cta == 0 && lane == 0) g0[G_EPOCH] = epoch + 1;
        TSL(15);
        return;
    }

    const uint32_t tile = sm + OFF_RING + warp * TILE_BYTES;
    const uint32_t fullb = bars + (BAR_FULL + warp) * 8;
    const uint32_t pw = sm + OFF_P + warp * (2 * P_PITCH);
    if (warp < 8) {
        {
            uint32_t q0[8], q1[8];
            bar_sync(4, 288);
#pragma unroll
            for (int i = 0; i < 8; i++) {
                const float2 v = lds64f(sm + OFF_QS + (g & 1) * 256 + i * 32 + t4 * 8);
                q0[i] = __float_as_uint(v.x), q1[i] = __float_as_uint(v.y);
            }
            uint32_t sp = pw + (t4 & 1) * P_PITCH + ((t4 >> 1) * 8 + g) * 2;
#pragma unroll 1
            for (int it = 0; it < 8; it++, sp += 64) {
                const uint32_t ab = tile + (it & 1) * (8 * TILE_BYTES) + (lane & 15) * 128 + (((lane >> 4) ^ (lane & 7)) << 4);
                mbar_wait(fullb + (it & 1) * 64, (it >> 1) & 1);
                float acc[2][2][4] = {};
#pragma unroll
                for (int ks = 0; ks < 8; ks++)
#pragma unroll
                    for (int m = 0; m < 2; m++) {
                        uint32_t a[4];
                        ldsm4(a, (ab ^ ((ks & 3) << 5)) + (ks >> 2) * 4096 + m * 2048);
                        mma(acc[m][ks & 1], a[0], a[1], a[2], a[3], (ks & 1) ? q1[ks - 1] : q0[ks], (ks & 1) ? q1[ks] : q0[ks + 1]);
                    }
                __syncwarp();
                if (lane == 0) mbar_arrive(fullb + (it & 1) * 64 + (BAR_EMPTY - BAR_FULL) * 8);
#pragma unroll
                for (int m = 0; m < 2; m++) {
                    const float s = sel4(acc[m][0], t4) + sel4(acc[m][1], t4);
                    sts16(sp + m * 32, (uint16_t)pack2(rbf(s) * 0.08838834764831845f, 0.f));
                }
            }
        }
        __syncwarp();
        if (warp == 7) TSL(6);
        const uint32_t pa = pw + (lane >> 4) * P_PITCH + (lane & 15) * 32;
        const uint32_t sa = sm + OFF_SM + (lane >> 4) * 64;
        const uint4 v0 = lds128(pa), v1 = lds128(pa + 16);
        const uint32_t sv[8] = {v0.x, v0.y, v0.z, v0.w, v1.x, v1.y, v1.z, v1.w};
        float e[16];
        float m = -INFINITY;
#pragma unroll
        for (int i = 0; i < 8; i++) {
            e[2 * i] = blo(sv[i]);
            e[2 * i + 1] = bhi(sv[i]);
            m = fmaxf(m, fmaxf(e[2 * i], e[2 * i + 1]));
        }
#pragma unroll
        for (int o = 8; o; o >>= 1) m = fmaxf(m, __shfl_xor_sync(0xffffffffu, m, o));
        float l = 0.f;
#pragma unroll
        for (int i = 0; i < 16; i++) {
            e[i] = ex2((e[i] - m) * LOG2E);
            l += e[i];
        }
#pragma unroll
        for (int o = 8; o; o >>= 1) l += __shfl_xor_sync(0xffffffffu, l, o);
        if ((lane & 15) == 0) sts64(sa + warp * 8, __float_as_uint(m), __float_as_uint(l));
        bar_sync(2, NCW * 32);
        const float2 v = lds64f(sa + (lane & 7) * 8);
        float M = v.x;
#pragma unroll
        for (int o = 4; o; o >>= 1) M = fmaxf(M, __shfl_xor_sync(0xffffffffu, M, o));
        float L = v.y * ex2((v.x - M) * LOG2E);
#pragma unroll
        for (int o = 4; o; o >>= 1) L += __shfl_xor_sync(0xffffffffu, L, o);
        const float sc = ex2((m - M) * LOG2E) * rcp(L);
        sts128(pa, pack2(e[0] * sc, e[1] * sc), pack2(e[2] * sc, e[3] * sc), pack2(e[4] * sc, e[5] * sc), pack2(e[6] * sc, e[7] * sc));
        sts128(pa + 16, pack2(e[8] * sc, e[9] * sc), pack2(e[10] * sc, e[11] * sc), pack2(e[12] * sc, e[13] * sc), pack2(e[14] * sc, e[15] * sc));
        __syncwarp();
    } else {
        bar_sync(2, NCW * 32);
    }

    uint32_t sh[8] = {}, op[8] = {};
    {
        const uint32_t* const src_m = gs + G_M + (72 + warp * 8) * 32 + lane;
        fetch<8, 1>(src_m + 72 * 32, 32, op);
        get<8, 1>(src_m, 32, sh);
        get<8, 1>(src_m + 72 * 32, 32, op);
    }
    const int side = lds32(sm + OFF_WIN + 8), set = (epoch & 1) * G_SET, rr = (lane >> 4) * 8 + (lane & 7);
    const uint32_t dst_o = pin(4 * (set + dual(D_O + cta * 128) + (tid & 0x70) + (tid & 3) * 4 + ((tid >> 2) & 3)));
    const uint32_t src_o = pin(4 * (set + near(D_O + grp * 1024, side) + g * 128 + warp * 16 + t4 * 4));
    const int unit = warp < 8 ? 8 * sub + warp : 64 + sub;
    uint32_t rside[1] = {};
    get<1, 1>(gs + G_SIDE + unit * 8, 0, rside);
    const uint32_t dst_p = pin(4 * (near(d_part(unit), rside[0] - 1) + grp * 64 + lane * 2));
    const uint32_t src_x = pin(4 * (set + near(D_X1 + warp * 256, side) + lane));
    const uint32_t dst_a = pin(4 * (set + dual(D_ACT + (grp * 36 + (warp < 4 ? 4 * sub + warp : 32 + sub)) * 32) + lane));
    const uint32_t src_a = pin(4 * (set + near(D_ACT + (grp * 36 + 4 * warp) * 32, side) + lane));
    const uint32_t rowoff = pin(warp < 8 ? lane * 128 + ((warp ^ (lane & 7)) << 4) : lane * 16), rowstep = warp < 8 ? 4096 : 512;
    const uint32_t l16 = pin(lane * 16);
    const uint32_t ored = pin((warp * 1088 + (t4 & 1) * 576 + ((t4 >> 1) * 8 + g) * 4) | ((tid >> 6) * 64 + tid * 8) << 16);

    if (warp < 8) {
        float acc[8][4] = {};
        uint32_t pp = pw + (lane & 1) * P_PITCH + (lane >> 3) * 16;
#pragma unroll 1
        for (int it = 0; it < 8; it++, pp += 64) {
            const uint32_t ab = tile + (it & 1) * (8 * TILE_BYTES) + ((lane & 7) + (lane >> 4) * 8) * 128 + ((((lane >> 3) & 1) ^ (lane & 7)) << 4);
            uint32_t pb[4];
            ldsm4(pb, pp);
            mbar_wait(fullb + (it & 1) * 64, (it >> 1) & 1);
#pragma unroll
            for (int ks = 0; ks < 2; ks++)
#pragma unroll
                for (int m = 0; m < 8; m++) {
                    uint32_t a[4];
                    ldsm4t(a, (ab ^ ((m & 3) << 5)) + (m >> 2) * 4096 + ks * 2048);
                    mma(acc[m], a[0], a[1], a[2], a[3], pb[2 * ks], pb[2 * ks + 1]);
                }
            __syncwarp();
            if (lane == 0) mbar_arrive(fullb + (it & 1) * 64 + (BAR_EMPTY - BAR_FULL) * 8);
        }
        if (warp == 7) TSL(7);
        const uint32_t ra = sm + OFF_ORED + (ored & 0xffff);
#pragma unroll
        for (int m = 0; m < 8; m++) sts32(ra + m * 64, __float_as_uint(sel4(acc[m], t4)));
    }
    bar_sync(5, NCW * 32);
    if (warp < 4) {
        float s[2][2] = {};
#pragma unroll
        for (int w = 0; w < 8; w++) {
            const float2 v = lds64f(sm + OFF_ORED + w * 1088 + (ored >> 16));
            s[w & 1][0] += v.x;
            s[w & 1][1] += v.y;
        }
        put1d(at(g0, dst_o), pack2(s[0][0] + s[1][0], s[0][1] + s[1][1]));
        if (warp == 0) TSL(8);
    }

    project<0>(sm, at(g0, src_o), at(g0, dst_p), sm + (warp < 8 ? OFF_WO : OFF_OX) + rowoff, rowstep, l16, 288, warp, lane);
    if (warp == 0) TSL(9);

    {
        uint32_t h[8] = {}, mean2;
        float inv;
        get<1, 1>(at(g0, src_x), 0, reinterpret_cast<uint32_t(&)[1]>(h[0]));
        get<8, 1>(at(g0, src_x), 32, h);
        if (warp == 0) TSL(11);
        ln_partial(h, sm + OFF_ST + g * 80 + warp * 8, t4 == 0);
        bar_sync(3, 288);
        ln_combine(sm + OFF_ST + g * 80, mean2, inv);
#pragma unroll
        for (int i = 0; i < 8; i++) h[i] = modulate2(h[i], mean2, inv, sh[i], op[i]);
        sts128(sm + OFF_RED + warp * 1024 + lane * 16, h[0], h[1], h[2], h[3]);
        sts128(sm + OFF_RED + warp * 1024 + 512 + lane * 16, h[4], h[5], h[6], h[7]);
        if (warp == 0) TSL(12);
        if (cta < 72) {
            float r = 0.f;
#pragma unroll
            for (int i = 0; i < 8; i++) {
                const uint32_t wr = lds32(sm + OFF_WR + (warp * 32 + i * 4 + t4) * 4);
                r = fmaf(blo(h[i]), blo(wr), fmaf(bhi(h[i]), bhi(wr), r));
            }
            r = quad_sum(r);
            if (t4 == 0) sts32(sm + OFF_RT + g * 48 + warp * 4, __float_as_uint(r));
        }
    }
    bar_sync(3, 288);

    if (warp < (sub < 4 ? 5 : 4)) {
        const int pl = ((lane >> 3) & 1) ^ P.zg;
        const uint32_t ks = warp < 4 ? 1024 : 256;
        uint32_t aa = sm + (warp < 4 ? OFF_GU + rr * 64 + (((lane & 6) << 3) ^ (warp << 4)) : OFF_GX + rr * 16) + pl * 4 * ks;
        float acc[2][4] = {};
        constexpr int UN = GU_UNROLL;
#pragma unroll UN
        for (int i = 0; i < 9; i++, aa += 8 * ks) {
            const uint4 b0 = lds128(sm + OFF_RED + i * 1024 + lane * 16), b1 = lds128(sm + OFF_RED + i * 1024 + 512 + lane * 16);
            uint32_t a[4][4];
            mbar_wait(bars + (BAR_GU + i) * 8, 0);
#pragma unroll
            for (int k = 0; k < 4; k++) ldsm4t(a[k], aa + k * ks);
            mma(acc[0], a[0][0], a[0][1], a[0][2], a[0][3], b0.x, b0.y);
            mma(acc[1], a[1][0], a[1][1], a[1][2], a[1][3], b0.z, b0.w);
            mma(acc[0], a[2][0], a[2][1], a[2][2], a[2][3], b1.x, b1.y);
            mma(acc[1], a[3][0], a[3][1], a[3][2], a[3][3], b1.z, b1.w);
        }
        if (warp == 1) TSL(17);
        const uint32_t gate = pack2(acc[0][0] + acc[1][0], acc[0][1] + acc[1][1]), up = pack2(acc[0][2] + acc[1][2], acc[0][3] + acc[1][3]);
        put1d(at(g0, dst_a), movm(bmul2(silu2(gate), up)));
        if (warp == 1) TSL(13);
    } else {
        mbar_wait(bars + (BAR_GU + 8) * 8, 0);
    }

    project<1>(sm, at(g0, src_a), at(g0, dst_p), sm + (warp < 8 ? OFF_WD : OFF_DX) + rowoff, rowstep, l16, cta < 72 ? 320 : 288, warp, lane);
    if (warp == 0) TSL(14);
    if (warp == 8) TSL(27);

    if (cta < 72) {
        const uint32_t ga = sm + OFF_GB + warp * 1024 + ((lane >> 3) & 1) * 256 + (lane >> 4) * 128 + (lane & 7) * 16;
        float acc[2][4] = {};
        mbar_wait(bars + BAR_GB * 8, 0);
        if (warp == 0) TSL(22);
#pragma unroll
        for (int i = 0; i < 2; i++) {
            uint32_t w[4];
            ldsm4t(w, ga + i * 512);
            mma(acc[0], w[0], w[1], w[2], w[3], sc[4 * i], sc[4 * i + 1]);
            mma(acc[1], w[0], w[1], w[2], w[3], sc[4 * i + 2], sc[4 * i + 3]);
        }
        sts64(sm + OFF_RED + 9216 + tid * 8, __float_as_uint(acc[0][0] + acc[1][2]), __float_as_uint(acc[0][1] + acc[1][3]));
        if (warp) {
            bar_arrive(7, 288);
        } else {
            bar_sync(7, 288);
            float s[2][2] = {};
#pragma unroll
            for (int w = 0; w < 9; w++) {
                const float2 v = lds64f(sm + OFF_RED + 9216 + tid * 8 + w * 256);
                s[w & 1][0] += v.x;
                s[w & 1][1] += v.y;
            }
            sts32(sm + OFF_QS + lane * 4, movm(pack2(s[0][0] + s[1][0], s[0][1] + s[1][1])));
            __syncwarp();
            bar_arrive(9, 64);
            TSL(25);
        }
    }
}

typedef CUresult (*EncodeFn)(CUtensorMap*, CUtensorMapDataType, cuuint32_t, void*, const cuuint64_t*, const cuuint64_t*,
                             const cuuint32_t*, const cuuint32_t*, CUtensorMapInterleave, CUtensorMapSwizzle,
                             CUtensorMapL2promotion, CUtensorMapFloatOOBfill);

void make_map(EncodeFn enc, CUtensorMap* m, void* p, int cols, int rows, int pitch, int bc, int br, int bp, int planes, size_t pstride,
              CUtensorMapSwizzle sw, int promo) {
    cuuint64_t dims[3] = {(cuuint64_t)cols, (cuuint64_t)rows, (cuuint64_t)planes};
    cuuint64_t strides[2] = {(cuuint64_t)pitch * 2, (cuuint64_t)pstride};
    cuuint32_t box[3] = {(cuuint32_t)bc, (cuuint32_t)br, (cuuint32_t)bp};
    cuuint32_t es[3] = {1, 1, 1};
    enc(m, CU_TENSOR_MAP_DATA_TYPE_BFLOAT16, 3, p, dims, strides, box, es, CU_TENSOR_MAP_INTERLEAVE_NONE, sw,
        (CUtensorMapL2promotion)promo, CU_TENSOR_MAP_FLOAT_OOB_FILL_NONE);
}

}

extern "C" void kernel_launch(void* const* d_in, const int* in_sizes, int n_in, void* d_out, int out_size) {
    static EncodeFn enc = nullptr;
    static uint32_t* scratch = nullptr;
    if (!enc) {
        void* fn = nullptr;
        cudaDriverEntryPointQueryResult st;
        cudaGetDriverEntryPoint("cuTensorMapEncodeTiled", &fn, cudaEnableDefault, &st);
        enc = (EncodeFn)fn;
        cudaGetSymbolAddress(&fn, g_scratch);
        scratch = (uint32_t*)(((uintptr_t)fn + 8 * G_SET - 1) & ~(uintptr_t)(8 * G_SET - 1));
        cudaFuncSetAttribute(fused_kernel, cudaFuncAttributeMaxDynamicSharedMemorySize, SMEM_BYTES);
    }
    Params P;
    Maps T;
    const CUtensorMapSwizzle none = CU_TENSOR_MAP_SWIZZLE_NONE;
    const int PROMO_W = CU_TENSOR_MAP_L2_PROMOTION_L2_128B, PROMO_KV = CU_TENSOR_MAP_L2_PROMOTION_L2_256B;
    make_map(enc, &T.m[M_K], d_in[1], 64, NB * HKV * SK, DH, 64, 32, 2, 2, 128, CU_TENSOR_MAP_SWIZZLE_128B, PROMO_KV);
    make_map(enc, &T.m[M_V], d_in[2], 64, NB * HKV * SK, DH, 64, 32, 2, 2, 128, CU_TENSOR_MAP_SWIZZLE_128B, PROMO_KV);
    make_map(enc, &T.m[M_WQ], d_in[3], HQ * DH, DM, HQ * DH, 32, 192, 1, 1, 16, CU_TENSOR_MAP_SWIZZLE_64B, PROMO_W);
    make_map(enc, &T.m[M_WM], d_in[11], 6 * DM, DM, 6 * DM, 32, 192, 1, 1, 16, CU_TENSOR_MAP_SWIZZLE_64B, PROMO_W);
    make_map(enc, &T.m[M_WA], d_in[11], DM, DM, 6 * DM, 16, 192, 2, 2, DM * 2, CU_TENSOR_MAP_SWIZZLE_32B, PROMO_W);
    make_map(enc, &T.m[M_GB], d_in[11], 6 * DM, DM, 6 * DM, 8, 192, 1, 1, 16, none, PROMO_W);
    char *wg = (char*)d_in[7], *wu = (char*)d_in[8], *wo = (char*)d_in[4], *wd = (char*)d_in[9];
    P.zg = wg > wu;
    P.zo = wo > wd;
    const size_t sg = P.zg ? wg - wu : wu - wg, so = P.zo ? wo - wd : wd - wo;
    make_map(enc, &T.m[M_GU], P.zg ? wu : wg, FF, DM, FF, 32, 64, 2, 2, sg, CU_TENSOR_MAP_SWIZZLE_64B, PROMO_W);
    make_map(enc, &T.m[M_GX], P.zg ? wu : wg, FF, DM, FF, 8, 64, 2, 2, sg, none, PROMO_W);
    make_map(enc, &T.m[M_OD], P.zo ? wd : wo, DM, FF, DM, 64, 64, 1, 2, so, CU_TENSOR_MAP_SWIZZLE_128B, PROMO_W);
    make_map(enc, &T.m[M_OX], P.zo ? wd : wo, DM, FF, DM, 8, 64, 1, 2, so, none, PROMO_W);
    P.x = (const __nv_bfloat16*)d_in[0];
    P.wr = (const __nv_bfloat16*)d_in[6];
    P.c = (const __nv_bfloat16*)d_in[10];
    P.k = (const __nv_bfloat16*)d_in[1];
    P.out = (__nv_bfloat16*)d_out;
    P.scratch = scratch;
    void* args[2] = {&P, &T};
    cudaLaunchCooperativeKernel((const void*)fused_kernel, dim3(NCTA), dim3(NTHREADS), args, SMEM_BYTES, cudaStreamPerThread);
}
```

```cpp
#include <cuda_runtime.h>
#include <cuda_bf16.h>
#include <cuda.h>
#include <stdint.h>

typedef unsigned long long u64;

#define TAU 568
#define TAU_W 650
#define L_KV 3200
#define L_WO 3050
#define L_GU 3050
#define L_WD 3100
#define L_LAST 250
#define L_GB 3000
#define W_0 6
#define W_LO 2
#define W_HI 8
#define T_PACE 20
#define SMOOTH 1
#define NK0 3
#define NK1 2
#define PFK 2
#define T_CLEAR 116
#define NPING0 4
#define NPING1 16

namespace {

constexpr int NB = 8, DM = 576, HQ = 32, HKV = 16, SK = 8192, WIN = 2048, DH = 128, FF = 4608;
constexpr int NCTA = 128;
constexpr int NCW = 10;
constexpr int NTHREADS = (NCW + 2) * 32;
constexpr int TILE_BYTES = 8192, NT = 64;
constexpr int SPIN_LIMIT = 1 << 22;

constexpr int OFF_RING = 0;
constexpr int OFF_WM = 121856;
constexpr int OFF_WQ = OFF_WM + 36864;
constexpr int OFF_GU = 0;
constexpr int OFF_WD = 73728;
constexpr int OFF_GB = 114688;
constexpr int OFF_OX = 131072;
constexpr int OFF_DX = OFF_OX + 4096;
constexpr int OFF_GX = OFF_DX + 4608;
constexpr int OFF_WO = OFF_WQ;
constexpr int OFF_P = OFF_WQ + 36864;
constexpr int P_PITCH = 528;
constexpr int OFF_RED = OFF_P + 16 * P_PITCH;
constexpr int OFF_ORED = OFF_RED + 5 * 4608 - 8704;
constexpr int OFF_ST = OFF_RED + 5 * 4608;
constexpr int OFF_SM = OFF_ST + 640;
constexpr int OFF_RT = OFF_SM + 128;
constexpr int OFF_QS = OFF_RT + 384;
constexpr int OFF_WR = OFF_QS + 512;
constexpr int OFF_WIN = OFF_WR + 1152;
constexpr int OFF_BAR = OFF_WIN + 16;
constexpr int BAR_FULL = 6, BAR_WO = 22, BAR_GU = 26, BAR_WD = 35, BAR_EMPTY = 40, BAR_SYNC = 56, BAR_WMF = 59, BAR_GB = 60, NBAR = 70;
constexpr int SMEM_BYTES = OFF_BAR + NBAR * 8;

constexpr int D_X1 = 0;
constexpr int D_O = 3072;
constexpr int D_ACT = D_O + 512 * 32;
constexpr int D_H = D_ACT + 576 * 32;
constexpr int D_Q = D_H + 3072;
constexpr int G_M = 2 * (D_Q + NB * HQ * 64);
constexpr int G_SIDE = G_M + 216 * 32;
constexpr int G_CNT = G_SIDE + 72 * 8;
constexpr int G_SET = 1 << 18;
__device__ __forceinline__ int d_part(int unit) { return (64 + unit + (unit & 64)) * 1024; }
constexpr int D_PING = 200 * 1024;
constexpr int G_EPOCH = 201 * 2048;
static_assert(G_CNT < 64 * 2048, "scratch layout");
__device__ uint32_t g_scratch[4 * G_SET];
__device__ __forceinline__ int dual(int w) { return w + (w & ~1023); }
__device__ __forceinline__ int near(int w, int side) { return dual(w) + (((__popc(w & 0x16400) ^ side) & 1) << 10); }

#define TI(i)
#define TS(i)
#define TSL(i)

enum { M_K, M_V, M_GU, M_GX, M_OD, M_OX, M_WQ, M_WM, M_WA, M_GB, NMAP };
struct Params {
    const __nv_bfloat16 *c, *x, *k;
    __nv_bfloat16* out;
    uint32_t* scratch;
    const __nv_bfloat16* wr;
    int zg, zo;
};
struct Maps {
    CUtensorMap m[NMAP];
};

__device__ __forceinline__ void mbar_init(uint32_t bar, int cnt) {
    asm volatile("mbarrier.init.shared::cta.b64 [%0], %1;" ::"r"(bar), "r"(cnt));
}
__device__ __forceinline__ void mbar_expect(uint32_t bar, uint32_t bytes) {
    asm volatile("mbarrier.arrive.expect_tx.shared::cta.b64 _, [%0], %1;" ::"r"(bar), "r"(bytes) : "memory");
}
__device__ __forceinline__ void mbar_arrive(uint32_t bar) {
    asm volatile("mbarrier.arrive.shared::cta.b64 _, [%0];" ::"r"(bar) : "memory");
}
__device__ __forceinline__ void mbar_wait(uint32_t bar, uint32_t parity) {
    asm volatile("{\n.reg .pred p;\n.reg .u32 c;\n"
                 "mbarrier.try_wait.parity.shared::cta.b64 p, [%0], %1;\n@p bra DONE;\nmov.u32 c, %2;\n"
                 "AGAIN:\nmbarrier.try_wait.parity.shared::cta.b64 p, [%0], %1;\nsub.u32 c, c, 1;\n"
                 "setp.eq.or.u32 p, c, 0, p;\n@!p bra AGAIN;\nDONE:\n}"
                 ::"r"(bar), "r"(parity), "n"(SPIN_LIMIT) : "memory");
}
__device__ __forceinline__ bool mbar_test(uint32_t bar, uint32_t parity) {
    uint32_t ok;
    asm volatile("{\n.reg .pred p;\nmbarrier.test_wait.parity.shared::cta.b64 p, [%1], %2;\nselp.u32 %0, 1, 0, p;\n}"
                 : "=r"(ok) : "r"(bar), "r"(parity) : "memory");
    return ok;
}
__device__ __forceinline__ void tma3d_hint(uint32_t dst, const CUtensorMap* m, int x, int y, int z, uint32_t bar, u64 pol) {
    asm volatile("cp.async.bulk.tensor.3d.shared::cluster.global.mbarrier::complete_tx::bytes.L2::cache_hint"
                 " [%0], [%1, {%2, %3, %4}], [%5], %6;"
                 ::"r"(dst), "l"(m), "r"(x), "r"(y), "r"(z), "r"(bar), "l"(pol) : "memory");
}
__device__ __forceinline__ void tma3d(uint32_t dst, const CUtensorMap* m, int x, int y, int z, uint32_t bar) {
    asm volatile("cp.async.bulk.tensor.3d.shared::cluster.global.mbarrier::complete_tx::bytes [%0], [%1, {%2, %3, %4}], [%5];"
                 ::"r"(dst), "l"(m), "r"(x), "r"(y), "r"(z), "r"(bar) : "memory");
}
__device__ __forceinline__ void bar_sync(int id, int n) { asm volatile("bar.sync %0, %1;" ::"r"(id), "r"(n) : "memory"); }
__device__ __forceinline__ void bar_arrive(int id, int n) { asm volatile("bar.arrive %0, %1;" ::"r"(id), "r"(n) : "memory"); }
__device__ __forceinline__ void ldsm4(uint32_t (&r)[4], uint32_t a) {
    asm volatile("ldmatrix.sync.aligned.m8n8.x4.shared.b16 {%0,%1,%2,%3}, [%4];"
                 : "=r"(r[0]), "=r"(r[1]), "=r"(r[2]), "=r"(r[3]) : "r"(a) : "memory");
}
__device__ __forceinline__ void ldsm4t(uint32_t (&r)[4], uint32_t a) {
    asm volatile("ldmatrix.sync.aligned.m8n8.x4.trans.shared.b16 {%0,%1,%2,%3}, [%4];"
                 : "=r"(r[0]), "=r"(r[1]), "=r"(r[2]), "=r"(r[3]) : "r"(a) : "memory");
}
__device__ __forceinline__ void mma(float (&c)[4], uint32_t a0, uint32_t a1, uint32_t a2, uint32_t a3, uint32_t b0, uint32_t b1) {
    asm volatile("mma.sync.aligned.m16n8k16.row.col.f32.bf16.bf16.f32 {%0,%1,%2,%3}, {%4,%5,%6,%7}, {%8,%9}, {%0,%1,%2,%3};"
                 : "+f"(c[0]), "+f"(c[1]), "+f"(c[2]), "+f"(c[3])
                 : "r"(a0), "r"(a1), "r"(a2), "r"(a3), "r"(b0), "r"(b1));
}
__device__ __forceinline__ uint32_t movm(uint32_t a) {
    uint32_t d;
    asm volatile("movmatrix.sync.aligned.m8n8.trans.b16 %0, %1;" : "=r"(d) : "r"(a));
    return d;
}
__device__ __forceinline__ uint32_t lds32(uint32_t a) { uint32_t v; asm volatile("ld.volatile.shared.b32 %0, [%1];" : "=r"(v) : "r"(a) : "memory"); return v; }
__device__ __forceinline__ float2 lds64f(uint32_t a) { float2 v; asm volatile("ld.shared.v2.f32 {%0,%1}, [%2];" : "=f"(v.x), "=f"(v.y) : "r"(a) : "memory"); return v; }
__device__ __forceinline__ uint4 lds128(uint32_t a) { uint4 v; asm volatile("ld.shared.v4.b32 {%0,%1,%2,%3}, [%4];" : "=r"(v.x), "=r"(v.y), "=r"(v.z), "=r"(v.w) : "r"(a) : "memory"); return v; }
__device__ __forceinline__ void sts32(uint32_t a, uint32_t v) { asm volatile("st.shared.b32 [%0], %1;" ::"r"(a), "r"(v) : "memory"); }
__device__ __forceinline__ void sts16(uint32_t a, uint16_t v) { asm volatile("st.shared.b16 [%0], %1;" ::"r"(a), "h"(v) : "memory"); }
__device__ __forceinline__ void sts64(uint32_t a, uint32_t x, uint32_t y) { asm volatile("st.shared.v2.b32 [%0], {%1,%2};" ::"r"(a), "r"(x), "r"(y) : "memory"); }
__device__ __forceinline__ void sts128(uint32_t a, uint32_t x, uint32_t y, uint32_t z, uint32_t w) {
    asm volatile("st.shared.v4.b32 [%0], {%1,%2,%3,%4};" ::"r"(a), "r"(x), "r"(y), "r"(z), "r"(w) : "memory");
}
__device__ __forceinline__ void sts128f(uint32_t a, const float (&c)[4]) {
    sts128(a, __float_as_uint(c[0]), __float_as_uint(c[1]), __float_as_uint(c[2]), __float_as_uint(c[3]));
}

__device__ __forceinline__ float sel4(const float (&c)[4], int t) { return (t & 2) ? ((t & 1) ? c[3] : c[2]) : ((t & 1) ? c[1] : c[0]); }

template <int LUT>
__device__ __forceinline__ uint32_t lop3(uint32_t a, uint32_t b, uint32_t c) {
    uint32_t d;
    asm("lop3.b32 %0, %1, %2, %3, %4;" : "=r"(d) : "r"(a), "r"(b), "r"(c), "n"(LUT));
    return d;
}
__device__ __forceinline__ uint32_t pin(uint32_t v) { return __shfl_xor_sync(0xffffffffu, v, 0); }
template <typename T>
__device__ __forceinline__ T* at(T* base, uint32_t bytes) { return (T*)((const char*)base + bytes); }

__device__ __forceinline__ uint32_t clock32(uint32_t dep) {
    uint32_t t;
    asm volatile("{\n.reg .pred p;\nsetp.eq.u32 p, %1, 0x9e3779b9;\n@p nanosleep.u32 1;\nmov.u32 %0, %clock;\n}" : "=r"(t) : "r"(dep) : "memory");
    return t;
}

__device__ __forceinline__ uint32_t nz(uint32_t v) { return v ? v : 0x80000000u; }
__device__ __forceinline__ void st1(uint32_t* p, uint32_t a) { asm volatile("st.relaxed.gpu.global.b32 [%0], %1;" ::"l"(p), "r"(a) : "memory"); }
__device__ __forceinline__ void st2(uint32_t* p, uint32_t a, uint32_t b) {
    asm volatile("st.relaxed.gpu.global.v2.b32 [%0], {%1,%2};" ::"l"(p), "r"(a), "r"(b) : "memory");
}
__device__ __forceinline__ void zero4(uint32_t* p) { asm volatile("st.relaxed.gpu.global.v4.b32 [%0], {%1,%1,%1,%1};" ::"l"(p), "r"(0) : "memory"); }
__device__ __forceinline__ void put1d(uint32_t* p, uint32_t a) { a = nz(a), st1(p, a), st1(p + 1024, a); }
__device__ __forceinline__ void put2d(uint32_t* p, uint32_t a, uint32_t b) { a = nz(a), b = nz(b), st2(p, a, b), st2(p + 1024, a, b); }
__device__ __forceinline__ uint32_t ld1(const uint32_t* p) {
    uint32_t v;
    asm volatile("ld.relaxed.gpu.global.b32 %0, [%1];" : "=r"(v) : "l"(p) : "memory");
    return v;
}
template <int N, int V>
__device__ __forceinline__ void fetch(const uint32_t* p, int stride, uint32_t (&a)[N * V]) {
#pragma unroll
    for (int i = 0; i < N; i++) {
        if (V == 1)
            asm volatile("{\n.reg .pred p;\nsetp.eq.u32 p, %0, 0;\n@p ld.relaxed.gpu.global.b32 %0, [%1];\n}"
                         : "+r"(a[i]) : "l"(p + i * stride) : "memory");
        if (V == 4)
            asm volatile("{\n.reg .pred p;\nsetp.eq.u32 p, %4, 0;\n@p ld.relaxed.gpu.global.v4.b32 {%0,%1,%2,%3}, [%5];\n}"
                         : "+r"(a[V * i]), "+r"(a[V * i + V / 4]), "+r"(a[V * i + V / 2]), "+r"(a[V * i + V - 1])
                         : "r"(min(min(a[V * i], a[V * i + V / 4]), min(a[V * i + V / 2], a[V * i + V - 1]))), "l"(p + i * stride) : "memory");
    }
}
template <int N>
__device__ __forceinline__ bool missing(const uint32_t (&a)[N]) {
    uint32_t lo = a[0];
#pragma unroll
    for (int i = 1; i < N; i++) lo = min(lo, a[i]);
    return __any_sync(0xffffffffu, lo == 0);
}
template <int N, int V>
__device__ __forceinline__ void get(const uint32_t* p, int stride, uint32_t (&a)[N * V]) {
    int it = 0;
    do fetch<N, V>(p, stride, a);
    while (missing(a) & (++it < SPIN_LIMIT));
}
__device__ __forceinline__ void cp16(uint32_t dst, const void* src) {
    asm volatile("cp.async.cg.shared.global [%0], [%1], 16;" ::"r"(dst), "l"(src) : "memory");
}

__device__ __forceinline__ uint32_t pack2(float lo, float hi) {
    uint32_t r;
    asm("cvt.rn.bf16x2.f32 %0, %1, %2;" : "=r"(r) : "f"(hi), "f"(lo));
    return r;
}
__device__ __forceinline__ float rbf(float x) { return __uint_as_float(pack2(0.f, x)); }
__device__ __forceinline__ float blo(uint32_t v) { return __uint_as_float(v << 16); }
__device__ __forceinline__ float bhi(uint32_t v) { return __uint_as_float(v & 0xffff0000u); }
__device__ __forceinline__ uint32_t badd2(uint32_t a, uint32_t b) { uint32_t r; asm("add.rn.bf16x2 %0, %1, %2;" : "=r"(r) : "r"(a), "r"(b)); return r; }
__device__ __forceinline__ uint32_t bsub2(uint32_t a, uint32_t b) { uint32_t r; asm("sub.rn.bf16x2 %0, %1, %2;" : "=r"(r) : "r"(a), "r"(b)); return r; }
__device__ __forceinline__ uint32_t bmul2(uint32_t a, uint32_t b) { uint32_t r; asm("mul.rn.bf16x2 %0, %1, %2;" : "=r"(r) : "r"(a), "r"(b)); return r; }
__device__ __forceinline__ float ex2(float x) { float r; asm("ex2.approx.ftz.f32 %0, %1;" : "=f"(r) : "f"(x)); return r; }
__device__ __forceinline__ float rcp(float x) { float r; asm("rcp.approx.ftz.f32 %0, %1;" : "=f"(r) : "f"(x)); return r; }
__device__ __forceinline__ float sqrt_f(float x) { float r; asm("sqrt.approx.ftz.f32 %0, %1;" : "=f"(r) : "f"(x)); return r; }
constexpr float LOG2E = 1.4426950408889634f;
constexpr uint32_t ONE2 = 0x3f803f80u;
__device__ __forceinline__ float sigmoid_f(float x) { return rcp(1.0f + ex2(-LOG2E * x)); }
__device__ __forceinline__ uint32_t silu2(uint32_t v) {
    const float a = blo(v), b = bhi(v);
    return pack2(a * sigmoid_f(a), b * sigmoid_f(b));
}
__device__ __forceinline__ float quad_sum(float v) {
    v += __shfl_xor_sync(0xffffffffu, v, 1);
    return v + __shfl_xor_sync(0xffffffffu, v, 2);
}
__device__ __forceinline__ void ln_partial(const uint32_t (&v)[8], uint32_t dst, bool writer) {
    float s0 = 0.f, s1 = 0.f;
#pragma unroll
    for (int i = 0; i < 8; i++) {
        s0 += blo(v[i]);
        s1 += bhi(v[i]);
    }
    const float mean = quad_sum(s0 + s1) * (1.0f / 64);
    s0 = s1 = 0.f;
#pragma unroll
    for (int i = 0; i < 8; i++) {
        const float a = blo(v[i]) - mean, b = bhi(v[i]) - mean;
        s0 = fmaf(a, a, s0);
        s1 = fmaf(b, b, s1);
    }
    s0 = quad_sum(s0 + s1);
    if (writer) sts64(dst, __float_as_uint(mean), __float_as_uint(s0));
}
__device__ __forceinline__ void ln_combine(uint32_t src, uint32_t& mean2, float& inv) {
    float m[10], q0 = 0.f, q1 = 0.f, s = 0.f;
#pragma unroll
    for (int i = 0; i < 5; i++) {
        const uint4 v = lds128(src + i * 16);
        m[2 * i] = __uint_as_float(v.x);
        m[2 * i + 1] = __uint_as_float(v.z);
        q0 += __uint_as_float(v.y);
        if (i < 4) q1 += __uint_as_float(v.w);
    }
    const float mean = (((m[0] + m[1]) + (m[2] + m[3])) + ((m[4] + m[5]) + (m[6] + m[7])) + m[8]) * (1.0f / 9);
#pragma unroll
    for (int i = 0; i < 9; i++) s = fmaf(m[i] - mean, m[i] - mean, s);
    const float var = fmaf(s, 64.f, q0 + q1) * (1.0f / DM);
    mean2 = pack2(mean, mean);
    inv = rcp(rbf(sqrt_f(rbf(rbf(var) + 1e-5f))));
}
__device__ __forceinline__ uint32_t modulate2(uint32_t x, uint32_t mean2, float inv, uint32_t shift, uint32_t onep) {
    const uint32_t d = bsub2(x, mean2);
    return badd2(bmul2(pack2(blo(d) * inv, bhi(d) * inv), onep), shift);
}
template <int N>
__device__ __forceinline__ void sum_frags(float (&c)[4], uint32_t addr, int stride) {
#pragma unroll
    for (int w = 0; w < N; w++) {
        const uint4 v = lds128(addr + w * stride);
        c[0] += __uint_as_float(v.x); c[1] += __uint_as_float(v.y);
        c[2] += __uint_as_float(v.z); c[3] += __uint_as_float(v.w);
    }
}

template <int ST>
__device__ __forceinline__ void project(uint32_t sm, const uint32_t* src, uint32_t* dst, uint32_t wa, uint32_t ws, uint32_t l16, int nsync, int warp, int lane) {
    constexpr int NW = ST ? 9 : 8, NI = ST ? 5 : 4, NP = NI - 2;
    const uint32_t wbar = sm + OFF_BAR + (ST ? BAR_WD : BAR_WO) * 8, stage = sm + (ST ? OFF_WO : OFF_P) + l16;
    uint32_t w[NW][4] = {}, f[NW][4], b[4] = {};
    auto load_w = [&](int j) {
        const int i0 = j == 4 ? 8 : ST ? 2 * ((j + 3) & 3) : 2 * j;
        ldsm4t(w[i0], wa + i0 * ws);
        if (j < 4) ldsm4t(w[i0 + 1], wa + (i0 + 1) * ws);
    };
    bool have_w = false;
    int it = 0;
    do {
        if (!have_w && __all_sync(0xffffffffu, lane >= NP || mbar_test(wbar + lane * 8, 0))) {
            have_w = true;
#pragma unroll
            for (int j = 0; j < NP; j++) load_w(j);
        }
        if (warp >= NW) break;
        if (ST) fetch<4, 1>(src, 32, b);
        else fetch<1, 4>(src, 0, b);
    } while (missing(b) & (++it < SPIN_LIMIT));
    if (warp == 0) TSL(ST ? 24 : 21);
    if (warp < NW) sts128(stage + warp * 512, b[0], b[2], b[1], b[3]);
    bar_sync(ST ? 6 : 3, nsync);
#pragma unroll
    for (int i = 0; i < NW; i++) {
        const int k = ST && i < 8 ? (i + 6) & 7 : i;
        const uint4 v = lds128(stage + k * 512);
        f[k][0] = v.x, f[k][1] = v.y, f[k][2] = v.z, f[k][3] = v.w;
    }
    float acc[4][4] = {};
#pragma unroll
    for (int j = 0; j < NI; j++) {
        const int i0 = j == 4 ? 8 : ST ? 2 * ((j + 3) & 3) : 2 * j, n = j == 4 ? 1 : 2;
        if (j >= NP || !have_w) {
            mbar_wait(wbar + j * 8, 0);
            load_w(j);
        }
#pragma unroll
        for (int i = i0; i < i0 + n; i++) {
            mma(acc[2 * (i & 1)], f[i][0], f[i][1], f[i][2], f[i][3], w[i][0], w[i][1]);
            mma(acc[2 * (i & 1) + 1], f[i][0], f[i][1], f[i][2], f[i][3], w[i][2], w[i][3]);
        }
    }
    const float s0 = (acc[2][0] + acc[3][2]) + (acc[0][0] + acc[1][2]), s1 = (acc[2][1] + acc[3][3]) + (acc[0][1] + acc[1][3]);
    st2(dst, (__float_as_uint(s0) | 1) ^ ST, (__float_as_uint(s1) | 1) ^ ST);
}

template <int ST, typename F>
__device__ __forceinline__ uint32_t reduce16(const uint32_t* src, F arrived) {
    uint32_t a[32] = {}, bad[16], any;
    int it = 0;
#pragma unroll
    for (int i = 0; i < 16; i++) bad[i] = 1;
    do {
#pragma unroll
        for (int i = 0; i < 16; i++)
            asm volatile("{\n.reg .pred p;\nsetp.ne.u32 p, %2, 0;\n@p ld.relaxed.gpu.global.v2.b32 {%0,%1}, [%3];\n}"
                         : "+r"(a[2 * i]), "+r"(a[2 * i + 1]) : "r"(bad[i]), "l"(src + i * 64) : "memory");
#pragma unroll
        for (int i = 0; i < 16; i++) bad[i] = lop3<ST ? 0xa8 : 0x2a>(a[2 * i], a[2 * i + 1], 1);
        any = lop3<0xfe>(lop3<0xfe>(lop3<0xfe>(bad[0], bad[1], bad[2]), lop3<0xfe>(bad[3], bad[4], bad[5]), lop3<0xfe>(bad[6], bad[7], bad[8])),
                         lop3<0xfe>(lop3<0xfe>(bad[9], bad[10], bad[11]), lop3<0xfe>(bad[12], bad[13], bad[14]), bad[15]), 0);
    } while (__any_sync(0xffffffffu, any != 0) & (++it < SPIN_LIMIT));
    arrived();
    float f[8];
#pragma unroll
    for (int i = 0; i < 8; i++)
        f[i] = (__uint_as_float(a[i]) + __uint_as_float(a[i + 8])) + (__uint_as_float(a[i + 16]) + __uint_as_float(a[i + 24]));
    f[0] = (f[0] + f[2]) + (f[4] + f[6]);
    f[1] = (f[1] + f[3]) + (f[5] + f[7]);
    return pack2(f[0], f[1]);
}

__global__ void __launch_bounds__(NTHREADS, 1) fused_kernel(const Params P, const __grid_constant__ Maps T) {
    extern __shared__ __align__(1024) char smem_raw[];
    constexpr uint32_t sm = 1024;
    const int tid = threadIdx.x, lane = tid & 31;
    const int cta = blockIdx.x, grp = cta >> 3, sub = cta & 7;
    const uint32_t bars = sm + OFF_BAR;
    const int row0 = (sub * HKV + grp) * SK + (SK - WIN);
    if (tid >> 5 == 9) {
#pragma unroll
        for (int i = 0; i < PFK; i++) asm volatile("prefetch.global.L2 [%0];" ::"l"(P.k + (size_t)row0 * DH + (lane + i * 32) * 64) : "memory");
    }
    u64 pol;
    asm volatile("createpolicy.fractional.L2::evict_first.b64 %0, 1.0;" : "=l"(pol));
    if (tid == NCW * 32) {
        TS(0);
        const int n0 = cta < 90 ? 0 : 3;
#pragma unroll
        for (int i = 0; i < 6; i++) mbar_init(bars + i * 8, 1);
        asm volatile("fence.mbarrier_init.release.cluster;" ::: "memory");
#pragma unroll
        for (int i = 0; i < 3; i++) {
            mbar_expect(bars + (n0 + i) * 8, 12288);
            tma3d(sm + OFF_WM + (n0 + i) * 12288, &T.m[cta < 36 ? M_WA : cta < 90 ? M_WM : M_WQ], cta < 36 ? 16 * cta : 32 * cta,
                  i * 192, 0, bars + (n0 + i) * 8);
            TI(n0 + i);
        }
        TS(26);
    }
    if (tid == NCW * 32 + 32) {
#pragma unroll
        for (int i = 0; i < 4; i++) mbar_init(bars + (BAR_FULL + i) * 8, 1);
        asm volatile("fence.mbarrier_init.release.cluster;" ::: "memory");
#pragma unroll
        for (int t = 0; t < NK0; t++) {
            mbar_expect(bars + (BAR_FULL + t) * 8, TILE_BYTES);
            tma3d_hint(sm + OFF_RING + t * TILE_BYTES, &T.m[M_K], 0, row0 + t * 32, 0, bars + (BAR_FULL + t) * 8, pol);
            TI(6 + t);
        }
    }
    if (tid < 288 && cta < 90) {
#pragma unroll
        for (int i = 0; i < 2; i++) {
            const int row = (lane >> 3) + 4 * i, so = row * DM + (tid >> 5) * 64 + (lane & 7) * 8;
            const uint32_t d = sm + OFF_RED + (tid >> 5) * 2048 + row * 128 + (((lane & 7) ^ row) << 4);
            cp16(d, P.c + so);
            if (cta < 36) cp16(d + 1024, P.x + so);
        }
    }
    uint32_t* const g0 = P.scratch;
    const uint32_t epoch = ld1(g0 + G_EPOCH);
    const int warp = __shfl_sync(0xffffffffu, tid >> 5, 0);

    if (warp >= NCW) {
        const int pw = warp - NCW;
        bar_arrive(1, (NCW + 1) * 32);
        if (pw && lane < M_WQ) asm volatile("prefetch.tensormap [%0];" ::"l"(&T.m[M_WQ - lane]) : "memory");
        if (tid == NCW * 32) sts32(sm + OFF_WIN, 0);
        __syncwarp();
        bar_sync(15, NTHREADS);
        if (lane == 0) {
            if (pw == 0 && cta < 90) {
#pragma unroll 1
                for (int n = 3; n < 6; n++) {
                    mbar_expect(bars + n * 8, 12288);
                    mbar_wait(bars + (n - 3) * 8, 0);
                    tma3d(sm + OFF_WM + n * 12288, &T.m[M_WQ], 32 * cta, (n - 3) * 192, 0, bars + n * 8);
                    TI(n);
                }
            }
#pragma unroll 1
            for (int t = NK0 + (1 - pw) * NK1; t < NK0 + NK1 + 3 * (1 - pw); t++) {
                mbar_expect(bars + (BAR_FULL + t) * 8, TILE_BYTES);
                mbar_wait(bars + (t + (pw ? BAR_FULL - NK1 : 3 - NK0 - NK1)) * 8, 0);
                tma3d_hint(sm + OFF_RING + t * TILE_BYTES, &T.m[M_K], 0, row0 + t * 32, 0, bars + (BAR_FULL + t) * 8, pol);
                TI(6 + t);
            }
            if (pw == 0) {
                auto on_time = [&](int due, uint32_t bar, uint32_t parity) {
                    uint32_t origin;
                    do origin = lds32(sm + OFF_WIN);
                    while (origin && (int)(clock32(0) - origin - due) < 0 && !mbar_test(bar, parity));
                };
#pragma unroll 1
                for (int t = NK0 + NK1 + 3; t < 2 * NT; t++) {
                    if (t == 14 && cta < 90) mbar_wait(bars + BAR_WMF * 8, 0);
                    if (t == 15) TS(30);
                    const uint32_t fb = bars + (BAR_FULL + (t & 15)) * 8;
                    const int hi = t - (lds32(sm + OFF_WIN) ? W_HI : W_0), lo = t - W_LO;
                    mbar_wait(fb + (BAR_EMPTY - BAR_FULL) * 8, (~t >> 4) & 1);
                    mbar_expect(fb, TILE_BYTES);
                    mbar_wait(bars + (BAR_FULL + (hi & 15)) * 8, (hi >> 4) & 1);
                    on_time(t * TAU - L_KV, bars + (BAR_FULL + (lo & 15)) * 8, (lo >> 4) & 1);
                    tma3d_hint(sm + OFF_RING + (t & 15) * TILE_BYTES, &T.m[t >> 6], 0, row0 + (t & (NT - 1)) * 32, 0, fb, pol);
                    TI(6 + t);
                    if (t == T_CLEAR) mbar_arrive(bars + (BAR_SYNC + 1) * 8);
                }
                mbar_wait(bars + BAR_SYNC * 8, 0);
                auto window = [&](int b, int lead) {
                    mbar_wait(bars + (b - W_HI) * 8, b - W_HI < BAR_WO);
                    on_time((2 * NT - 1) * TAU + (b - BAR_WO + 1) * TAU_W - lead, bars + (b - W_LO) * 8, b - W_LO < BAR_WO);
                };
#pragma unroll 1
                for (int i = 0; i < 4; i++) {
                    window(BAR_WO + i, L_WO);
                    tma3d(sm + OFF_WO + i * 8192, &T.m[M_OD], 64 * sub, grp * 256 + i * 64, P.zo, bars + (BAR_WO + i) * 8);
                    tma3d(sm + OFF_OX + i * 1024, &T.m[M_OX], 512 + 8 * sub, grp * 256 + i * 64, P.zo, bars + (BAR_WO + i) * 8);
                    TI(134 + i);
                }
                TS(28);
#pragma unroll 1
                for (int i = 0; i < 9; i++) {
                    mbar_wait(bars + (BAR_EMPTY + i) * 8, 1);
                    window(BAR_GU + i, L_GU);
                    tma3d(sm + OFF_GU + i * 8192, &T.m[M_GU], grp * 288 + 32 * sub, i * 64, 0, bars + (BAR_GU + i) * 8);
                    if (sub < 4) tma3d(sm + OFF_GX + i * 2048, &T.m[M_GX], grp * 288 + 256 + 8 * sub, i * 64, 0, bars + (BAR_GU + i) * 8);
                    TI(138 + i);
                }
                TS(29);
#pragma unroll 1
                for (int i = 0; i < 5; i++) {
                    const int blk = i < 4 ? (i + 3) & 3 : 4, r = min(blk * 64, 224);
                    mbar_wait(bars + (BAR_EMPTY + 9 + blk) * 8, 1);
                    window(BAR_WD + i, L_WD + (i == 4 ? L_LAST : 0));
                    tma3d(sm + OFF_WD + r * 128, &T.m[M_OD], 64 * sub, grp * 288 + r, P.zo ^ 1, bars + (BAR_WD + i) * 8);
                    tma3d(sm + OFF_DX + r * 16, &T.m[M_OX], 512 + 8 * sub, grp * 288 + r, P.zo ^ 1, bars + (BAR_WD + i) * 8);
                    TI(147 + i);
                }
                if (cta < 72) {
                    mbar_wait(bars + (BAR_EMPTY + 14) * 8, 1);
                    mbar_wait(bars + (BAR_EMPTY + 15) * 8, 1);
                    mbar_expect(bars + BAR_GB * 8, 9216);
                    window(BAR_WD + 5, L_GB);
#pragma unroll
                    for (int i = 0; i < 3; i++) tma3d(sm + OFF_GB + i * 3072, &T.m[M_GB], 5 * DM + 8 * cta, i * 192, 0, bars + BAR_GB * 8);
                }
            } else {
#pragma unroll 1
                for (int i = BAR_WO; i < BAR_WD + 5; i++) mbar_expect(bars + i * 8, i < BAR_GU || i >= BAR_WD ? 9216 : sub < 4 ? 10240 : 8192);
                mbar_arrive(bars + BAR_SYNC * 8);
                uint32_t* const cnt = g0 + (epoch & 1) * G_SET + G_CNT;
                uint32_t origin = 0;
#pragma unroll 1
                for (int t = cta & 3; t < 144; t += 4) {
                    const uint32_t bar = bars + (BAR_FULL + (t < 2 * NT ? t & 15 : t - 112)) * 8;
                    mbar_wait(bar, (t >> 4) & 1);
                    if (t < 2 * NT) mbar_arrive(bar + (BAR_EMPTY - BAR_FULL) * 8);
                    const uint32_t t0 = clock32(0);
                    const int c = (int)atomicAdd(cnt, 1u) - 16;
                    const uint32_t o = t0 + ((clock32(c) - t0) >> 1) - ((c * TAU + max(c - 32 * (2 * NT - 1), 0) * (TAU_W - TAU)) >> 5);
                    if (t < T_PACE) continue;
                    origin = (origin ? origin + ((int)(o - origin) >> SMOOTH) : o) | 1;
                    sts32(sm + OFF_WIN, origin);
                }
            }
        }
        return;
    }

    if (lane == 0) {
#pragma unroll
        for (int i = 0; i < 6; i++) {
            const int b = 10 + warp * 6 + i;
            mbar_init(bars + b * 8, b >= BAR_EMPTY && b < BAR_EMPTY + 16 && ((b ^ cta) & 3) == 0 ? 2 : 1);
        }
        asm volatile("fence.mbarrier_init.release.cluster;" ::: "memory");
    }
    __syncwarp();
    if (warp < 9) bar_arrive(15, NTHREADS);
    const int g = lane >> 2, t4 = lane & 3;
    uint32_t* const gs = g0 + (epoch & 1) * G_SET;

    uint32_t sc[8] = {};
    if (warp < 9) {
        const int off_h = (cta < 36 ? dual(D_H + 2 * cta * 32) : G_M + 4 * (cta - 36) * 32) + tid;
        const int off_h2 = off_h + (cta < 36 ? 1024 : 64);
        const int off_q = dual(D_Q + g * (HQ * 64) + cta * 16) + warp * 8 + t4 * 2;
        uint32_t bf[8] = {}, xp = 0, mean2 = 0;
        float inv = 0.f;
        if (cta < 36) xp = __ldg(reinterpret_cast<const uint32_t*>(P.x) + g * (DM / 2) + 8 * cta + 4 * (warp & 1) + t4);
        if (warp < 2) {
            st2(gs + off_q, 0, 0), st2(gs + off_q + 1024, 0, 0);
            if (cta < 36) st1(gs + off_h, 0), st1(gs + off_h2, 0);
        }
        if (cta < 90) {
            asm volatile("cp.async.wait_all;" ::: "memory");
            __syncwarp();
            const uint32_t fa = sm + OFF_RED + warp * 2048 + (lane & 7) * 128 + (((lane >> 3) ^ (lane & 7)) << 4);
            ldsm4(reinterpret_cast<uint32_t(&)[4]>(bf[0]), fa);
            ldsm4(reinterpret_cast<uint32_t(&)[4]>(bf[4]), fa ^ 64);
            if (cta < 36) {
                uint32_t xv[8];
                ldsm4(reinterpret_cast<uint32_t(&)[4]>(xv[0]), fa + 1024);
                ldsm4(reinterpret_cast<uint32_t(&)[4]>(xv[4]), (fa ^ 64) + 1024);
                ln_partial(xv, sm + OFF_ST + g * 80 + warp * 8, t4 == 0);
            }
#pragma unroll
            for (int i = 0; i < 8; i++) sc[i] = bf[i] = silu2(bf[i]);
        }
        if (warp == 0) TSL(18);
        bar_sync(1, (NCW + 1) * 32);
        if (cta < 36 && warp < 2) ln_combine(sm + OFF_ST + g * 80, mean2, inv);
        const int r = warp * 64 + (lane >> 4) * 8 + (lane & 7), hi8 = (lane >> 3) & 1, box = warp / 3;
#pragma unroll 1
        for (int pass = cta < 90 ? 0 : 1; pass < 2; pass++) {
            const bool pa = pass == 0 && cta < 36;
            const uint32_t ab = sm + OFF_WM + pass * 36864 +
                                (pa ? (box + hi8) * 6144 + r * 32 + ((lane & 4) << 2) : r * 64 + (((2 * hi8) ^ ((r >> 1) & 3)) << 4));
            const uint32_t as = pa ? 512 : 1024, red = sm + OFF_RED + pass * 9216;
            mbar_wait(bars + (pass * 3 + box) * 8, 0);
            if (warp == 8) TSL(pass ? 31 : 19);
            uint32_t a[4][2][4];
#pragma unroll
            for (int i = 0; i < 4; i++) {
                ldsm4t(a[i][0], ab + i * as);
                ldsm4t(a[i][1], (ab ^ 16) + i * as);
            }
            if (pass) {
                bar_sync(8, NCW * 32);
#pragma unroll
                for (int i = 0; i < 8; i++) bf[i] = 0;
                const uint32_t* const src_h = gs + near(D_H + warp * 256, lds32(sm + OFF_WIN + 4)) + lane;
                get<1, 1>(src_h, 0, reinterpret_cast<uint32_t(&)[1]>(bf[0]));
                get<8, 1>(src_h, 32, bf);
                if (warp == 0) TSL(3);
            }
            float acc[2][4] = {};
#pragma unroll
            for (int i = 0; i < 4; i++)
#pragma unroll
                for (int m = 0; m < 2; m++) mma(acc[m], a[i][m][0], a[i][m][1], a[i][m][2], a[i][m][3], bf[2 * i], bf[2 * i + 1]);
            sts128f(red + tid * 16, acc[0]);
            sts128f(red + 4608 + tid * 16, acc[1]);
            bar_sync(3, 288);
            if (warp < 2) {
                float c[4] = {};
                sum_frags<9>(c, red + warp * 4608 + lane * 16, 512);
                uint32_t lo = movm(pack2(c[0], c[1])), hi = movm(pack2(c[2], c[3]));
                if (pass) {
                    put2d(gs + off_q, lo, hi);
                    if (warp == 0) TSL(4);
                } else {
                    const uint32_t hi1 = badd2(hi, ONE2);
                    if (pa) hi = lo = modulate2(xp, mean2, inv, lo, hi1);
                    if (cta >= 72) lo = badd2(lo, ONE2), hi = hi1;
                    st1(gs + off_h, nz(lo));
                    st1(gs + off_h2, nz(hi));
                    if (warp == 0 && pa) TSL(2);
                }
            } else if (tid == 64 && pass == 0) {
                mbar_arrive(bars + BAR_WMF * 8);
            }
        }
    } else {
        if ((uint32_t)__cvta_generic_to_shared(smem_raw) != sm) __trap();
        uint32_t* const ping = g0 + dual(D_PING) + cta * 8;
        if (lane < 16) st1(ping + (lane >> 3) * 1024 + (lane & 7), 0);
        bar_sync(15, NTHREADS);
        uint32_t best[2] = {~0u, ~0u}, v = 0;
#pragma unroll 1
        for (int part = 0; part < 2; part++) {
            if (lane == 0) {
#pragma unroll 1
                for (int r = part ? NPING1 : NPING0; r > 0; r--) {
#pragma unroll
                    for (int k = 0; k < 2; k++) {
                        const uint32_t t0 = clock32(v);
                        v = atomicExch(ping + k * 1024, t0);
                        best[k] = min(best[k], clock32(v) - t0);
                    }
                }
                sts32(sm + OFF_WIN + 4 + 4 * part, ((best[1] < best[0]) ^ __popc(D_PING & 0x16400)) & 1);
            }
            __syncwarp();
            if (part) break;
            TSL(20);
            bar_arrive(8, NCW * 32);
            mbar_wait(bars + 5 * 8, 0);
            uint32_t a[4] = {};
            get<1, 4>(gs + near(D_Q + (sub * HQ + 2 * grp) * 64, lds32(sm + OFF_WIN + 4)) + lane * 4, 0, a);
            sts128(sm + OFF_QS + lane * 16, a[0], a[1], a[2], a[3]);
            __syncwarp();
            TSL(5);
            bar_arrive(4, 288);
        }
#pragma unroll
        for (int i = lane; i < 72; i += 32) cp16(sm + OFF_WR + i * 16, P.wr + i * 8);
        __syncwarp();
        if (cta < 72 && lane < 16) st1(g0 + ((epoch ^ lane >> 3) & 1) * G_SET + G_SIDE + cta * 8 + (lane & 7), lane < 8 ? 1 + lds32(sm + OFF_WIN + 8) : 0);
        asm volatile("cp.async.wait_all;" ::: "memory");
        __syncwarp();
        bar_arrive(2, NCW * 32);
        if (cta == 0 && lane == 0) st1(g0 + (~epoch & 1) * G_SET + G_CNT, 0);
        mbar_wait(bars + (BAR_SYNC + 1) * 8, 0);
#pragma unroll 1
        for (int c = 0; c < 4; c++) {
            uint32_t* const pg = g0 + (c >> 1) * G_SET + (c & 1) * 1024;
            zero4(pg + dual(D_O + cta * 128) + lane * 4);
            zero4(pg + dual(D_ACT + (grp * 36 + 4 * sub) * 32) + lane * 4);
            if (lane < 8 ? sub < 4 : lane < 16 && cta < 72)
                zero4(pg + dual(lane < 8 ? D_ACT + (grp * 36 + 32 + sub) * 32 : D_X1 + cta * 32) + (lane & 7) * 4);
        }
#pragma unroll 1
        for (int u = 0; u < 9; u++) zero4(g0 + dual(d_part(u < 8 ? 8 * sub + u : 64 + sub)) + (lane >> 4) * 1024 + grp * 64 + (lane & 15) * 4);
        {
            uint32_t* const nx = g0 + (~epoch & 1) * G_SET;
            uint32_t* const q = nx + dual(D_Q + g * (HQ * 64) + cta * 16) + t4 * 4;
            zero4(q), zero4(q + 1024);
            if (cta < 90) zero4(nx + (cta < 36 ? dual(D_H + 2 * cta * 32) + (lane >> 4) * (1024 - 64) : G_M + 4 * (cta - 36) * 32) + lane * 4);
        }
        __syncwarp();
        if (cta >= 72) {
            bar_arrive(5, NCW * 32);
            return;
        }
        const uint32_t io = pin(4 * (g * (DM / 2) + 4 * cta + t4));
        uint32_t x = __ldg(at(reinterpret_cast<const uint32_t*>(P.x), io)), ga[1] = {};
        get<1, 1>(gs + G_M + cta * 32 + lane, 0, ga);
        const uint32_t src_p = pin(4 * (near(d_part(cta), lds32(sm + OFF_WIN + 8)) + lane * 2));
        const uint32_t dst_x = pin(4 * ((epoch & 1) * G_SET + dual(D_X1 + cta * 32) + lane));
        bar_sync(5, NCW * 32);
        x = badd2(x, bmul2(ga[0], reduce16<0>(at(g0, src_p), [] {})));
        put1d(at(g0, dst_x), x);
        TSL(10);
        bar_sync(6, NCW * 32);
        const uint4 r0 = lds128(sm + OFF_RT + g * 48), r1 = lds128(sm + OFF_RT + g * 48 + 16);
        float r = __uint_as_float(lds32(sm + OFF_RT + g * 48 + 32));
        r += ((__uint_as_float(r0.x) + __uint_as_float(r0.y)) + (__uint_as_float(r0.z) + __uint_as_float(r0.w))) +
             ((__uint_as_float(r1.x) + __uint_as_float(r1.y)) + (__uint_as_float(r1.z) + __uint_as_float(r1.w)));
        r = sigmoid_f(rbf(r));
        const uint32_t h = lds32(sm + OFF_RED + (cta >> 2) * 512 + lane * 16 + (cta & 3) * 4), rs = pack2(r, r);
        uint32_t gb;
        const uint32_t y = reduce16<1>(at(g0, src_p), [&] {
            TSL(23);
            bar_sync(9, 64);
            gb = lds32(sm + OFF_QS + lane * 4);
        });
        *at(reinterpret_cast<uint32_t*>(P.out), io) = badd2(x, bmul2(gb, badd2(h, bmul2(y, rs))));
        if (cta == 0 && lane == 0) g0[G_EPOCH] = epoch + 1;
        TSL(15);
        return;
    }

    const uint32_t tile = sm + OFF_RING + warp * TILE_BYTES;
    const uint32_t fullb = bars + (BAR_FULL + warp) * 8;
    const uint32_t pw = sm + OFF_P + warp * (2 * P_PITCH);
    if (warp < 8) {
        {
            uint32_t q0[8], q1[8];
            bar_sync(4, 288);
#pragma unroll
            for (int i = 0; i < 8; i++) {
                const float2 v = lds64f(sm + OFF_QS + (g & 1) * 256 + i * 32 + t4 * 8);
                q0[i] = __float_as_uint(v.x), q1[i] = __float_as_uint(v.y);
            }
            uint32_t sp = pw + (t4 & 1) * P_PITCH + ((t4 >> 1) * 8 + g) * 2;
#pragma unroll 1
            for (int it = 0; it < 8; it++, sp += 64) {
                const uint32_t ab = tile + (it & 1) * (8 * TILE_BYTES) + (lane & 15) * 128 + (((lane >> 4) ^ (lane & 7)) << 4);
                mbar_wait(fullb + (it & 1) * 64, (it >> 1) & 1);
                float acc[2][2][4] = {};
#pragma unroll
                for (int ks = 0; ks < 8; ks++)
#pragma unroll
                    for (int m = 0; m < 2; m++) {
                        uint32_t a[4];
                        ldsm4(a, (ab ^ ((ks & 3) << 5)) + (ks >> 2) * 4096 + m * 2048);
                        mma(acc[m][ks & 1], a[0], a[1], a[2], a[3], (ks & 1) ? q1[ks - 1] : q0[ks], (ks & 1) ? q1[ks] : q0[ks + 1]);
                    }
                __syncwarp();
                if (lane == 0) mbar_arrive(fullb + (it & 1) * 64 + (BAR_EMPTY - BAR_FULL) * 8);
#pragma unroll
                for (int m = 0; m < 2; m++) {
                    const float s = sel4(acc[m][0], t4) + sel4(acc[m][1], t4);
                    sts16(sp + m * 32, (uint16_t)pack2(rbf(s) * 0.08838834764831845f, 0.f));
                }
            }
        }
        __syncwarp();
        if (warp == 7) TSL(6);
        const uint32_t pa = pw + (lane >> 4) * P_PITCH + (lane & 15) * 32;
        const uint32_t sa = sm + OFF_SM + (lane >> 4) * 64;
        const uint4 v0 = lds128(pa), v1 = lds128(pa + 16);
        const uint32_t sv[8] = {v0.x, v0.y, v0.z, v0.w, v1.x, v1.y, v1.z, v1.w};
        float e[16];
        float m = -INFINITY;
#pragma unroll
        for (int i = 0; i < 8; i++) {
            e[2 * i] = blo(sv[i]);
            e[2 * i + 1] = bhi(sv[i]);
            m = fmaxf(m, fmaxf(e[2 * i], e[2 * i + 1]));
        }
#pragma unroll
        for (int o = 8; o; o >>= 1) m = fmaxf(m, __shfl_xor_sync(0xffffffffu, m, o));
        float l = 0.f;
#pragma unroll
        for (int i = 0; i < 16; i++) {
            e[i] = ex2((e[i] - m) * LOG2E);
            l += e[i];
        }
#pragma unroll
        for (int o = 8; o; o >>= 1) l += __shfl_xor_sync(0xffffffffu, l, o);
        if ((lane & 15) == 0) sts64(sa + warp * 8, __float_as_uint(m), __float_as_uint(l));
        bar_sync(2, NCW * 32);
        const float2 v = lds64f(sa + (lane & 7) * 8);
        float M = v.x;
#pragma unroll
        for (int o = 4; o; o >>= 1) M = fmaxf(M, __shfl_xor_sync(0xffffffffu, M, o));
        float L = v.y * ex2((v.x - M) * LOG2E);
#pragma unroll
        for (int o = 4; o; o >>= 1) L += __shfl_xor_sync(0xffffffffu, L, o);
        const float sc = ex2((m - M) * LOG2E) * rcp(L);
        sts128(pa, pack2(e[0] * sc, e[1] * sc), pack2(e[2] * sc, e[3] * sc), pack2(e[4] * sc, e[5] * sc), pack2(e[6] * sc, e[7] * sc));
        sts128(pa + 16, pack2(e[8] * sc, e[9] * sc), pack2(e[10] * sc, e[11] * sc), pack2(e[12] * sc, e[13] * sc), pack2(e[14] * sc, e[15] * sc));
        __syncwarp();
    } else {
        bar_sync(2, NCW * 32);
    }

    uint32_t sh[8] = {}, op[8] = {};
    {
        const uint32_t* const src_m = gs + G_M + (72 + warp * 8) * 32 + lane;
        fetch<8, 1>(src_m + 72 * 32, 32, op);
        get<8, 1>(src_m, 32, sh);
        get<8, 1>(src_m + 72 * 32, 32, op);
    }
    const int side = lds32(sm + OFF_WIN + 8), set = (epoch & 1) * G_SET, rr = (lane >> 4) * 8 + (lane & 7);
    const uint32_t dst_o = pin(4 * (set + dual(D_O + cta * 128) + (tid & 0x70) + (tid & 3) * 4 + ((tid >> 2) & 3)));
    const uint32_t src_o = pin(4 * (set + near(D_O + grp * 1024, side) + g * 128 + warp * 16 + t4 * 4));
    const int unit = warp < 8 ? 8 * sub + warp : 64 + sub;
    uint32_t rside[1] = {};
    get<1, 1>(gs + G_SIDE + unit * 8, 0, rside);
    const uint32_t dst_p = pin(4 * (near(d_part(unit), rside[0] - 1) + grp * 64 + lane * 2));
    const uint32_t src_x = pin(4 * (set + near(D_X1 + warp * 256, side) + lane));
    const uint32_t dst_a = pin(4 * (set + dual(D_ACT + (grp * 36 + (warp < 4 ? 4 * sub + warp : 32 + sub)) * 32) + lane));
    const uint32_t src_a = pin(4 * (set + near(D_ACT + (grp * 36 + 4 * warp) * 32, side) + lane));
    const uint32_t rowoff = pin(warp < 8 ? lane * 128 + ((warp ^ (lane & 7)) << 4) : lane * 16), rowstep = warp < 8 ? 4096 : 512;
    const uint32_t l16 = pin(lane * 16);
    const uint32_t ored = pin((warp * 1088 + (t4 & 1) * 576 + ((t4 >> 1) * 8 + g) * 4) | ((tid >> 6) * 64 + tid * 8) << 16);

    if (warp < 8) {
        float acc[8][4] = {};
        uint32_t pp = pw + (lane & 1) * P_PITCH + (lane >> 3) * 16;
#pragma unroll 1
        for (int it = 0; it < 8; it++, pp += 64) {
            const uint32_t ab = tile + (it & 1) * (8 * TILE_BYTES) + ((lane & 7) + (lane >> 4) * 8) * 128 + ((((lane >> 3) & 1) ^ (lane & 7)) << 4);
            uint32_t pb[4];
            ldsm4(pb, pp);
            mbar_wait(fullb + (it & 1) * 64, (it >> 1) & 1);
#pragma unroll
            for (int ks = 0; ks < 2; ks++)
#pragma unroll
                for (int m = 0; m < 8; m++) {
                    uint32_t a[4];
                    ldsm4t(a, (ab ^ ((m & 3) << 5)) + (m >> 2) * 4096 + ks * 2048);
                    mma(acc[m], a[0], a[1], a[2], a[3], pb[2 * ks], pb[2 * ks + 1]);
                }
            __syncwarp();
            if (lane == 0) mbar_arrive(fullb + (it & 1) * 64 + (BAR_EMPTY - BAR_FULL) * 8);
        }
        if (warp == 7) TSL(7);
        const uint32_t ra = sm + OFF_ORED + (ored & 0xffff);
#pragma unroll
        for (int m = 0; m < 8; m++) sts32(ra + m * 64, __float_as_uint(sel4(acc[m], t4)));
    }
    bar_sync(5, NCW * 32);
    if (warp < 4) {
        float s[2][2] = {};
#pragma unroll
        for (int w = 0; w < 8; w++) {
            const float2 v = lds64f(sm + OFF_ORED + w * 1088 + (ored >> 16));
            s[w & 1][0] += v.x;
            s[w & 1][1] += v.y;
        }
        put1d(at(g0, dst_o), pack2(s[0][0] + s[1][0], s[0][1] + s[1][1]));
        if (warp == 0) TSL(8);
    }

    project<0>(sm, at(g0, src_o), at(g0, dst_p), sm + (warp < 8 ? OFF_WO : OFF_OX) + rowoff, rowstep, l16, 288, warp, lane);
    if (warp == 0) TSL(9);

    {
        uint32_t h[8] = {}, mean2;
        float inv;
        get<1, 1>(at(g0, src_x), 0, reinterpret_cast<uint32_t(&)[1]>(h[0]));
        get<8, 1>(at(g0, src_x), 32, h);
        if (warp == 0) TSL(11);
        ln_partial(h, sm + OFF_ST + g * 80 + warp * 8, t4 == 0);
        bar_sync(3, 288);
        ln_combine(sm + OFF_ST + g * 80, mean2, inv);
#pragma unroll
        for (int i = 0; i < 8; i++) h[i] = modulate2(h[i], mean2, inv, sh[i], op[i]);
        sts128(sm + OFF_RED + warp * 1024 + lane * 16, h[0], h[1], h[2], h[3]);
        sts128(sm + OFF_RED + warp * 1024 + 512 + lane * 16, h[4], h[5], h[6], h[7]);
        if (warp == 0) TSL(12);
        if (cta < 72) {
            float r = 0.f;
#pragma unroll
            for (int i = 0; i < 8; i++) {
                const uint32_t wr = lds32(sm + OFF_WR + (warp * 32 + i * 4 + t4) * 4);
                r = fmaf(blo(h[i]), blo(wr), fmaf(bhi(h[i]), bhi(wr), r));
            }
            r = quad_sum(r);
            if (t4 == 0) sts32(sm + OFF_RT + g * 48 + warp * 4, __float_as_uint(r));
        }
    }
    bar_sync(3, 288);

    if (warp < (sub < 4 ? 5 : 4)) {
        const int pl = ((lane >> 3) & 1) ^ P.zg;
        const uint32_t ks = warp < 4 ? 1024 : 256;
        uint32_t aa = sm + (warp < 4 ? OFF_GU + rr * 64 + (((lane & 6) << 3) ^ (warp << 4)) : OFF_GX + rr * 16) + pl * 4 * ks;
        float acc[2][4] = {};
#pragma unroll 1
        for (int i = 0; i < 9; i++, aa += 8 * ks) {
            const uint4 b0 = lds128(sm + OFF_RED + i * 1024 + lane * 16), b1 = lds128(sm + OFF_RED + i * 1024 + 512 + lane * 16);
            uint32_t a[4][4];
            mbar_wait(bars + (BAR_GU + i) * 8, 0);
#pragma unroll
            for (int k = 0; k < 4; k++) ldsm4t(a[k], aa + k * ks);
            mma(acc[0], a[0][0], a[0][1], a[0][2], a[0][3], b0.x, b0.y);
            mma(acc[1], a[1][0], a[1][1], a[1][2], a[1][3], b0.z, b0.w);
            mma(acc[0], a[2][0], a[2][1], a[2][2], a[2][3], b1.x, b1.y);
            mma(acc[1], a[3][0], a[3][1], a[3][2], a[3][3], b1.z, b1.w);
        }
        if (warp == 1) TSL(17);
        const uint32_t gate = pack2(acc[0][0] + acc[1][0], acc[0][1] + acc[1][1]), up = pack2(acc[0][2] + acc[1][2], acc[0][3] + acc[1][3]);
        put1d(at(g0, dst_a), movm(bmul2(silu2(gate), up)));
        if (warp == 1) TSL(13);
    } else {
        mbar_wait(bars + (BAR_GU + 8) * 8, 0);
    }

    project<1>(sm, at(g0, src_a), at(g0, dst_p), sm + (warp < 8 ? OFF_WD : OFF_DX) + rowoff, rowstep, l16, cta < 72 ? 320 : 288, warp, lane);
    if (warp == 0) TSL(14);
    if (warp == 8) TSL(27);

    if (cta < 72) {
        const uint32_t ga = sm + OFF_GB + warp * 1024 + ((lane >> 3) & 1) * 256 + (lane >> 4) * 128 + (lane & 7) * 16;
        float acc[2][4] = {};
        mbar_wait(bars + BAR_GB * 8, 0);
        if (warp == 0) TSL(22);
#pragma unroll
        for (int i = 0; i < 2; i++) {
            uint32_t w[4];
            ldsm4t(w, ga + i * 512);
            mma(acc[0], w[0], w[1], w[2], w[3], sc[4 * i], sc[4 * i + 1]);
            mma(acc[1], w[0], w[1], w[2], w[3], sc[4 * i + 2], sc[4 * i + 3]);
        }
        sts64(sm + OFF_RED + 9216 + tid * 8, __float_as_uint(acc[0][0] + acc[1][2]), __float_as_uint(acc[0][1] + acc[1][3]));
        if (warp) {
            bar_arrive(7, 288);
        } else {
            bar_sync(7, 288);
            float s[2][2] = {};
#pragma unroll
            for (int w = 0; w < 9; w++) {
                const float2 v = lds64f(sm + OFF_RED + 9216 + tid * 8 + w * 256);
                s[w & 1][0] += v.x;
                s[w & 1][1] += v.y;
            }
            sts32(sm + OFF_QS + lane * 4, movm(pack2(s[0][0] + s[1][0], s[0][1] + s[1][1])));
            __syncwarp();
            bar_arrive(9, 64);
            TSL(25);
        }
    }
}

typedef CUresult (*EncodeFn)(CUtensorMap*, CUtensorMapDataType, cuuint32_t, void*, const cuuint64_t*, const cuuint64_t*,
                             const cuuint32_t*, const cuuint32_t*, CUtensorMapInterleave, CUtensorMapSwizzle,
                             CUtensorMapL2promotion, CUtensorMapFloatOOBfill);

void make_map(EncodeFn enc, CUtensorMap* m, void* p, int cols, int rows, int pitch, int bc, int br, int bp, int planes, size_t pstride,
              CUtensorMapSwizzle sw, int promo) {
    cuuint64_t dims[3] = {(cuuint64_t)cols, (cuuint64_t)rows, (cuuint64_t)planes};
    cuuint64_t strides[2] = {(cuuint64_t)pitch * 2, (cuuint64_t)pstride};
    cuuint32_t box[3] = {(cuuint32_t)bc, (cuuint32_t)br, (cuuint32_t)bp};
    cuuint32_t es[3] = {1, 1, 1};
    enc(m, CU_TENSOR_MAP_DATA_TYPE_BFLOAT16, 3, p, dims, strides, box, es, CU_TENSOR_MAP_INTERLEAVE_NONE, sw,
        (CUtensorMapL2promotion)promo, CU_TENSOR_MAP_FLOAT_OOB_FILL_NONE);
}

}

extern "C" void kernel_launch(void* const* d_in, const int* in_sizes, int n_in, void* d_out, int out_size) {
    static EncodeFn enc = nullptr;
    static uint32_t* scratch = nullptr;
    if (!enc) {
        void* fn = nullptr;
        cudaDriverEntryPointQueryResult st;
        cudaGetDriverEntryPoint("cuTensorMapEncodeTiled", &fn, cudaEnableDefault, &st);
        enc = (EncodeFn)fn;
        cudaGetSymbolAddress(&fn, g_scratch);
        scratch = (uint32_t*)(((uintptr_t)fn + 8 * G_SET - 1) & ~(uintptr_t)(8 * G_SET - 1));
        cudaFuncSetAttribute(fused_kernel, cudaFuncAttributeMaxDynamicSharedMemorySize, SMEM_BYTES);
    }
    Params P;
    Maps T;
    const CUtensorMapSwizzle none = CU_TENSOR_MAP_SWIZZLE_NONE;
    const int PROMO_W = CU_TENSOR_MAP_L2_PROMOTION_L2_128B, PROMO_KV = CU_TENSOR_MAP_L2_PROMOTION_L2_256B;
    make_map(enc, &T.m[M_K], d_in[1], 64, NB * HKV * SK, DH, 64, 32, 2, 2, 128, CU_TENSOR_MAP_SWIZZLE_128B, PROMO_KV);
    make_map(enc, &T.m[M_V], d_in[2], 64, NB * HKV * SK, DH, 64, 32, 2, 2, 128, CU_TENSOR_MAP_SWIZZLE_128B, PROMO_KV);
    make_map(enc, &T.m[M_WQ], d_in[3], HQ * DH, DM, HQ * DH, 32, 192, 1, 1, 16, CU_TENSOR_MAP_SWIZZLE_64B, PROMO_W);
    make_map(enc, &T.m[M_WM], d_in[11], 6 * DM, DM, 6 * DM, 32, 192, 1, 1, 16, CU_TENSOR_MAP_SWIZZLE_64B, PROMO_W);
    make_map(enc, &T.m[M_WA], d_in[11], DM, DM, 6 * DM, 16, 192, 2, 2, DM * 2, CU_TENSOR_MAP_SWIZZLE_32B, PROMO_W);
    make_map(enc, &T.m[M_GB], d_in[11], 6 * DM, DM, 6 * DM, 8, 192, 1, 1, 16, none, PROMO_W);
    char *wg = (char*)d_in[7], *wu = (char*)d_in[8], *wo = (char*)d_in[4], *wd = (char*)d_in[9];
    P.zg = wg > wu;
    P.zo = wo > wd;
    const size_t sg = P.zg ? wg - wu : wu - wg, so = P.zo ? wo - wd : wd - wo;
    make_map(enc, &T.m[M_GU], P.zg ? wu : wg, FF, DM, FF, 32, 64, 2, 2, sg, CU_TENSOR_MAP_SWIZZLE_64B, PROMO_W);
    make_map(enc, &T.m[M_GX], P.zg ? wu : wg, FF, DM, FF, 8, 64, 2, 2, sg, none, PROMO_W);
    make_map(enc, &T.m[M_OD], P.zo ? wd : wo, DM, FF, DM, 64, 64, 1, 2, so, CU_TENSOR_MAP_SWIZZLE_128B, PROMO_W);
    make_map(enc, &T.m[M_OX], P.zo ? wd : wo, DM, FF, DM, 8, 64, 1, 2, so, none, PROMO_W);
    P.x = (const __nv_bfloat16*)d_in[0];
    P.wr = (const __nv_bfloat16*)d_in[6];
    P.c = (const __nv_bfloat16*)d_in[10];
    P.k = (const __nv_bfloat16*)d_in[1];
    P.out = (__nv_bfloat16*)d_out;
    P.scratch = scratch;
    void* args[2] = {&P, &T};
    cudaLaunchCooperativeKernel((const void*)fused_kernel, dim3(NCTA), dim3(NTHREADS), args, SMEM_BYTES, cudaStreamPerThread);
}
```

```cpp
#include <cuda_runtime.h>
#include <cuda_bf16.h>
#include <cuda.h>
#include <stdint.h>

typedef unsigned long long u64;

#define TAU 568
#define TAU_W 650
#define L_KV 3200
#define L_WO 3050
#define L_GU 3050
#define L_WD 3100
#define L_LAST 250
#define L_GB 3000
#define W_0 6
#define W_LO 2
#define W_HI 8
#define W_HT 5
#define T_PACE 20
#define NK0 3
#define NK1 2
#define PFK 2
#define T_CLEAR 116
#define NPING0 4
#define NPING1 10

namespace {

constexpr int NB = 8, DM = 576, HQ = 32, HKV = 16, SK = 8192, WIN = 2048, DH = 128, FF = 4608;
constexpr int NCTA = 128;
constexpr int NCW = 10;
constexpr int NTHREADS = (NCW + 2) * 32;
constexpr int TILE_BYTES = 8192, NT = 64;
constexpr int SPIN_LIMIT = 1 << 22;

constexpr int OFF_RING = 0;
constexpr int OFF_WM = 121856;
constexpr int OFF_WQ = OFF_WM + 36864;
constexpr int OFF_GU = 0;
constexpr int OFF_WD = 73728;
constexpr int OFF_GB = 114688;
constexpr int OFF_OX = 131072;
constexpr int OFF_DX = OFF_OX + 4096;
constexpr int OFF_GX = OFF_DX + 4608;
constexpr int OFF_WO = OFF_WQ;
constexpr int OFF_P = OFF_WQ + 36864;
constexpr int P_PITCH = 528;
constexpr int OFF_RED = OFF_P + 16 * P_PITCH;
constexpr int OFF_ORED = OFF_RED + 5 * 4608 - 8704;
constexpr int OFF_ST = OFF_RED + 5 * 4608;
constexpr int OFF_SM = OFF_ST + 640;
constexpr int OFF_RT = OFF_SM + 128;
constexpr int OFF_QS = OFF_RT + 384;
constexpr int OFF_WR = OFF_QS + 512;
constexpr int OFF_WIN = OFF_WR + 1152;
constexpr int OFF_BAR = OFF_WIN + 16;
constexpr int BAR_FULL = 6, BAR_WO = 22, BAR_GU = 26, BAR_WD = 35, BAR_EMPTY = 40, BAR_SYNC = 56, BAR_WMF = 59, BAR_GB = 60, NBAR = 70;
constexpr int SMEM_BYTES = OFF_BAR + NBAR * 8;

constexpr int D_X1 = 0;
constexpr int D_O = 3072;
constexpr int D_ACT = D_O + 512 * 32;
constexpr int D_H = D_ACT + 576 * 32;
constexpr int D_Q = D_H + 3072;
constexpr int G_M = 2 * (D_Q + NB * HQ * 64);
constexpr int G_SIDE = G_M + 216 * 32;
constexpr int G_CNT = G_SIDE + 72 * 8;
constexpr int G_SET = 1 << 18;
__device__ __forceinline__ int d_part(int unit) { return (64 + unit + (unit & 64)) * 1024; }
constexpr int D_PING = 200 * 1024;
constexpr int G_EPOCH = 201 * 2048;
static_assert(G_CNT < 64 * 2048, "scratch layout");
__device__ uint32_t g_scratch[4 * G_SET];
__device__ __forceinline__ int dual(int w) { return w + (w & ~1023); }
__device__ __forceinline__ int near(int w, int side) { return dual(w) + (((__popc(w & 0x16400) ^ side) & 1) << 10); }

#define TL(i, back)
#define TI(i)
#define TS(i)
#define TSL(i)

enum { M_K, M_V, M_GU, M_GX, M_OD, M_OX, M_WQ, M_WM, M_WA, M_GB, NMAP };
struct Params {
    const __nv_bfloat16 *c, *x, *k;
    __nv_bfloat16* out;
    uint32_t* scratch;
    const __nv_bfloat16* wr;
    int zg, zo;
};
struct Maps {
    CUtensorMap m[NMAP];
};

__device__ __forceinline__ void mbar_init(uint32_t bar, int cnt) {
    asm volatile("mbarrier.init.shared::cta.b64 [%0], %1;" ::"r"(bar), "r"(cnt));
}
__device__ __forceinline__ void mbar_expect(uint32_t bar, uint32_t bytes) {
    asm volatile("mbarrier.arrive.expect_tx.shared::cta.b64 _, [%0], %1;" ::"r"(bar), "r"(bytes) : "memory");
}
__device__ __forceinline__ void mbar_arrive(uint32_t bar) {
    asm volatile("mbarrier.arrive.shared::cta.b64 _, [%0];" ::"r"(bar) : "memory");
}
__device__ __forceinline__ void mbar_wait(uint32_t bar, uint32_t parity) {
    asm volatile("{\n.reg .pred p;\n.reg .u32 c;\n"
                 "mbarrier.try_wait.parity.shared::cta.b64 p, [%0], %1;\n@p bra DONE;\nmov.u32 c, %2;\n"
                 "AGAIN:\nmbarrier.try_wait.parity.shared::cta.b64 p, [%0], %1;\nsub.u32 c, c, 1;\n"
                 "setp.eq.or.u32 p, c, 0, p;\n@!p bra AGAIN;\nDONE:\n}"
                 ::"r"(bar), "r"(parity), "n"(SPIN_LIMIT) : "memory");
}
__device__ __forceinline__ bool mbar_test(uint32_t bar, uint32_t parity) {
    uint32_t ok;
    asm volatile("{\n.reg .pred p;\nmbarrier.test_wait.parity.shared::cta.b64 p, [%1], %2;\nselp.u32 %0, 1, 0, p;\n}"
                 : "=r"(ok) : "r"(bar), "r"(parity) : "memory");
    return ok;
}
__device__ __forceinline__ void tma3d_hint(uint32_t dst, const CUtensorMap* m, int x, int y, int z, uint32_t bar, u64 pol) {
    asm volatile("cp.async.bulk.tensor.3d.shared::cluster.global.mbarrier::complete_tx::bytes.L2::cache_hint"
                 " [%0], [%1, {%2, %3, %4}], [%5], %6;"
                 ::"r"(dst), "l"(m), "r"(x), "r"(y), "r"(z), "r"(bar), "l"(pol) : "memory");
}
__device__ __forceinline__ void tma3d(uint32_t dst, const CUtensorMap* m, int x, int y, int z, uint32_t bar) {
    asm volatile("cp.async.bulk.tensor.3d.shared::cluster.global.mbarrier::complete_tx::bytes [%0], [%1, {%2, %3, %4}], [%5];"
                 ::"r"(dst), "l"(m), "r"(x), "r"(y), "r"(z), "r"(bar) : "memory");
}
__device__ __forceinline__ void bar_sync(int id, int n) { asm volatile("bar.sync %0, %1;" ::"r"(id), "r"(n) : "memory"); }
__device__ __forceinline__ void bar_arrive(int id, int n) { asm volatile("bar.arrive %0, %1;" ::"r"(id), "r"(n) : "memory"); }
__device__ __forceinline__ void ldsm4(uint32_t (&r)[4], uint32_t a) {
    asm volatile("ldmatrix.sync.aligned.m8n8.x4.shared.b16 {%0,%1,%2,%3}, [%4];"
                 : "=r"(r[0]), "=r"(r[1]), "=r"(r[2]), "=r"(r[3]) : "r"(a) : "memory");
}
__device__ __forceinline__ void ldsm4t(uint32_t (&r)[4], uint32_t a) {
    asm volatile("ldmatrix.sync.aligned.m8n8.x4.trans.shared.b16 {%0,%1,%2,%3}, [%4];"
                 : "=r"(r[0]), "=r"(r[1]), "=r"(r[2]), "=r"(r[3]) : "r"(a) : "memory");
}
__device__ __forceinline__ void mma(float (&c)[4], uint32_t a0, uint32_t a1, uint32_t a2, uint32_t a3, uint32_t b0, uint32_t b1) {
    asm volatile("mma.sync.aligned.m16n8k16.row.col.f32.bf16.bf16.f32 {%0,%1,%2,%3}, {%4,%5,%6,%7}, {%8,%9}, {%0,%1,%2,%3};"
                 : "+f"(c[0]), "+f"(c[1]), "+f"(c[2]), "+f"(c[3])
                 : "r"(a0), "r"(a1), "r"(a2), "r"(a3), "r"(b0), "r"(b1));
}
__device__ __forceinline__ uint32_t movm(uint32_t a) {
    uint32_t d;
    asm volatile("movmatrix.sync.aligned.m8n8.trans.b16 %0, %1;" : "=r"(d) : "r"(a));
    return d;
}
__device__ __forceinline__ uint32_t lds32(uint32_t a) { uint32_t v; asm volatile("ld.volatile.shared.b32 %0, [%1];" : "=r"(v) : "r"(a) : "memory"); return v; }
__device__ __forceinline__ float2 lds64f(uint32_t a) { float2 v; asm volatile("ld.shared.v2.f32 {%0,%1}, [%2];" : "=f"(v.x), "=f"(v.y) : "r"(a) : "memory"); return v; }
__device__ __forceinline__ uint4 lds128(uint32_t a) { uint4 v; asm volatile("ld.shared.v4.b32 {%0,%1,%2,%3}, [%4];" : "=r"(v.x), "=r"(v.y), "=r"(v.z), "=r"(v.w) : "r"(a) : "memory"); return v; }
__device__ __forceinline__ void sts32(uint32_t a, uint32_t v) { asm volatile("st.shared.b32 [%0], %1;" ::"r"(a), "r"(v) : "memory"); }
__device__ __forceinline__ void sts16(uint32_t a, uint16_t v) { asm volatile("st.shared.b16 [%0], %1;" ::"r"(a), "h"(v) : "memory"); }
__device__ __forceinline__ void sts64(uint32_t a, uint32_t x, uint32_t y) { asm volatile("st.shared.v2.b32 [%0], {%1,%2};" ::"r"(a), "r"(x), "r"(y) : "memory"); }
__device__ __forceinline__ void sts128(uint32_t a, uint32_t x, uint32_t y, uint32_t z, uint32_t w) {
    asm volatile("st.shared.v4.b32 [%0], {%1,%2,%3,%4};" ::"r"(a), "r"(x), "r"(y), "r"(z), "r"(w) : "memory");
}
__device__ __forceinline__ void sts128f(uint32_t a, const float (&c)[4]) {
    sts128(a, __float_as_uint(c[0]), __float_as_uint(c[1]), __float_as_uint(c[2]), __float_as_uint(c[3]));
}

__device__ __forceinline__ float sel4(const float (&c)[4], int t) { return (t & 2) ? ((t & 1) ? c[3] : c[2]) : ((t & 1) ? c[1] : c[0]); }

template <int LUT>
__device__ __forceinline__ uint32_t lop3(uint32_t a, uint32_t b, uint32_t c) {
    uint32_t d;
    asm("lop3.b32 %0, %1, %2, %3, %4;" : "=r"(d) : "r"(a), "r"(b), "r"(c), "n"(LUT));
    return d;
}
__device__ __forceinline__ uint32_t pin(uint32_t v) { return __shfl_xor_sync(0xffffffffu, v, 0); }
template <typename T>
__device__ __forceinline__ T* at(T* base, uint32_t bytes) { return (T*)((const char*)base + bytes); }

__device__ __forceinline__ uint32_t clock32(uint32_t dep) {
    uint32_t t;
    asm volatile("{\n.reg .pred p;\nsetp.eq.u32 p, %1, 0x9e3779b9;\n@p nanosleep.u32 1;\nmov.u32 %0, %clock;\n}" : "=r"(t) : "r"(dep) : "memory");
    return t;
}

__device__ __forceinline__ uint32_t nz(uint32_t v) { return v ? v : 0x80000000u; }
__device__ __forceinline__ void st1(uint32_t* p, uint32_t a) { asm volatile("st.relaxed.gpu.global.b32 [%0], %1;" ::"l"(p), "r"(a) : "memory"); }
__device__ __forceinline__ void st2(uint32_t* p, uint32_t a, uint32_t b) {
    asm volatile("st.relaxed.gpu.global.v2.b32 [%0], {%1,%2};" ::"l"(p), "r"(a), "r"(b) : "memory");
}
__device__ __forceinline__ void zero4(uint32_t* p) { asm volatile("st.relaxed.gpu.global.v4.b32 [%0], {%1,%1,%1,%1};" ::"l"(p), "r"(0) : "memory"); }
__device__ __forceinline__ void put1d(uint32_t* p, uint32_t a) { a = nz(a), st1(p, a), st1(p + 1024, a); }
__device__ __forceinline__ void put2d(uint32_t* p, uint32_t a, uint32_t b) { a = nz(a), b = nz(b), st2(p, a, b), st2(p + 1024, a, b); }
__device__ __forceinline__ uint32_t ld1(const uint32_t* p) {
    uint32_t v;
    asm volatile("ld.relaxed.gpu.global.b32 %0, [%1];" : "=r"(v) : "l"(p) : "memory");
    return v;
}
template <int N, int V>
__device__ __forceinline__ void fetch(const uint32_t* p, int stride, uint32_t (&a)[N * V]) {
#pragma unroll
    for (int i = 0; i < N; i++) {
        if (V == 1)
            asm volatile("{\n.reg .pred p;\nsetp.eq.u32 p, %0, 0;\n@p ld.relaxed.gpu.global.b32 %0, [%1];\n}"
                         : "+r"(a[i]) : "l"(p + i * stride) : "memory");
        if (V == 4)
            asm volatile("{\n.reg .pred p;\nsetp.eq.u32 p, %4, 0;\n@p ld.relaxed.gpu.global.v4.b32 {%0,%1,%2,%3}, [%5];\n}"
                         : "+r"(a[V * i]), "+r"(a[V * i + V / 4]), "+r"(a[V * i + V / 2]), "+r"(a[V * i + V - 1])
                         : "r"(min(min(a[V * i], a[V * i + V / 4]), min(a[V * i + V / 2], a[V * i + V - 1]))), "l"(p + i * stride) : "memory");
    }
}
template <int N>
__device__ __forceinline__ bool missing(const uint32_t (&a)[N]) {
    uint32_t lo = a[0];
#pragma unroll
    for (int i = 1; i < N; i++) lo = min(lo, a[i]);
    return __any_sync(0xffffffffu, lo == 0);
}
template <int N, int V>
__device__ __forceinline__ void get(const uint32_t* p, int stride, uint32_t (&a)[N * V]) {
    int it = 0;
    do fetch<N, V>(p, stride, a);
    while (missing(a) & (++it < SPIN_LIMIT));
}
__device__ __forceinline__ void cp16(uint32_t dst, const void* src) {
    asm volatile("cp.async.cg.shared.global [%0], [%1], 16;" ::"r"(dst), "l"(src) : "memory");
}

__device__ __forceinline__ uint32_t pack2(float lo, float hi) {
    uint32_t r;
    asm("cvt.rn.bf16x2.f32 %0, %1, %2;" : "=r"(r) : "f"(hi), "f"(lo));
    return r;
}
__device__ __forceinline__ float rbf(float x) { return __uint_as_float(pack2(0.f, x)); }
__device__ __forceinline__ float blo(uint32_t v) { return __uint_as_float(v << 16); }
__device__ __forceinline__ float bhi(uint32_t v) { return __uint_as_float(v & 0xffff0000u); }
__device__ __forceinline__ uint32_t badd2(uint32_t a, uint32_t b) { uint32_t r; asm("add.rn.bf16x2 %0, %1, %2;" : "=r"(r) : "r"(a), "r"(b)); return r; }
__device__ __forceinline__ uint32_t bsub2(uint32_t a, uint32_t b) { uint32_t r; asm("sub.rn.bf16x2 %0, %1, %2;" : "=r"(r) : "r"(a), "r"(b)); return r; }
__device__ __forceinline__ uint32_t bmul2(uint32_t a, uint32_t b) { uint32_t r; asm("mul.rn.bf16x2 %0, %1, %2;" : "=r"(r) : "r"(a), "r"(b)); return r; }
__device__ __forceinline__ float ex2(float x) { float r; asm("ex2.approx.ftz.f32 %0, %1;" : "=f"(r) : "f"(x)); return r; }
__device__ __forceinline__ float rcp(float x) { float r; asm("rcp.approx.ftz.f32 %0, %1;" : "=f"(r) : "f"(x)); return r; }
__device__ __forceinline__ float sqrt_f(float x) { float r; asm("sqrt.approx.ftz.f32 %0, %1;" : "=f"(r) : "f"(x)); return r; }
constexpr float LOG2E = 1.4426950408889634f;
constexpr uint32_t ONE2 = 0x3f803f80u;
__device__ __forceinline__ float sigmoid_f(float x) { return rcp(1.0f + ex2(-LOG2E * x)); }
__device__ __forceinline__ uint32_t silu2(uint32_t v) {
    const float a = blo(v), b = bhi(v);
    return pack2(a * sigmoid_f(a), b * sigmoid_f(b));
}
__device__ __forceinline__ float quad_sum(float v) {
    v += __shfl_xor_sync(0xffffffffu, v, 1);
    return v + __shfl_xor_sync(0xffffffffu, v, 2);
}
__device__ __forceinline__ void ln_partial(const uint32_t (&v)[8], uint32_t dst, bool writer) {
    float s0 = 0.f, s1 = 0.f;
#pragma unroll
    for (int i = 0; i < 8; i++) {
        s0 += blo(v[i]);
        s1 += bhi(v[i]);
    }
    const float mean = quad_sum(s0 + s1) * (1.0f / 64);
    s0 = s1 = 0.f;
#pragma unroll
    for (int i = 0; i < 8; i++) {
        const float a = blo(v[i]) - mean, b = bhi(v[i]) - mean;
        s0 = fmaf(a, a, s0);
        s1 = fmaf(b, b, s1);
    }
    s0 = quad_sum(s0 + s1);
    if (writer) sts64(dst, __float_as_uint(mean), __float_as_uint(s0));
}
__device__ __forceinline__ void ln_combine(uint32_t src, uint32_t& mean2, float& inv) {
    float m[10], q0 = 0.f, q1 = 0.f, s = 0.f;
#pragma unroll
    for (int i = 0; i < 5; i++) {
        const uint4 v = lds128(src + i * 16);
        m[2 * i] = __uint_as_float(v.x);
        m[2 * i + 1] = __uint_as_float(v.z);
        q0 += __uint_as_float(v.y);
        if (i < 4) q1 += __uint_as_float(v.w);
    }
    const float mean = (((m[0] + m[1]) + (m[2] + m[3])) + ((m[4] + m[5]) + (m[6] + m[7])) + m[8]) * (1.0f / 9);
#pragma unroll
    for (int i = 0; i < 9; i++) s = fmaf(m[i] - mean, m[i] - mean, s);
    const float var = fmaf(s, 64.f, q0 + q1) * (1.0f / DM);
    mean2 = pack2(mean, mean);
    inv = rcp(rbf(sqrt_f(rbf(rbf(var) + 1e-5f))));
}
__device__ __forceinline__ uint32_t modulate2(uint32_t x, uint32_t mean2, float inv, uint32_t shift, uint32_t onep) {
    const uint32_t d = bsub2(x, mean2);
    return badd2(bmul2(pack2(blo(d) * inv, bhi(d) * inv), onep), shift);
}
template <int N>
__device__ __forceinline__ void sum_frags(float (&c)[4], uint32_t addr, int stride) {
#pragma unroll
    for (int w = 0; w < N; w++) {
        const uint4 v = lds128(addr + w * stride);
        c[0] += __uint_as_float(v.x); c[1] += __uint_as_float(v.y);
        c[2] += __uint_as_float(v.z); c[3] += __uint_as_float(v.w);
    }
}

template <int ST>
__device__ __forceinline__ void project(uint32_t sm, const uint32_t* src, uint32_t* dst, uint32_t wa, uint32_t ws, uint32_t l16, int nsync, int warp, int lane) {
    constexpr int NW = ST ? 9 : 8, NI = ST ? 5 : 4, NP = NI - 2;
    const uint32_t wbar = sm + OFF_BAR + (ST ? BAR_WD : BAR_WO) * 8, stage = sm + (ST ? OFF_WO : OFF_P) + l16;
    uint32_t w[NW][4] = {}, f[NW][4], b[4] = {};
    auto load_w = [&](int j) {
        const int i0 = j == 4 ? 8 : ST ? 2 * ((j + 3) & 3) : 2 * j;
        ldsm4t(w[i0], wa + i0 * ws);
        if (j < 4) ldsm4t(w[i0 + 1], wa + (i0 + 1) * ws);
    };
    bool have_w = false;
    int it = 0;
    do {
        if (!have_w && __all_sync(0xffffffffu, lane >= NP || mbar_test(wbar + lane * 8, 0))) {
            have_w = true;
#pragma unroll
            for (int j = 0; j < NP; j++) load_w(j);
        }
        if (warp >= NW) break;
        if (ST) fetch<4, 1>(src, 32, b);
        else fetch<1, 4>(src, 0, b);
    } while (missing(b) & (++it < SPIN_LIMIT));
    if (warp == 0) TSL(ST ? 24 : 21);
    if (warp < NW) sts128(stage + warp * 512, b[0], b[2], b[1], b[3]);
    bar_sync(ST ? 6 : 3, nsync);
#pragma unroll
    for (int i = 0; i < NW; i++) {
        const int k = ST && i < 8 ? (i + 6) & 7 : i;
        const uint4 v = lds128(stage + k * 512);
        f[k][0] = v.x, f[k][1] = v.y, f[k][2] = v.z, f[k][3] = v.w;
    }
    float acc[4][4] = {};
#pragma unroll
    for (int j = 0; j < NI; j++) {
        const int i0 = j == 4 ? 8 : ST ? 2 * ((j + 3) & 3) : 2 * j, n = j == 4 ? 1 : 2;
        if (j >= NP || !have_w) {
            mbar_wait(wbar + j * 8, 0);
            load_w(j);
        }
#pragma unroll
        for (int i = i0; i < i0 + n; i++) {
            mma(acc[2 * (i & 1)], f[i][0], f[i][1], f[i][2], f[i][3], w[i][0], w[i][1]);
            mma(acc[2 * (i & 1) + 1], f[i][0], f[i][1], f[i][2], f[i][3], w[i][2], w[i][3]);
        }
    }
    const float s0 = (acc[2][0] + acc[3][2]) + (acc[0][0] + acc[1][2]), s1 = (acc[2][1] + acc[3][3]) + (acc[0][1] + acc[1][3]);
    st2(dst, (__float_as_uint(s0) | 1) ^ ST, (__float_as_uint(s1) | 1) ^ ST);
}

template <int ST, typename F>
__device__ __forceinline__ uint32_t reduce16(const uint32_t* src, F arrived) {
    uint32_t a[32] = {}, bad[16], any;
    int it = 0;
#pragma unroll
    for (int i = 0; i < 16; i++) bad[i] = 1;
    do {
#pragma unroll
        for (int i = 0; i < 16; i++)
            asm volatile("{\n.reg .pred p;\nsetp.ne.u32 p, %2, 0;\n@p ld.relaxed.gpu.global.v2.b32 {%0,%1}, [%3];\n}"
                         : "+r"(a[2 * i]), "+r"(a[2 * i + 1]) : "r"(bad[i]), "l"(src + i * 64) : "memory");
#pragma unroll
        for (int i = 0; i < 16; i++) bad[i] = lop3<ST ? 0xa8 : 0x2a>(a[2 * i], a[2 * i + 1], 1);
        any = lop3<0xfe>(lop3<0xfe>(lop3<0xfe>(bad[0], bad[1], bad[2]), lop3<0xfe>(bad[3], bad[4], bad[5]), lop3<0xfe>(bad[6], bad[7], bad[8])),
                         lop3<0xfe>(lop3<0xfe>(bad[9], bad[10], bad[11]), lop3<0xfe>(bad[12], bad[13], bad[14]), bad[15]), 0);
    } while (__any_sync(0xffffffffu, any != 0) & (++it < SPIN_LIMIT));
    arrived();
    float f[8];
#pragma unroll
    for (int i = 0; i < 8; i++)
        f[i] = (__uint_as_float(a[i]) + __uint_as_float(a[i + 8])) + (__uint_as_float(a[i + 16]) + __uint_as_float(a[i + 24]));
    f[0] = (f[0] + f[2]) + (f[4] + f[6]);
    f[1] = (f[1] + f[3]) + (f[5] + f[7]);
    return pack2(f[0], f[1]);
}

__global__ void __launch_bounds__(NTHREADS, 1) fused_kernel(const Params P, const __grid_constant__ Maps T) {
    extern __shared__ __align__(1024) char smem_raw[];
    constexpr uint32_t sm = 1024;
    const int tid = threadIdx.x, lane = tid & 31;
    const int cta = blockIdx.x, grp = cta >> 3, sub = cta & 7;
    const uint32_t bars = sm + OFF_BAR;
    const int row0 = (sub * HKV + grp) * SK + (SK - WIN);
    if (tid >> 5 == 9) {
#pragma unroll
        for (int i = 0; i < PFK; i++) asm volatile("prefetch.global.L2 [%0];" ::"l"(P.k + (size_t)row0 * DH + (lane + i * 32) * 64) : "memory");
    }
    u64 pol;
    asm volatile("createpolicy.fractional.L2::evict_first.b64 %0, 1.0;" : "=l"(pol));
    if (tid == NCW * 32) {
        TS(0);
        const int n0 = cta < 90 ? 0 : 3;
#pragma unroll
        for (int i = 0; i < 6; i++) mbar_init(bars + i * 8, 1);
        asm volatile("fence.mbarrier_init.release.cluster;" ::: "memory");
#pragma unroll
        for (int i = 0; i < 3; i++) {
            mbar_expect(bars + (n0 + i) * 8, 12288);
            tma3d(sm + OFF_WM + (n0 + i) * 12288, &T.m[cta < 36 ? M_WA : cta < 90 ? M_WM : M_WQ], cta < 36 ? 16 * cta : 32 * cta,
                  i * 192, 0, bars + (n0 + i) * 8);
            TI(n0 + i);
        }
        TS(26);
    }
    if (tid == NCW * 32 + 32) {
#pragma unroll
        for (int i = 0; i < 4; i++) mbar_init(bars + (BAR_FULL + i) * 8, 1);
        asm volatile("fence.mbarrier_init.release.cluster;" ::: "memory");
#pragma unroll
        for (int t = 0; t < NK0; t++) {
            mbar_expect(bars + (BAR_FULL + t) * 8, TILE_BYTES);
            tma3d_hint(sm + OFF_RING + t * TILE_BYTES, &T.m[M_K], 0, row0 + t * 32, 0, bars + (BAR_FULL + t) * 8, pol);
            TI(6 + t);
        }
    }
    if (tid < 288 && cta < 90) {
#pragma unroll
        for (int i = 0; i < 2; i++) {
            const int row = (lane >> 3) + 4 * i, so = row * DM + (tid >> 5) * 64 + (lane & 7) * 8;
            const uint32_t d = sm + OFF_RED + (tid >> 5) * 2048 + row * 128 + (((lane & 7) ^ row) << 4);
            cp16(d, P.c + so);
            if (cta < 36) cp16(d + 1024, P.x + so);
        }
    }
    uint32_t* const g0 = P.scratch;
    const uint32_t epoch = ld1(g0 + G_EPOCH);
    const int warp = __shfl_sync(0xffffffffu, tid >> 5, 0);

    if (warp >= NCW) {
        const int pw = warp - NCW;
        bar_arrive(1, (NCW + 1) * 32);
        if (pw && lane < M_WQ) asm volatile("prefetch.tensormap [%0];" ::"l"(&T.m[M_WQ - lane]) : "memory");
        if (tid == NCW * 32) sts32(sm + OFF_WIN, 0);
        __syncwarp();
        bar_sync(15, NTHREADS);
        if (lane == 0) {
            if (pw == 0 && cta < 90) {
#pragma unroll 1
                for (int n = 3; n < 6; n++) {
                    mbar_expect(bars + n * 8, 12288);
                    mbar_wait(bars + (n - 3) * 8, 0);
                    tma3d(sm + OFF_WM + n * 12288, &T.m[M_WQ], 32 * cta, (n - 3) * 192, 0, bars + n * 8);
                    TI(n);
                }
            }
#pragma unroll 1
            for (int t = NK0 + (1 - pw) * NK1; t < NK0 + NK1 + 3 * (1 - pw); t++) {
                mbar_expect(bars + (BAR_FULL + t) * 8, TILE_BYTES);
                mbar_wait(bars + (t + (pw ? BAR_FULL - NK1 : 3 - NK0 - NK1)) * 8, 0);
                tma3d_hint(sm + OFF_RING + t * TILE_BYTES, &T.m[M_K], 0, row0 + t * 32, 0, bars + (BAR_FULL + t) * 8, pol);
                TI(6 + t);
            }
            if (pw == 0) {
                auto on_time = [&](int due, uint32_t bar, uint32_t parity) {
                    uint32_t origin;
                    do origin = lds32(sm + OFF_WIN);
                    while (origin && (int)(clock32(0) - origin - due) < 0 && !mbar_test(bar, parity));
                };
#pragma unroll 1
                for (int t = NK0 + NK1 + 3; t < 2 * NT; t++) {
                    if (t == 14 && cta < 90) mbar_wait(bars + BAR_WMF * 8, 0);
                    if (t == 15) TS(30);
                    const uint32_t fb = bars + (BAR_FULL + (t & 15)) * 8;
                    const int hi = t - (lds32(sm + OFF_WIN) ? W_HI : W_0), lo = t - W_LO;
                    mbar_wait(fb + (BAR_EMPTY - BAR_FULL) * 8, (~t >> 4) & 1);
                    mbar_expect(fb, TILE_BYTES);
                    mbar_wait(bars + (BAR_FULL + (hi & 15)) * 8, (hi >> 4) & 1);
                    on_time(t * TAU - L_KV, bars + (BAR_FULL + (lo & 15)) * 8, (lo >> 4) & 1);
                    tma3d_hint(sm + OFF_RING + (t & 15) * TILE_BYTES, &T.m[t >> 6], 0, row0 + (t & (NT - 1)) * 32, 0, fb, pol);
                    TI(6 + t);
                    if (t == T_CLEAR) mbar_arrive(bars + (BAR_SYNC + 1) * 8);
                }
                mbar_wait(bars + BAR_SYNC * 8, 0);
                auto window = [&](int b, int lead) {
                    mbar_wait(bars + (b - W_HT) * 8, b - W_HT < BAR_WO);
                    on_time((2 * NT - 1) * TAU + (b - BAR_WO + 1) * TAU_W - lead, bars + (b - W_LO) * 8, b - W_LO < BAR_WO);
                };
#pragma unroll 1
                for (int i = 0; i < 4; i++) {
                    window(BAR_WO + i, L_WO);
                    tma3d(sm + OFF_WO + i * 8192, &T.m[M_OD], 64 * sub, grp * 256 + i * 64, P.zo, bars + (BAR_WO + i) * 8);
                    tma3d(sm + OFF_OX + i * 1024, &T.m[M_OX], 512 + 8 * sub, grp * 256 + i * 64, P.zo, bars + (BAR_WO + i) * 8);
                    TI(134 + i);
                }
                TS(28);
#pragma unroll 1
                for (int i = 0; i < 9; i++) {
                    mbar_wait(bars + (BAR_EMPTY + i) * 8, 1);
                    window(BAR_GU + i, L_GU);
                    tma3d(sm + OFF_GU + i * 8192, &T.m[M_GU], grp * 288 + 32 * sub, i * 64, 0, bars + (BAR_GU + i) * 8);
                    if (sub < 4) tma3d(sm + OFF_GX + i * 2048, &T.m[M_GX], grp * 288 + 256 + 8 * sub, i * 64, 0, bars + (BAR_GU + i) * 8);
                    TI(138 + i);
                }
                TS(29);
#pragma unroll 1
                for (int i = 0; i < 5; i++) {
                    const int blk = i < 4 ? (i + 3) & 3 : 4, r = min(blk * 64, 224);
                    mbar_wait(bars + (BAR_EMPTY + 9 + blk) * 8, 1);
                    window(BAR_WD + i, L_WD + (i == 4 ? L_LAST : 0));
                    tma3d(sm + OFF_WD + r * 128, &T.m[M_OD], 64 * sub, grp * 288 + r, P.zo ^ 1, bars + (BAR_WD + i) * 8);
                    tma3d(sm + OFF_DX + r * 16, &T.m[M_OX], 512 + 8 * sub, grp * 288 + r, P.zo ^ 1, bars + (BAR_WD + i) * 8);
                    TI(147 + i);
                }
                if (cta < 72) {
                    mbar_wait(bars + (BAR_EMPTY + 14) * 8, 1);
                    mbar_wait(bars + (BAR_EMPTY + 15) * 8, 1);
                    mbar_expect(bars + BAR_GB * 8, 9216);
                    window(BAR_WD + 5, L_GB);
#pragma unroll
                    for (int i = 0; i < 3; i++) tma3d(sm + OFF_GB + i * 3072, &T.m[M_GB], 5 * DM + 8 * cta, i * 192, 0, bars + BAR_GB * 8);
                }
            } else {
#pragma unroll 1
                for (int i = BAR_WO; i < BAR_WD + 5; i++) mbar_expect(bars + i * 8, i < BAR_GU || i >= BAR_WD ? 9216 : sub < 4 ? 10240 : 8192);
                mbar_arrive(bars + BAR_SYNC * 8);
                uint32_t* const cnt = g0 + (epoch & 1) * G_SET + G_CNT;
#pragma unroll 1
                for (int t = cta & 3; t < 144; t += 4) {
                    const uint32_t bar = bars + (BAR_FULL + (t < 2 * NT ? t & 15 : t - 112)) * 8;
                    mbar_wait(bar, (t >> 4) & 1);
                    if (t < 2 * NT) mbar_arrive(bar + (BAR_EMPTY - BAR_FULL) * 8);
                    const uint32_t t0 = clock32(0);
                    const int c = (int)atomicAdd(cnt, 1u) - 16;
                    const uint32_t o = t0 + ((clock32(c) - t0) >> 1) - ((c * TAU + max(c - 32 * (2 * NT - 1), 0) * (TAU_W - TAU)) >> 5);
                    if (t >= T_PACE) sts32(sm + OFF_WIN, o | 1);
                    if ((t >> 2) == 8 || (t >> 2) == 24) TL(t >> 2, ((clock32(0) - t0) * 9) >> 4);
                }
            }
        }
        return;
    }

    if (lane == 0) {
#pragma unroll
        for (int i = 0; i < 6; i++) {
            const int b = 10 + warp * 6 + i;
            mbar_init(bars + b * 8, b >= BAR_EMPTY && b < BAR_EMPTY + 16 && ((b ^ cta) & 3) == 0 ? 2 : 1);
        }
        asm volatile("fence.mbarrier_init.release.cluster;" ::: "memory");
    }
    __syncwarp();
    if (warp < 9) bar_arrive(15, NTHREADS);
    const int g = lane >> 2, t4 = lane & 3;
    uint32_t* const gs = g0 + (epoch & 1) * G_SET;

    uint32_t sc[8] = {};
    if (warp < 9) {
        const int off_h = (cta < 36 ? dual(D_H + 2 * cta * 32) : G_M + 4 * (cta - 36) * 32) + tid;
        const int off_h2 = off_h + (cta < 36 ? 1024 : 64);
        const int off_q = dual(D_Q + g * (HQ * 64) + cta * 16) + warp * 8 + t4 * 2;
        uint32_t bf[8] = {}, xp = 0, mean2 = 0;
        float inv = 0.f;
        if (cta < 36) xp = __ldg(reinterpret_cast<const uint32_t*>(P.x) + g * (DM / 2) + 8 * cta + 4 * (warp & 1) + t4);
        if (warp < 2) {
            st2(gs + off_q, 0, 0), st2(gs + off_q + 1024, 0, 0);
            if (cta < 36) st1(gs + off_h, 0), st1(gs + off_h2, 0);
        }
        if (cta < 90) {
            asm volatile("cp.async.wait_all;" ::: "memory");
            __syncwarp();
            const uint32_t fa = sm + OFF_RED + warp * 2048 + (lane & 7) * 128 + (((lane >> 3) ^ (lane & 7)) << 4);
            ldsm4(reinterpret_cast<uint32_t(&)[4]>(bf[0]), fa);
            ldsm4(reinterpret_cast<uint32_t(&)[4]>(bf[4]), fa ^ 64);
            if (cta < 36) {
                uint32_t xv[8];
                ldsm4(reinterpret_cast<uint32_t(&)[4]>(xv[0]), fa + 1024);
                ldsm4(reinterpret_cast<uint32_t(&)[4]>(xv[4]), (fa ^ 64) + 1024);
                ln_partial(xv, sm + OFF_ST + g * 80 + warp * 8, t4 == 0);
            }
#pragma unroll
            for (int i = 0; i < 8; i++) sc[i] = bf[i] = silu2(bf[i]);
        }
        if (warp == 0) TSL(18);
        bar_sync(1, (NCW + 1) * 32);
        if (cta < 36 && warp < 2) ln_combine(sm + OFF_ST + g * 80, mean2, inv);
        const int r = warp * 64 + (lane >> 4) * 8 + (lane & 7), hi8 = (lane >> 3) & 1, box = warp / 3;
#pragma unroll 1
        for (int pass = cta < 90 ? 0 : 1; pass < 2; pass++) {
            const bool pa = pass == 0 && cta < 36;
            const uint32_t ab = sm + OFF_WM + pass * 36864 +
                                (pa ? (box + hi8) * 6144 + r * 32 + ((lane & 4) << 2) : r * 64 + (((2 * hi8) ^ ((r >> 1) & 3)) << 4));
            const uint32_t as = pa ? 512 : 1024, red = sm + OFF_RED + pass * 9216;
            mbar_wait(bars + (pass * 3 + box) * 8, 0);
            if (warp == 8) TSL(pass ? 31 : 19);
            uint32_t a[4][2][4];
#pragma unroll
            for (int i = 0; i < 4; i++) {
                ldsm4t(a[i][0], ab + i * as);
                ldsm4t(a[i][1], (ab ^ 16) + i * as);
            }
            if (pass) {
                bar_sync(8, NCW * 32);
#pragma unroll
                for (int i = 0; i < 8; i++) bf[i] = 0;
                const uint32_t* const src_h = gs + near(D_H + warp * 256, lds32(sm + OFF_WIN + 4)) + lane;
                get<1, 1>(src_h, 0, reinterpret_cast<uint32_t(&)[1]>(bf[0]));
                get<8, 1>(src_h, 32, bf);
                if (warp == 0) TSL(3);
            }
            float acc[2][4] = {};
#pragma unroll
            for (int i = 0; i < 4; i++)
#pragma unroll
                for (int m = 0; m < 2; m++) mma(acc[m], a[i][m][0], a[i][m][1], a[i][m][2], a[i][m][3], bf[2 * i], bf[2 * i + 1]);
            sts128f(red + tid * 16, acc[0]);
            sts128f(red + 4608 + tid * 16, acc[1]);
            bar_sync(3, 288);
            if (warp < 2) {
                float c[4] = {};
                sum_frags<9>(c, red + warp * 4608 + lane * 16, 512);
                uint32_t lo = movm(pack2(c[0], c[1])), hi = movm(pack2(c[2], c[3]));
                if (pass) {
                    put2d(gs + off_q, lo, hi);
                    if (warp == 0) TSL(4);
                } else {
                    const uint32_t hi1 = badd2(hi, ONE2);
                    if (pa) hi = lo = modulate2(xp, mean2, inv, lo, hi1);
                    if (cta >= 72) lo = badd2(lo, ONE2), hi = hi1;
                    st1(gs + off_h, nz(lo));
                    st1(gs + off_h2, nz(hi));
                    if (warp == 0 && pa) TSL(2);
                }
            } else if (tid == 64 && pass == 0) {
                mbar_arrive(bars + BAR_WMF * 8);
            }
        }
    } else {
        if ((uint32_t)__cvta_generic_to_shared(smem_raw) != sm) __trap();
        uint32_t* const ping = g0 + dual(D_PING) + cta * 8;
        if (lane < 16) st1(ping + (lane >> 3) * 1024 + (lane & 7), 0);
        bar_sync(15, NTHREADS);
        uint32_t best[2] = {~0u, ~0u}, v = 0;
#pragma unroll 1
        for (int part = 0; part < 2; part++) {
            if (lane == 0) {
#pragma unroll 1
                for (int r = part ? NPING1 : NPING0; r > 0; r--) {
#pragma unroll
                    for (int k = 0; k < 2; k++) {
                        const uint32_t t0 = clock32(v);
                        v = atomicExch(ping + k * 1024, t0);
                        best[k] = min(best[k], clock32(v) - t0);
                    }
                }
                sts32(sm + OFF_WIN + 4 + 4 * part, ((best[1] < best[0]) ^ __popc(D_PING & 0x16400)) & 1);
            }
            __syncwarp();
            if (part) break;
            TSL(20);
            bar_arrive(8, NCW * 32);
            mbar_wait(bars + 5 * 8, 0);
            uint32_t a[4] = {};
            get<1, 4>(gs + near(D_Q + (sub * HQ + 2 * grp) * 64, lds32(sm + OFF_WIN + 4)) + lane * 4, 0, a);
            sts128(sm + OFF_QS + lane * 16, a[0], a[1], a[2], a[3]);
            __syncwarp();
            TSL(5);
            bar_arrive(4, 288);
        }
#pragma unroll
        for (int i = lane; i < 72; i += 32) cp16(sm + OFF_WR + i * 16, P.wr + i * 8);
        __syncwarp();
        if (cta < 72 && lane < 16) st1(g0 + ((epoch ^ lane >> 3) & 1) * G_SET + G_SIDE + cta * 8 + (lane & 7), lane < 8 ? 1 + lds32(sm + OFF_WIN + 8) : 0);
        asm volatile("cp.async.wait_all;" ::: "memory");
        __syncwarp();
        bar_arrive(2, NCW * 32);
        if (cta == 0 && lane == 0) st1(g0 + (~epoch & 1) * G_SET + G_CNT, 0);
        mbar_wait(bars + (BAR_SYNC + 1) * 8, 0);
#pragma unroll 1
        for (int c = 0; c < 4; c++) {
            uint32_t* const pg = g0 + (c >> 1) * G_SET + (c & 1) * 1024;
            zero4(pg + dual(D_O + cta * 128) + lane * 4);
            zero4(pg + dual(D_ACT + (grp * 36 + 4 * sub) * 32) + lane * 4);
            if (lane < 8 ? sub < 4 : lane < 16 && cta < 72)
                zero4(pg + dual(lane < 8 ? D_ACT + (grp * 36 + 32 + sub) * 32 : D_X1 + cta * 32) + (lane & 7) * 4);
        }
#pragma unroll 1
        for (int u = 0; u < 9; u++) zero4(g0 + dual(d_part(u < 8 ? 8 * sub + u : 64 + sub)) + (lane >> 4) * 1024 + grp * 64 + (lane & 15) * 4);
        {
            uint32_t* const nx = g0 + (~epoch & 1) * G_SET;
            uint32_t* const q = nx + dual(D_Q + g * (HQ * 64) + cta * 16) + t4 * 4;
            zero4(q), zero4(q + 1024);
            if (cta < 90) zero4(nx + (cta < 36 ? dual(D_H + 2 * cta * 32) + (lane >> 4) * (1024 - 64) : G_M + 4 * (cta - 36) * 32) + lane * 4);
        }
        __syncwarp();
        if (cta >= 72) {
            bar_arrive(5, NCW * 32);
            return;
        }
        const uint32_t io = pin(4 * (g * (DM / 2) + 4 * cta + t4));
        uint32_t x = __ldg(at(reinterpret_cast<const uint32_t*>(P.x), io)), ga[1] = {};
        get<1, 1>(gs + G_M + cta * 32 + lane, 0, ga);
        const uint32_t src_p = pin(4 * (near(d_part(cta), lds32(sm + OFF_WIN + 8)) + lane * 2));
        const uint32_t dst_x = pin(4 * ((epoch & 1) * G_SET + dual(D_X1 + cta * 32) + lane));
        bar_sync(5, NCW * 32);
        x = badd2(x, bmul2(ga[0], reduce16<0>(at(g0, src_p), [] {})));
        put1d(at(g0, dst_x), x);
        TSL(10);
        bar_sync(6, NCW * 32);
        const uint4 r0 = lds128(sm + OFF_RT + g * 48), r1 = lds128(sm + OFF_RT + g * 48 + 16);
        float r = __uint_as_float(lds32(sm + OFF_RT + g * 48 + 32));
        r += ((__uint_as_float(r0.x) + __uint_as_float(r0.y)) + (__uint_as_float(r0.z) + __uint_as_float(r0.w))) +
             ((__uint_as_float(r1.x) + __uint_as_float(r1.y)) + (__uint_as_float(r1.z) + __uint_as_float(r1.w)));
        r = sigmoid_f(rbf(r));
        const uint32_t h = lds32(sm + OFF_RED + (cta >> 2) * 512 + lane * 16 + (cta & 3) * 4), rs = pack2(r, r);
        uint32_t gb;
        const uint32_t y = reduce16<1>(at(g0, src_p), [&] {
            TSL(23);
            bar_sync(9, 64);
            gb = lds32(sm + OFF_QS + lane * 4);
        });
        *at(reinterpret_cast<uint32_t*>(P.out), io) = badd2(x, bmul2(gb, badd2(h, bmul2(y, rs))));
        if (cta == 0 && lane == 0) g0[G_EPOCH] = epoch + 1;
        TSL(15);
        if (lane == 0) TL(0, 0);
        return;
    }

    const uint32_t tile = sm + OFF_RING + warp * TILE_BYTES;
    const uint32_t fullb = bars + (BAR_FULL + warp) * 8;
    const uint32_t pw = sm + OFF_P + warp * (2 * P_PITCH);
    if (warp < 8) {
        {
            uint32_t q0[8], q1[8];
            bar_sync(4, 288);
#pragma unroll
            for (int i = 0; i < 8; i++) {
                const float2 v = lds64f(sm + OFF_QS + (g & 1) * 256 + i * 32 + t4 * 8);
                q0[i] = __float_as_uint(v.x), q1[i] = __float_as_uint(v.y);
            }
            uint32_t sp = pw + (t4 & 1) * P_PITCH + ((t4 >> 1) * 8 + g) * 2;
#pragma unroll 1
            for (int it = 0; it < 8; it++, sp += 64) {
                const uint32_t ab = tile + (it & 1) * (8 * TILE_BYTES) + (lane & 15) * 128 + (((lane >> 4) ^ (lane & 7)) << 4);
                mbar_wait(fullb + (it & 1) * 64, (it >> 1) & 1);
                float acc[2][2][4] = {};
#pragma unroll
                for (int ks = 0; ks < 8; ks++)
#pragma unroll
                    for (int m = 0; m < 2; m++) {
                        uint32_t a[4];
                        ldsm4(a, (ab ^ ((ks & 3) << 5)) + (ks >> 2) * 4096 + m * 2048);
                        mma(acc[m][ks & 1], a[0], a[1], a[2], a[3], (ks & 1) ? q1[ks - 1] : q0[ks], (ks & 1) ? q1[ks] : q0[ks + 1]);
                    }
                __syncwarp();
                if (lane == 0) mbar_arrive(fullb + (it & 1) * 64 + (BAR_EMPTY - BAR_FULL) * 8);
#pragma unroll
                for (int m = 0; m < 2; m++) {
                    const float s = sel4(acc[m][0], t4) + sel4(acc[m][1], t4);
                    sts16(sp + m * 32, (uint16_t)pack2(rbf(s) * 0.08838834764831845f, 0.f));
                }
            }
        }
        __syncwarp();
        if (warp == 7) TSL(6);
        const uint32_t pa = pw + (lane >> 4) * P_PITCH + (lane & 15) * 32;
        const uint32_t sa = sm + OFF_SM + (lane >> 4) * 64;
        const uint4 v0 = lds128(pa), v1 = lds128(pa + 16);
        const uint32_t sv[8] = {v0.x, v0.y, v0.z, v0.w, v1.x, v1.y, v1.z, v1.w};
        float e[16];
        float m = -INFINITY;
#pragma unroll
        for (int i = 0; i < 8; i++) {
            e[2 * i] = blo(sv[i]);
            e[2 * i + 1] = bhi(sv[i]);
            m = fmaxf(m, fmaxf(e[2 * i], e[2 * i + 1]));
        }
#pragma unroll
        for (int o = 8; o; o >>= 1) m = fmaxf(m, __shfl_xor_sync(0xffffffffu, m, o));
        float l = 0.f;
#pragma unroll
        for (int i = 0; i < 16; i++) {
            e[i] = ex2((e[i] - m) * LOG2E);
            l += e[i];
        }
#pragma unroll
        for (int o = 8; o; o >>= 1) l += __shfl_xor_sync(0xffffffffu, l, o);
        if ((lane & 15) == 0) sts64(sa + warp * 8, __float_as_uint(m), __float_as_uint(l));
        bar_sync(2, NCW * 32);
        const float2 v = lds64f(sa + (lane & 7) * 8);
        float M = v.x;
#pragma unroll
        for (int o = 4; o; o >>= 1) M = fmaxf(M, __shfl_xor_sync(0xffffffffu, M, o));
        float L = v.y * ex2((v.x - M) * LOG2E);
#pragma unroll
        for (int o = 4; o; o >>= 1) L += __shfl_xor_sync(0xffffffffu, L, o);
        const float sc = ex2((m - M) * LOG2E) * rcp(L);
        sts128(pa, pack2(e[0] * sc, e[1] * sc), pack2(e[2] * sc, e[3] * sc), pack2(e[4] * sc, e[5] * sc), pack2(e[6] * sc, e[7] * sc));
        sts128(pa + 16, pack2(e[8] * sc, e[9] * sc), pack2(e[10] * sc, e[11] * sc), pack2(e[12] * sc, e[13] * sc), pack2(e[14] * sc, e[15] * sc));
        __syncwarp();
    } else {
        bar_sync(2, NCW * 32);
    }

    uint32_t sh[8] = {}, op[8] = {};
    {
        const uint32_t* const src_m = gs + G_M + (72 + warp * 8) * 32 + lane;
        fetch<8, 1>(src_m + 72 * 32, 32, op);
        get<8, 1>(src_m, 32, sh);
        get<8, 1>(src_m + 72 * 32, 32, op);
    }
    const int side = lds32(sm + OFF_WIN + 8), set = (epoch & 1) * G_SET, rr = (lane >> 4) * 8 + (lane & 7);
    const uint32_t dst_o = pin(4 * (set + dual(D_O + cta * 128) + (tid & 0x70) + (tid & 3) * 4 + ((tid >> 2) & 3)));
    const uint32_t src_o = pin(4 * (set + near(D_O + grp * 1024, side) + g * 128 + warp * 16 + t4 * 4));
    const int unit = warp < 8 ? 8 * sub + warp : 64 + sub;
    uint32_t rside[1] = {};
    get<1, 1>(gs + G_SIDE + unit * 8, 0, rside);
    const uint32_t dst_p = pin(4 * (near(d_part(unit), rside[0] - 1) + grp * 64 + lane * 2));
    const uint32_t src_x = pin(4 * (set + near(D_X1 + warp * 256, side) + lane));
    const uint32_t dst_a = pin(4 * (set + dual(D_ACT + (grp * 36 + (warp < 4 ? 4 * sub + warp : 32 + sub)) * 32) + lane));
    const uint32_t src_a = pin(4 * (set + near(D_ACT + (grp * 36 + 4 * warp) * 32, side) + lane));
    const uint32_t rowoff = pin(warp < 8 ? lane * 128 + ((warp ^ (lane & 7)) << 4) : lane * 16), rowstep = warp < 8 ? 4096 : 512;
    const uint32_t l16 = pin(lane * 16);
    const uint32_t ored = pin((warp * 1088 + (t4 & 1) * 576 + ((t4 >> 1) * 8 + g) * 4) | ((tid >> 6) * 64 + tid * 8) << 16);

    if (warp < 8) {
        float acc[8][4] = {};
        uint32_t pp = pw + (lane & 1) * P_PITCH + (lane >> 3) * 16;
#pragma unroll 1
        for (int it = 0; it < 8; it++, pp += 64) {
            const uint32_t ab = tile + (it & 1) * (8 * TILE_BYTES) + ((lane & 7) + (lane >> 4) * 8) * 128 + ((((lane >> 3) & 1) ^ (lane & 7)) << 4);
            uint32_t pb[4];
            ldsm4(pb, pp);
            mbar_wait(fullb + (it & 1) * 64, (it >> 1) & 1);
#pragma unroll
            for (int ks = 0; ks < 2; ks++)
#pragma unroll
                for (int m = 0; m < 8; m++) {
                    uint32_t a[4];
                    ldsm4t(a, (ab ^ ((m & 3) << 5)) + (m >> 2) * 4096 + ks * 2048);
                    mma(acc[m], a[0], a[1], a[2], a[3], pb[2 * ks], pb[2 * ks + 1]);
                }
            __syncwarp();
            if (lane == 0) mbar_arrive(fullb + (it & 1) * 64 + (BAR_EMPTY - BAR_FULL) * 8);
        }
        if (warp == 7) TSL(7);
        const uint32_t ra = sm + OFF_ORED + (ored & 0xffff);
#pragma unroll
        for (int m = 0; m < 8; m++) sts32(ra + m * 64, __float_as_uint(sel4(acc[m], t4)));
    }
    bar_sync(5, NCW * 32);
    if (warp < 4) {
        float s[2][2] = {};
#pragma unroll
        for (int w = 0; w < 8; w++) {
            const float2 v = lds64f(sm + OFF_ORED + w * 1088 + (ored >> 16));
            s[w & 1][0] += v.x;
            s[w & 1][1] += v.y;
        }
        put1d(at(g0, dst_o), pack2(s[0][0] + s[1][0], s[0][1] + s[1][1]));
        if (warp == 0) TSL(8);
    }

    project<0>(sm, at(g0, src_o), at(g0, dst_p), sm + (warp < 8 ? OFF_WO : OFF_OX) + rowoff, rowstep, l16, 288, warp, lane);
    if (warp == 0) TSL(9);

    {
        uint32_t h[8] = {}, mean2;
        float inv;
        get<1, 1>(at(g0, src_x), 0, reinterpret_cast<uint32_t(&)[1]>(h[0]));
        get<8, 1>(at(g0, src_x), 32, h);
        if (warp == 0) TSL(11);
        ln_partial(h, sm + OFF_ST + g * 80 + warp * 8, t4 == 0);
        bar_sync(3, 288);
        ln_combine(sm + OFF_ST + g * 80, mean2, inv);
#pragma unroll
        for (int i = 0; i < 8; i++) h[i] = modulate2(h[i], mean2, inv, sh[i], op[i]);
        sts128(sm + OFF_RED + warp * 1024 + lane * 16, h[0], h[1], h[2], h[3]);
        sts128(sm + OFF_RED + warp * 1024 + 512 + lane * 16, h[4], h[5], h[6], h[7]);
        if (warp == 0) TSL(12);
        if (cta < 72) {
            float r = 0.f;
#pragma unroll
            for (int i = 0; i < 8; i++) {
                const uint32_t wr = lds32(sm + OFF_WR + (warp * 32 + i * 4 + t4) * 4);
                r = fmaf(blo(h[i]), blo(wr), fmaf(bhi(h[i]), bhi(wr), r));
            }
            r = quad_sum(r);
            if (t4 == 0) sts32(sm + OFF_RT + g * 48 + warp * 4, __float_as_uint(r));
        }
    }
    bar_sync(3, 288);

    if (warp < (sub < 4 ? 5 : 4)) {
        const int pl = ((lane >> 3) & 1) ^ P.zg;
        const uint32_t ks = warp < 4 ? 1024 : 256;
        uint32_t aa = sm + (warp < 4 ? OFF_GU + rr * 64 + (((lane & 6) << 3) ^ (warp << 4)) : OFF_GX + rr * 16) + pl * 4 * ks;
        float acc[2][4] = {};
#pragma unroll 1
        for (int i = 0; i < 9; i++, aa += 8 * ks) {
            const uint4 b0 = lds128(sm + OFF_RED + i * 1024 + lane * 16), b1 = lds128(sm + OFF_RED + i * 1024 + 512 + lane * 16);
            uint32_t a[4][4];
            mbar_wait(bars + (BAR_GU + i) * 8, 0);
#pragma unroll
            for (int k = 0; k < 4; k++) ldsm4t(a[k], aa + k * ks);
            mma(acc[0], a[0][0], a[0][1], a[0][2], a[0][3], b0.x, b0.y);
            mma(acc[1], a[1][0], a[1][1], a[1][2], a[1][3], b0.z, b0.w);
            mma(acc[0], a[2][0], a[2][1], a[2][2], a[2][3], b1.x, b1.y);
            mma(acc[1], a[3][0], a[3][1], a[3][2], a[3][3], b1.z, b1.w);
        }
        if (warp == 1) TSL(17);
        const uint32_t gate = pack2(acc[0][0] + acc[1][0], acc[0][1] + acc[1][1]), up = pack2(acc[0][2] + acc[1][2], acc[0][3] + acc[1][3]);
        put1d(at(g0, dst_a), movm(bmul2(silu2(gate), up)));
        if (warp == 1) TSL(13);
    } else {
        mbar_wait(bars + (BAR_GU + 8) * 8, 0);
    }

    project<1>(sm, at(g0, src_a), at(g0, dst_p), sm + (warp < 8 ? OFF_WD : OFF_DX) + rowoff, rowstep, l16, cta < 72 ? 320 : 288, warp, lane);
    if (warp == 0) TSL(14);
    if (warp == 8) TSL(27);

    if (cta < 72) {
        const uint32_t ga = sm + OFF_GB + warp * 1024 + ((lane >> 3) & 1) * 256 + (lane >> 4) * 128 + (lane & 7) * 16;
        float acc[2][4] = {};
        mbar_wait(bars + BAR_GB * 8, 0);
        if (warp == 0) TSL(22);
#pragma unroll
        for (int i = 0; i < 2; i++) {
            uint32_t w[4];
            ldsm4t(w, ga + i * 512);
            mma(acc[0], w[0], w[1], w[2], w[3], sc[4 * i], sc[4 * i + 1]);
            mma(acc[1], w[0], w[1], w[2], w[3], sc[4 * i + 2], sc[4 * i + 3]);
        }
        sts64(sm + OFF_RED + 9216 + tid * 8, __float_as_uint(acc[0][0] + acc[1][2]), __float_as_uint(acc[0][1] + acc[1][3]));
        if (warp) {
            bar_arrive(7, 288);
        } else {
            bar_sync(7, 288);
            float s[2][2] = {};
#pragma unroll
            for (int w = 0; w < 9; w++) {
                const float2 v = lds64f(sm + OFF_RED + 9216 + tid * 8 + w * 256);
                s[w & 1][0] += v.x;
                s[w & 1][1] += v.y;
            }
            sts32(sm + OFF_QS + lane * 4, movm(pack2(s[0][0] + s[1][0], s[0][1] + s[1][1])));
            __syncwarp();
            bar_arrive(9, 64);
            TSL(25);
        }
    }
}

typedef CUresult (*EncodeFn)(CUtensorMap*, CUtensorMapDataType, cuuint32_t, void*, const cuuint64_t*, const cuuint64_t*,
                             const cuuint32_t*, const cuuint32_t*, CUtensorMapInterleave, CUtensorMapSwizzle,
                             CUtensorMapL2promotion, CUtensorMapFloatOOBfill);

void make_map(EncodeFn enc, CUtensorMap* m, void* p, int cols, int rows, int pitch, int bc, int br, int bp, int planes, size_t pstride,
              CUtensorMapSwizzle sw, int promo) {
    cuuint64_t dims[3] = {(cuuint64_t)cols, (cuuint64_t)rows, (cuuint64_t)planes};
    cuuint64_t strides[2] = {(cuuint64_t)pitch * 2, (cuuint64_t)pstride};
    cuuint32_t box[3] = {(cuuint32_t)bc, (cuuint32_t)br, (cuuint32_t)bp};
    cuuint32_t es[3] = {1, 1, 1};
    enc(m, CU_TENSOR_MAP_DATA_TYPE_BFLOAT16, 3, p, dims, strides, box, es, CU_TENSOR_MAP_INTERLEAVE_NONE, sw,
        (CUtensorMapL2promotion)promo, CU_TENSOR_MAP_FLOAT_OOB_FILL_NONE);
}

}

extern "C" void kernel_launch(void* const* d_in, const int* in_sizes, int n_in, void* d_out, int out_size) {
    static EncodeFn enc = nullptr;
    static uint32_t* scratch = nullptr;
    if (!enc) {
        void* fn = nullptr;
        cudaDriverEntryPointQueryResult st;
        cudaGetDriverEntryPoint("cuTensorMapEncodeTiled", &fn, cudaEnableDefault, &st);
        enc = (EncodeFn)fn;
        cudaGetSymbolAddress(&fn, g_scratch);
        scratch = (uint32_t*)(((uintptr_t)fn + 8 * G_SET - 1) & ~(uintptr_t)(8 * G_SET - 1));
        cudaFuncSetAttribute(fused_kernel, cudaFuncAttributeMaxDynamicSharedMemorySize, SMEM_BYTES);
    }
    Params P;
    Maps T;
    const CUtensorMapSwizzle none = CU_TENSOR_MAP_SWIZZLE_NONE;
    const int PROMO_W = CU_TENSOR_MAP_L2_PROMOTION_L2_128B, PROMO_KV = CU_TENSOR_MAP_L2_PROMOTION_L2_256B;
    make_map(enc, &T.m[M_K], d_in[1], 64, NB * HKV * SK, DH, 64, 32, 2, 2, 128, CU_TENSOR_MAP_SWIZZLE_128B, PROMO_KV);
    make_map(enc, &T.m[M_V], d_in[2], 64, NB * HKV * SK, DH, 64, 32, 2, 2, 128, CU_TENSOR_MAP_SWIZZLE_128B, PROMO_KV);
    make_map(enc, &T.m[M_WQ], d_in[3], HQ * DH, DM, HQ * DH, 32, 192, 1, 1, 16, CU_TENSOR_MAP_SWIZZLE_64B, PROMO_W);
    make_map(enc, &T.m[M_WM], d_in[11], 6 * DM, DM, 6 * DM, 32, 192, 1, 1, 16, CU_TENSOR_MAP_SWIZZLE_64B, PROMO_W);
    make_map(enc, &T.m[M_WA], d_in[11], DM, DM, 6 * DM, 16, 192, 2, 2, DM * 2, CU_TENSOR_MAP_SWIZZLE_32B, PROMO_W);
    make_map(enc, &T.m[M_GB], d_in[11], 6 * DM, DM, 6 * DM, 8, 192, 1, 1, 16, none, PROMO_W);
    char *wg = (char*)d_in[7], *wu = (char*)d_in[8], *wo = (char*)d_in[4], *wd = (char*)d_in[9];
    P.zg = wg > wu;
    P.zo = wo > wd;
    const size_t sg = P.zg ? wg - wu : wu - wg, so = P.zo ? wo - wd : wd - wo;
    make_map(enc, &T.m[M_GU], P.zg ? wu : wg, FF, DM, FF, 32, 64, 2, 2, sg, CU_TENSOR_MAP_SWIZZLE_64B, PROMO_W);
    make_map(enc, &T.m[M_GX], P.zg ? wu : wg, FF, DM, FF, 8, 64, 2, 2, sg, none, PROMO_W);
    make_map(enc, &T.m[M_OD], P.zo ? wd : wo, DM, FF, DM, 64, 64, 1, 2, so, CU_TENSOR_MAP_SWIZZLE_128B, PROMO_W);
    make_map(enc, &T.m[M_OX], P.zo ? wd : wo, DM, FF, DM, 8, 64, 1, 2, so, none, PROMO_W);
    P.x = (const __nv_bfloat16*)d_in[0];
    P.wr = (const __nv_bfloat16*)d_in[6];
    P.c = (const __nv_bfloat16*)d_in[10];
    P.k = (const __nv_bfloat16*)d_in[1];
    P.out = (__nv_bfloat16*)d_out;
    P.scratch = scratch;
    void* args[2] = {&P, &T};
    cudaLaunchCooperativeKernel((const void*)fused_kernel, dim3(NCTA), dim3(NTHREADS), args, SMEM_BYTES, cudaStreamPerThread);
}
```

```cpp
#include <cuda_runtime.h>
#include <cuda_bf16.h>
#include <cuda.h>
#include <stdint.h>

typedef unsigned long long u64;

#define TAU 568
#define TAU_W 655
#define L_KV 3200
#define L_WO 3000
#define L_GU 3000
#define L_WD 2900
#define L_LAST 50
#define L_GB 2800
#define W_0 6
#define W_LO 2
#define W_HI 8
#define W_HT 5
#define T_PACE 20
#define NK0 3
#define NK1 2
#define PFK 2
#define T_CLEAR 116
#define NPING0 4
#define NPING1 10

namespace {

constexpr int NB = 8, DM = 576, HQ = 32, HKV = 16, SK = 8192, WIN = 2048, DH = 128, FF = 4608;
constexpr int NCTA = 128;
constexpr int NCW = 10;
constexpr int NTHREADS = (NCW + 2) * 32;
constexpr int TILE_BYTES = 8192, NT = 64;
constexpr int SPIN_LIMIT = 1 << 22;

constexpr int OFF_RING = 0;
constexpr int OFF_WM = 121856;
constexpr int OFF_WQ = OFF_WM + 36864;
constexpr int OFF_GU = 0;
constexpr int OFF_WD = 73728;
constexpr int OFF_GB = 114688;
constexpr int OFF_OX = 131072;
constexpr int OFF_DX = OFF_OX + 4096;
constexpr int OFF_GX = OFF_DX + 4608;
constexpr int OFF_WO = OFF_WQ;
constexpr int OFF_P = OFF_WQ + 36864;
constexpr int P_PITCH = 528;
constexpr int OFF_RED = OFF_P + 16 * P_PITCH;
constexpr int OFF_ORED = OFF_RED + 5 * 4608 - 8704;
constexpr int OFF_ST = OFF_RED + 5 * 4608;
constexpr int OFF_SM = OFF_ST + 640;
constexpr int OFF_RT = OFF_SM + 128;
constexpr int OFF_QS = OFF_RT + 384;
constexpr int OFF_WR = OFF_QS + 512;
constexpr int OFF_WIN = OFF_WR + 1152;
constexpr int OFF_BAR = OFF_WIN + 16;
constexpr int BAR_FULL = 6, BAR_WO = 22, BAR_GU = 26, BAR_WD = 35, BAR_EMPTY = 40, BAR_SYNC = 56, BAR_WMF = 59, BAR_GB = 60, NBAR = 70;
constexpr int SMEM_BYTES = OFF_BAR + NBAR * 8;

constexpr int D_X1 = 0;
constexpr int D_O = 3072;
constexpr int D_ACT = D_O + 512 * 32;
constexpr int D_H = D_ACT + 576 * 32;
constexpr int D_Q = D_H + 3072;
constexpr int G_M = 2 * (D_Q + NB * HQ * 64);
constexpr int G_SIDE = G_M + 216 * 32;
constexpr int G_CNT = G_SIDE + 72 * 8;
constexpr int G_SET = 1 << 18;
__device__ __forceinline__ int d_part(int unit) { return (64 + unit + (unit & 64)) * 1024; }
constexpr int D_PING = 200 * 1024;
constexpr int G_EPOCH = 201 * 2048;
static_assert(G_CNT < 64 * 2048, "scratch layout");
__device__ uint32_t g_scratch[4 * G_SET];
__device__ __forceinline__ int dual(int w) { return w + (w & ~1023); }
__device__ __forceinline__ int near(int w, int side) { return dual(w) + (((__popc(w & 0x16400) ^ side) & 1) << 10); }

#define TL(i, back)
#define TI(i)
#define TS(i)
#define TSL(i)

enum { M_K, M_V, M_GU, M_GX, M_OD, M_OX, M_WQ, M_WM, M_WA, M_GB, NMAP };
struct Params {
    const __nv_bfloat16 *c, *x, *k;
    __nv_bfloat16* out;
    uint32_t* scratch;
    const __nv_bfloat16* wr;
    int zg, zo;
};
struct Maps {
    CUtensorMap m[NMAP];
};

__device__ __forceinline__ void mbar_init(uint32_t bar, int cnt) {
    asm volatile("mbarrier.init.shared::cta.b64 [%0], %1;" ::"r"(bar), "r"(cnt));
}
__device__ __forceinline__ void mbar_expect(uint32_t bar, uint32_t bytes) {
    asm volatile("mbarrier.arrive.expect_tx.shared::cta.b64 _, [%0], %1;" ::"r"(bar), "r"(bytes) : "memory");
}
__device__ __forceinline__ void mbar_arrive(uint32_t bar) {
    asm volatile("mbarrier.arrive.shared::cta.b64 _, [%0];" ::"r"(bar) : "memory");
}
__device__ __forceinline__ void mbar_wait(uint32_t bar, uint32_t parity) {
    asm volatile("{\n.reg .pred p;\n.reg .u32 c;\n"
                 "mbarrier.try_wait.parity.shared::cta.b64 p, [%0], %1;\n@p bra DONE;\nmov.u32 c, %2;\n"
                 "AGAIN:\nmbarrier.try_wait.parity.shared::cta.b64 p, [%0], %1;\nsub.u32 c, c, 1;\n"
                 "setp.eq.or.u32 p, c, 0, p;\n@!p bra AGAIN;\nDONE:\n}"
                 ::"r"(bar), "r"(parity), "n"(SPIN_LIMIT) : "memory");
}
__device__ __forceinline__ bool mbar_test(uint32_t bar, uint32_t parity) {
    uint32_t ok;
    asm volatile("{\n.reg .pred p;\nmbarrier.test_wait.parity.shared::cta.b64 p, [%1], %2;\nselp.u32 %0, 1, 0, p;\n}"
                 : "=r"(ok) : "r"(bar), "r"(parity) : "memory");
    return ok;
}
__device__ __forceinline__ void tma3d_hint(uint32_t dst, const CUtensorMap* m, int x, int y, int z, uint32_t bar, u64 pol) {
    asm volatile("cp.async.bulk.tensor.3d.shared::cluster.global.mbarrier::complete_tx::bytes.L2::cache_hint"
                 " [%0], [%1, {%2, %3, %4}], [%5], %6;"
                 ::"r"(dst), "l"(m), "r"(x), "r"(y), "r"(z), "r"(bar), "l"(pol) : "memory");
}
__device__ __forceinline__ void tma3d(uint32_t dst, const CUtensorMap* m, int x, int y, int z, uint32_t bar) {
    asm volatile("cp.async.bulk.tensor.3d.shared::cluster.global.mbarrier::complete_tx::bytes [%0], [%1, {%2, %3, %4}], [%5];"
                 ::"r"(dst), "l"(m), "r"(x), "r"(y), "r"(z), "r"(bar) : "memory");
}
__device__ __forceinline__ void bar_sync(int id, int n) { asm volatile("bar.sync %0, %1;" ::"r"(id), "r"(n) : "memory"); }
__device__ __forceinline__ void bar_arrive(int id, int n) { asm volatile("bar.arrive %0, %1;" ::"r"(id), "r"(n) : "memory"); }
__device__ __forceinline__ void ldsm4(uint32_t (&r)[4], uint32_t a) {
    asm volatile("ldmatrix.sync.aligned.m8n8.x4.shared.b16 {%0,%1,%2,%3}, [%4];"
                 : "=r"(r[0]), "=r"(r[1]), "=r"(r[2]), "=r"(r[3]) : "r"(a) : "memory");
}
__device__ __forceinline__ void ldsm4t(uint32_t (&r)[4], uint32_t a) {
    asm volatile("ldmatrix.sync.aligned.m8n8.x4.trans.shared.b16 {%0,%1,%2,%3}, [%4];"
                 : "=r"(r[0]), "=r"(r[1]), "=r"(r[2]), "=r"(r[3]) : "r"(a) : "memory");
}
__device__ __forceinline__ void mma(float (&c)[4], uint32_t a0, uint32_t a1, uint32_t a2, uint32_t a3, uint32_t b0, uint32_t b1) {
    asm volatile("mma.sync.aligned.m16n8k16.row.col.f32.bf16.bf16.f32 {%0,%1,%2,%3}, {%4,%5,%6,%7}, {%8,%9}, {%0,%1,%2,%3};"
                 : "+f"(c[0]), "+f"(c[1]), "+f"(c[2]), "+f"(c[3])
                 : "r"(a0), "r"(a1), "r"(a2), "r"(a3), "r"(b0), "r"(b1));
}
__device__ __forceinline__ uint32_t movm(uint32_t a) {
    uint32_t d;
    asm volatile("movmatrix.sync.aligned.m8n8.trans.b16 %0, %1;" : "=r"(d) : "r"(a));
    return d;
}
__device__ __forceinline__ uint32_t lds32(uint32_t a) { uint32_t v; asm volatile("ld.volatile.shared.b32 %0, [%1];" : "=r"(v) : "r"(a) : "memory"); return v; }
__device__ __forceinline__ float2 lds64f(uint32_t a) { float2 v; asm volatile("ld.shared.v2.f32 {%0,%1}, [%2];" : "=f"(v.x), "=f"(v.y) : "r"(a) : "memory"); return v; }
__device__ __forceinline__ uint4 lds128(uint32_t a) { uint4 v; asm volatile("ld.shared.v4.b32 {%0,%1,%2,%3}, [%4];" : "=r"(v.x), "=r"(v.y), "=r"(v.z), "=r"(v.w) : "r"(a) : "memory"); return v; }
__device__ __forceinline__ void sts32(uint32_t a, uint32_t v) { asm volatile("st.shared.b32 [%0], %1;" ::"r"(a), "r"(v) : "memory"); }
__device__ __forceinline__ void sts16(uint32_t a, uint16_t v) { asm volatile("st.shared.b16 [%0], %1;" ::"r"(a), "h"(v) : "memory"); }
__device__ __forceinline__ void sts64(uint32_t a, uint32_t x, uint32_t y) { asm volatile("st.shared.v2.b32 [%0], {%1,%2};" ::"r"(a), "r"(x), "r"(y) : "memory"); }
__device__ __forceinline__ void sts128(uint32_t a, uint32_t x, uint32_t y, uint32_t z, uint32_t w) {
    asm volatile("st.shared.v4.b32 [%0], {%1,%2,%3,%4};" ::"r"(a), "r"(x), "r"(y), "r"(z), "r"(w) : "memory");
}
__device__ __forceinline__ void sts128f(uint32_t a, const float (&c)[4]) {
    sts128(a, __float_as_uint(c[0]), __float_as_uint(c[1]), __float_as_uint(c[2]), __float_as_uint(c[3]));
}

__device__ __forceinline__ float sel4(const float (&c)[4], int t) { return (t & 2) ? ((t & 1) ? c[3] : c[2]) : ((t & 1) ? c[1] : c[0]); }

template <int LUT>
__device__ __forceinline__ uint32_t lop3(uint32_t a, uint32_t b, uint32_t c) {
    uint32_t d;
    asm("lop3.b32 %0, %1, %2, %3, %4;" : "=r"(d) : "r"(a), "r"(b), "r"(c), "n"(LUT));
    return d;
}
__device__ __forceinline__ uint32_t pin(uint32_t v) { return __shfl_xor_sync(0xffffffffu, v, 0); }
template <typename T>
__device__ __forceinline__ T* at(T* base, uint32_t bytes) { return (T*)((const char*)base + bytes); }

__device__ __forceinline__ uint32_t clock32(uint32_t dep) {
    uint32_t t;
    asm volatile("{\n.reg .pred p;\nsetp.eq.u32 p, %1, 0x9e3779b9;\n@p nanosleep.u32 1;\nmov.u32 %0, %clock;\n}" : "=r"(t) : "r"(dep) : "memory");
    return t;
}

__device__ __forceinline__ uint32_t nz(uint32_t v) { return v ? v : 0x80000000u; }
__device__ __forceinline__ void st1(uint32_t* p, uint32_t a) { asm volatile("st.relaxed.gpu.global.b32 [%0], %1;" ::"l"(p), "r"(a) : "memory"); }
__device__ __forceinline__ void st2(uint32_t* p, uint32_t a, uint32_t b) {
    asm volatile("st.relaxed.gpu.global.v2.b32 [%0], {%1,%2};" ::"l"(p), "r"(a), "r"(b) : "memory");
}
__device__ __forceinline__ void zero4(uint32_t* p) { asm volatile("st.relaxed.gpu.global.v4.b32 [%0], {%1,%1,%1,%1};" ::"l"(p), "r"(0) : "memory"); }
__device__ __forceinline__ void put1d(uint32_t* p, uint32_t a) { a = nz(a), st1(p, a), st1(p + 1024, a); }
__device__ __forceinline__ void put2d(uint32_t* p, uint32_t a, uint32_t b) { a = nz(a), b = nz(b), st2(p, a, b), st2(p + 1024, a, b); }
__device__ __forceinline__ uint32_t ld1(const uint32_t* p) {
    uint32_t v;
    asm volatile("ld.relaxed.gpu.global.b32 %0, [%1];" : "=r"(v) : "l"(p) : "memory");
    return v;
}
template <int N, int V>
__device__ __forceinline__ void fetch(const uint32_t* p, int stride, uint32_t (&a)[N * V]) {
#pragma unroll
    for (int i = 0; i < N; i++) {
        if (V == 1)
            asm volatile("{\n.reg .pred p;\nsetp.eq.u32 p, %0, 0;\n@p ld.relaxed.gpu.global.b32 %0, [%1];\n}"
                         : "+r"(a[i]) : "l"(p + i * stride) : "memory");
        if (V == 4)
            asm volatile("{\n.reg .pred p;\nsetp.eq.u32 p, %4, 0;\n@p ld.relaxed.gpu.global.v4.b32 {%0,%1,%2,%3}, [%5];\n}"
                         : "+r"(a[V * i]), "+r"(a[V * i + V / 4]), "+r"(a[V * i + V / 2]), "+r"(a[V * i + V - 1])
                         : "r"(min(min(a[V * i], a[V * i + V / 4]), min(a[V * i + V / 2], a[V * i + V - 1]))), "l"(p + i * stride) : "memory");
    }
}
template <int N>
__device__ __forceinline__ bool missing(const uint32_t (&a)[N]) {
    uint32_t lo = a[0];
#pragma unroll
    for (int i = 1; i < N; i++) lo = min(lo, a[i]);
    return __any_sync(0xffffffffu, lo == 0);
}
template <int N, int V>
__device__ __forceinline__ void get(const uint32_t* p, int stride, uint32_t (&a)[N * V]) {
    int it = 0;
    do fetch<N, V>(p, stride, a);
    while (missing(a) & (++it < SPIN_LIMIT));
}
__device__ __forceinline__ void cp16(uint32_t dst, const void* src) {
    asm volatile("cp.async.cg.shared.global [%0], [%1], 16;" ::"r"(dst), "l"(src) : "memory");
}

__device__ __forceinline__ uint32_t pack2(float lo, float hi) {
    uint32_t r;
    asm("cvt.rn.bf16x2.f32 %0, %1, %2;" : "=r"(r) : "f"(hi), "f"(lo));
    return r;
}
__device__ __forceinline__ float rbf(float x) { return __uint_as_float(pack2(0.f, x)); }
__device__ __forceinline__ float blo(uint32_t v) { return __uint_as_float(v << 16); }
__device__ __forceinline__ float bhi(uint32_t v) { return __uint_as_float(v & 0xffff0000u); }
__device__ __forceinline__ uint32_t badd2(uint32_t a, uint32_t b) { uint32_t r; asm("add.rn.bf16x2 %0, %1, %2;" : "=r"(r) : "r"(a), "r"(b)); return r; }
__device__ __forceinline__ uint32_t bsub2(uint32_t a, uint32_t b) { uint32_t r; asm("sub.rn.bf16x2 %0, %1, %2;" : "=r"(r) : "r"(a), "r"(b)); return r; }
__device__ __forceinline__ uint32_t bmul2(uint32_t a, uint32_t b) { uint32_t r; asm("mul.rn.bf16x2 %0, %1, %2;" : "=r"(r) : "r"(a), "r"(b)); return r; }
__device__ __forceinline__ float ex2(float x) { float r; asm("ex2.approx.ftz.f32 %0, %1;" : "=f"(r) : "f"(x)); return r; }
__device__ __forceinline__ float rcp(float x) { float r; asm("rcp.approx.ftz.f32 %0, %1;" : "=f"(r) : "f"(x)); return r; }
__device__ __forceinline__ float sqrt_f(float x) { float r; asm("sqrt.approx.ftz.f32 %0, %1;" : "=f"(r) : "f"(x)); return r; }
constexpr float LOG2E = 1.4426950408889634f;
constexpr uint32_t ONE2 = 0x3f803f80u;
__device__ __forceinline__ float sigmoid_f(float x) { return rcp(1.0f + ex2(-LOG2E * x)); }
__device__ __forceinline__ uint32_t silu2(uint32_t v) {
    const float a = blo(v), b = bhi(v);
    return pack2(a * sigmoid_f(a), b * sigmoid_f(b));
}
__device__ __forceinline__ float quad_sum(float v) {
    v += __shfl_xor_sync(0xffffffffu, v, 1);
    return v + __shfl_xor_sync(0xffffffffu, v, 2);
}
__device__ __forceinline__ void ln_partial(const uint32_t (&v)[8], uint32_t dst, bool writer) {
    float s0 = 0.f, s1 = 0.f;
#pragma unroll
    for (int i = 0; i < 8; i++) {
        s0 += blo(v[i]);
        s1 += bhi(v[i]);
    }
    const float mean = quad_sum(s0 + s1) * (1.0f / 64);
    s0 = s1 = 0.f;
#pragma unroll
    for (int i = 0; i < 8; i++) {
        const float a = blo(v[i]) - mean, b = bhi(v[i]) - mean;
        s0 = fmaf(a, a, s0);
        s1 = fmaf(b, b, s1);
    }
    s0 = quad_sum(s0 + s1);
    if (writer) sts64(dst, __float_as_uint(mean), __float_as_uint(s0));
}
__device__ __forceinline__ void ln_combine(uint32_t src, uint32_t& mean2, float& inv) {
    float m[10], q0 = 0.f, q1 = 0.f, s = 0.f;
#pragma unroll
    for (int i = 0; i < 5; i++) {
        const uint4 v = lds128(src + i * 16);
        m[2 * i] = __uint_as_float(v.x);
        m[2 * i + 1] = __uint_as_float(v.z);
        q0 += __uint_as_float(v.y);
        if (i < 4) q1 += __uint_as_float(v.w);
    }
    const float mean = (((m[0] + m[1]) + (m[2] + m[3])) + ((m[4] + m[5]) + (m[6] + m[7])) + m[8]) * (1.0f / 9);
#pragma unroll
    for (int i = 0; i < 9; i++) s = fmaf(m[i] - mean, m[i] - mean, s);
    const float var = fmaf(s, 64.f, q0 + q1) * (1.0f / DM);
    mean2 = pack2(mean, mean);
    inv = rcp(rbf(sqrt_f(rbf(rbf(var) + 1e-5f))));
}
__device__ __forceinline__ uint32_t modulate2(uint32_t x, uint32_t mean2, float inv, uint32_t shift, uint32_t onep) {
    const uint32_t d = bsub2(x, mean2);
    return badd2(bmul2(pack2(blo(d) * inv, bhi(d) * inv), onep), shift);
}
template <int N>
__device__ __forceinline__ void sum_frags(float (&c)[4], uint32_t addr, int stride) {
#pragma unroll
    for (int w = 0; w < N; w++) {
        const uint4 v = lds128(addr + w * stride);
        c[0] += __uint_as_float(v.x); c[1] += __uint_as_float(v.y);
        c[2] += __uint_as_float(v.z); c[3] += __uint_as_float(v.w);
    }
}

template <int ST>
__device__ __forceinline__ void project(uint32_t sm, const uint32_t* src, uint32_t* dst, uint32_t wa, uint32_t ws, uint32_t l16, int nsync, int warp, int lane) {
    constexpr int NW = ST ? 9 : 8, NI = ST ? 5 : 4;
    const uint32_t wbar = sm + OFF_BAR + (ST ? BAR_WD : BAR_WO) * 8, stage = sm + (ST ? OFF_WO : OFF_P) + l16;
    if (warp < NW) {
        uint32_t b[4] = {};
        if (ST) get<4, 1>(src, 32, b);
        else get<1, 4>(src, 0, b);
        if (warp == 0) TSL(ST ? 24 : 21);
        sts128(stage + warp * 512, b[0], b[2], b[1], b[3]);
    }
    bar_sync(ST ? 6 : 3, nsync);
    float acc[4][4] = {};
#pragma unroll
    for (int j = 0; j < NI; j++) {
        const int i0 = j == 4 ? 8 : ST ? 2 * ((j + 3) & 3) : 2 * j, n = j == 4 ? 1 : 2;
        uint32_t w[2][4];
        uint4 f[2];
#pragma unroll
        for (int i = 0; i < n; i++) f[i] = lds128(stage + (i0 + i) * 512);
        mbar_wait(wbar + j * 8, 0);
#pragma unroll
        for (int i = 0; i < n; i++) ldsm4t(w[i], wa + (i0 + i) * ws);
#pragma unroll
        for (int i = 0; i < n; i++) {
            mma(acc[2 * i], f[i].x, f[i].y, f[i].z, f[i].w, w[i][0], w[i][1]);
            mma(acc[2 * i + 1], f[i].x, f[i].y, f[i].z, f[i].w, w[i][2], w[i][3]);
        }
    }
    const float s0 = (acc[2][0] + acc[3][2]) + (acc[0][0] + acc[1][2]), s1 = (acc[2][1] + acc[3][3]) + (acc[0][1] + acc[1][3]);
    st2(dst, (__float_as_uint(s0) | 1) ^ ST, (__float_as_uint(s1) | 1) ^ ST);
}

template <int ST, typename F>
__device__ __forceinline__ uint32_t reduce16(const uint32_t* src, F arrived) {
    uint32_t a[32] = {}, any;
    int it = 0;
    uint32_t bad[16];
#pragma unroll
    for (int i = 0; i < 16; i++) bad[i] = 1;
    do {
#pragma unroll
        for (int i = 0; i < 16; i++)
            asm volatile("{\n.reg .pred p;\nsetp.ne.u32 p, %2, 0;\n@p ld.relaxed.gpu.global.v2.b32 {%0,%1}, [%3];\n}"
                         : "+r"(a[2 * i]), "+r"(a[2 * i + 1]) : "r"(bad[i]), "l"(src + i * 64) : "memory");
#pragma unroll
        for (int i = 0; i < 16; i++) bad[i] = lop3<ST ? 0xa8 : 0x2a>(a[2 * i], a[2 * i + 1], 1);
        any = lop3<0xfe>(lop3<0xfe>(lop3<0xfe>(bad[0], bad[1], bad[2]), lop3<0xfe>(bad[3], bad[4], bad[5]), lop3<0xfe>(bad[6], bad[7], bad[8])),
                         lop3<0xfe>(lop3<0xfe>(bad[9], bad[10], bad[11]), lop3<0xfe>(bad[12], bad[13], bad[14]), bad[15]), 0);
    } while (__any_sync(0xffffffffu, any != 0) & (++it < SPIN_LIMIT));
    arrived();
    float f[8];
#pragma unroll
    for (int i = 0; i < 8; i++)
        f[i] = (__uint_as_float(a[i]) + __uint_as_float(a[i + 8])) + (__uint_as_float(a[i + 16]) + __uint_as_float(a[i + 24]));
    return pack2((f[0] + f[2]) + (f[4] + f[6]), (f[1] + f[3]) + (f[5] + f[7]));
}

__global__ void __launch_bounds__(NTHREADS, 1) fused_kernel(const Params P, const __grid_constant__ Maps T) {
    extern __shared__ __align__(1024) char smem_raw[];
    constexpr uint32_t sm = 1024;
    const int tid = threadIdx.x, lane = tid & 31;
    const int cta = blockIdx.x, grp = cta >> 3, sub = cta & 7;
    const uint32_t bars = sm + OFF_BAR;
    const int row0 = (sub * HKV + grp) * SK + (SK - WIN);
    if (tid >> 5 == 9) {
#pragma unroll
        for (int i = 0; i < PFK; i++) asm volatile("prefetch.global.L2 [%0];" ::"l"(P.k + (size_t)row0 * DH + (lane + i * 32) * 64) : "memory");
    }
    u64 pol;
    asm volatile("createpolicy.fractional.L2::evict_first.b64 %0, 1.0;" : "=l"(pol));
    if (tid == NCW * 32) {
        TS(0);
        const int n0 = cta < 90 ? 0 : 3;
#pragma unroll
        for (int i = 0; i < 6; i++) mbar_init(bars + i * 8, 1);
        asm volatile("fence.mbarrier_init.release.cluster;" ::: "memory");
#pragma unroll
        for (int i = 0; i < 3; i++) {
            mbar_expect(bars + (n0 + i) * 8, 12288);
            tma3d(sm + OFF_WM + (n0 + i) * 12288, &T.m[cta < 36 ? M_WA : cta < 90 ? M_WM : M_WQ], cta < 36 ? 16 * cta : 32 * cta,
                  i * 192, 0, bars + (n0 + i) * 8);
            TI(n0 + i);
        }
        TS(26);
    }
    if (tid == NCW * 32 + 32) {
#pragma unroll
        for (int i = 0; i < 4; i++) mbar_init(bars + (BAR_FULL + i) * 8, 1);
        asm volatile("fence.mbarrier_init.release.cluster;" ::: "memory");
#pragma unroll
        for (int t = 0; t < NK0; t++) {
            mbar_expect(bars + (BAR_FULL + t) * 8, TILE_BYTES);
            tma3d_hint(sm + OFF_RING + t * TILE_BYTES, &T.m[M_K], 0, row0 + t * 32, 0, bars + (BAR_FULL + t) * 8, pol);
            TI(6 + t);
        }
    }
    if (tid < 288 && cta < 90) {
#pragma unroll
        for (int i = 0; i < 2; i++) {
            const int row = (lane >> 3) + 4 * i, so = row * DM + (tid >> 5) * 64 + (lane & 7) * 8;
            const uint32_t d = sm + OFF_RED + (tid >> 5) * 2048 + row * 128 + (((lane & 7) ^ row) << 4);
            cp16(d, P.c + so);
            if (cta < 36) cp16(d + 1024, P.x + so);
        }
    }
    uint32_t* const g0 = P.scratch;
    const uint32_t epoch = ld1(g0 + G_EPOCH);
    const int warp = __shfl_sync(0xffffffffu, tid >> 5, 0);

    if (warp >= NCW) {
        const int pw = warp - NCW;
        bar_arrive(1, (NCW + 1) * 32);
        if (pw && lane < M_WQ) asm volatile("prefetch.tensormap [%0];" ::"l"(&T.m[M_WQ - lane]) : "memory");
        if (tid == NCW * 32) sts32(sm + OFF_WIN, 0);
        __syncwarp();
        bar_sync(15, NTHREADS);
        if (lane == 0) {
            if (pw == 0 && cta < 90) {
#pragma unroll 1
                for (int n = 3; n < 6; n++) {
                    mbar_expect(bars + n * 8, 12288);
                    mbar_wait(bars + (n - 3) * 8, 0);
                    tma3d(sm + OFF_WM + n * 12288, &T.m[M_WQ], 32 * cta, (n - 3) * 192, 0, bars + n * 8);
                    TI(n);
                }
            }
#pragma unroll 1
            for (int t = NK0 + (1 - pw) * NK1; t < NK0 + NK1 + 3 * (1 - pw); t++) {
                mbar_expect(bars + (BAR_FULL + t) * 8, TILE_BYTES);
                mbar_wait(bars + (t + (pw ? BAR_FULL - NK1 : 3 - NK0 - NK1)) * 8, 0);
                tma3d_hint(sm + OFF_RING + t * TILE_BYTES, &T.m[M_K], 0, row0 + t * 32, 0, bars + (BAR_FULL + t) * 8, pol);
                TI(6 + t);
            }
            if (pw == 0) {
                auto on_time = [&](int due, uint32_t bar, uint32_t parity) {
                    uint32_t origin;
                    do origin = lds32(sm + OFF_WIN);
                    while (origin && (int)(clock32(0) - origin - due) < 0 && !mbar_test(bar, parity));
                };
#pragma unroll 1
                for (int t = NK0 + NK1 + 3; t < 2 * NT; t++) {
                    if (t == 14 && cta < 90) mbar_wait(bars + BAR_WMF * 8, 0);
                    if (t == 15) TS(30);
                    const uint32_t fb = bars + (BAR_FULL + (t & 15)) * 8;
                    const int hi = t - (lds32(sm + OFF_WIN) ? W_HI : W_0), lo = t - W_LO;
                    mbar_wait(fb + (BAR_EMPTY - BAR_FULL) * 8, (~t >> 4) & 1);
                    mbar_expect(fb, TILE_BYTES);
                    mbar_wait(bars + (BAR_FULL + (hi & 15)) * 8, (hi >> 4) & 1);
                    on_time(t * TAU - L_KV, bars + (BAR_FULL + (lo & 15)) * 8, (lo >> 4) & 1);
                    tma3d_hint(sm + OFF_RING + (t & 15) * TILE_BYTES, &T.m[t >> 6], 0, row0 + (t & (NT - 1)) * 32, 0, fb, pol);
                    TI(6 + t);
                    if (t == T_CLEAR) mbar_arrive(bars + (BAR_SYNC + 1) * 8);
                }
                mbar_wait(bars + BAR_SYNC * 8, 0);
                auto window = [&](int b, int lead) {
                    mbar_wait(bars + (b - W_HT) * 8, b - W_HT < BAR_WO);
                    on_time((2 * NT - 1) * TAU + (b - BAR_WO + 1) * TAU_W - lead, bars + (b - W_LO) * 8, b - W_LO < BAR_WO);
                };
#pragma unroll 1
                for (int i = 0; i < 4; i++) {
                    window(BAR_WO + i, L_WO);
                    tma3d(sm + OFF_WO + i * 8192, &T.m[M_OD], 64 * sub, grp * 256 + i * 64, P.zo, bars + (BAR_WO + i) * 8);
                    tma3d(sm + OFF_OX + i * 1024, &T.m[M_OX], 512 + 8 * sub, grp * 256 + i * 64, P.zo, bars + (BAR_WO + i) * 8);
                    TI(134 + i);
                }
                TS(28);
#pragma unroll 1
                for (int i = 0; i < 9; i++) {
                    mbar_wait(bars + (BAR_EMPTY + i) * 8, 1);
                    window(BAR_GU + i, L_GU);
                    tma3d(sm + OFF_GU + i * 8192, &T.m[M_GU], grp * 288 + 32 * sub, i * 64, 0, bars + (BAR_GU + i) * 8);
                    if (sub < 4) tma3d(sm + OFF_GX + i * 2048, &T.m[M_GX], grp * 288 + 256 + 8 * sub, i * 64, 0, bars + (BAR_GU + i) * 8);
                    TI(138 + i);
                }
                TS(29);
#pragma unroll 1
                for (int i = 0; i < 5; i++) {
                    const int blk = i < 4 ? (i + 3) & 3 : 4, r = min(blk * 64, 224);
                    mbar_wait(bars + (BAR_EMPTY + 9 + blk) * 8, 1);
                    window(BAR_WD + i, L_WD + (i == 4 ? L_LAST : 0));
                    tma3d(sm + OFF_WD + r * 128, &T.m[M_OD], 64 * sub, grp * 288 + r, P.zo ^ 1, bars + (BAR_WD + i) * 8);
                    tma3d(sm + OFF_DX + r * 16, &T.m[M_OX], 512 + 8 * sub, grp * 288 + r, P.zo ^ 1, bars + (BAR_WD + i) * 8);
                    TI(147 + i);
                }
                if (cta < 72) {
                    mbar_wait(bars + (BAR_EMPTY + 14) * 8, 1);
                    mbar_wait(bars + (BAR_EMPTY + 15) * 8, 1);
#pragma unroll
                    for (int i = 0; i < 3; i++) mbar_expect(bars + (BAR_GB + i) * 8, 3072);
                    window(BAR_WD + 5, L_GB);
#pragma unroll
                    for (int i = 0; i < 3; i++) tma3d(sm + OFF_GB + i * 3072, &T.m[M_GB], 5 * DM + 8 * cta, i * 192, 0, bars + (BAR_GB + i) * 8);
                }
            } else {
#pragma unroll 1
                for (int i = BAR_WO; i < BAR_WD + 5; i++) mbar_expect(bars + i * 8, i < BAR_GU || i >= BAR_WD ? 9216 : sub < 4 ? 10240 : 8192);
                mbar_arrive(bars + BAR_SYNC * 8);
                uint32_t* const cnt = g0 + (epoch & 1) * G_SET + G_CNT;
#pragma unroll 1
                for (int t = cta & 3; t < 144; t += 4) {
                    const uint32_t bar = bars + (BAR_FULL + (t < 2 * NT ? t & 15 : t - 112)) * 8;
                    mbar_wait(bar, (t >> 4) & 1);
                    if (t < 2 * NT) mbar_arrive(bar + (BAR_EMPTY - BAR_FULL) * 8);
                    const uint32_t t0 = clock32(0);
                    const int c = (int)atomicAdd(cnt, 1u) - 16;
                    const uint32_t o = t0 + ((clock32(c) - t0) >> 1) - ((c * TAU + max(c - 32 * (2 * NT - 1), 0) * (TAU_W - TAU)) >> 5);
                    if (t >= T_PACE) sts32(sm + OFF_WIN, o | 1);
                    if ((t >> 2) == 8 || (t >> 2) == 24) TL(t >> 2, ((clock32(0) - t0) * 9) >> 4);
                }
            }
        }
        return;
    }

    if (lane == 0) {
#pragma unroll
        for (int i = 0; i < 6; i++) {
            const int b = 10 + warp * 6 + i;
            mbar_init(bars + b * 8, b >= BAR_EMPTY && b < BAR_EMPTY + 16 && ((b ^ cta) & 3) == 0 ? 2 : 1);
        }
        asm volatile("fence.mbarrier_init.release.cluster;" ::: "memory");
    }
    __syncwarp();
    if (warp < 9) bar_arrive(15, NTHREADS);
    const int g = lane >> 2, t4 = lane & 3;
    uint32_t* const gs = g0 + (epoch & 1) * G_SET;

    uint32_t sc[8] = {};
    if (warp < 9) {
        const int off_h = (cta < 36 ? dual(D_H + 2 * cta * 32) : G_M + 4 * (cta - 36) * 32) + tid;
        const int off_h2 = off_h + (cta < 36 ? 1024 : 64);
        const int off_q = dual(D_Q + g * (HQ * 64) + cta * 16) + warp * 8 + t4 * 2;
        uint32_t bf[8] = {}, xp = 0, mean2 = 0;
        float inv = 0.f;
        if (cta < 36) xp = __ldg(reinterpret_cast<const uint32_t*>(P.x) + g * (DM / 2) + 8 * cta + 4 * (warp & 1) + t4);
        if (warp < 2) {
            st2(gs + off_q, 0, 0), st2(gs + off_q + 1024, 0, 0);
            if (cta < 36) st1(gs + off_h, 0), st1(gs + off_h2, 0);
        }
        if (cta < 90) {
            asm volatile("cp.async.wait_all;" ::: "memory");
            __syncwarp();
            const uint32_t fa = sm + OFF_RED + warp * 2048 + (lane & 7) * 128 + (((lane >> 3) ^ (lane & 7)) << 4);
            ldsm4(reinterpret_cast<uint32_t(&)[4]>(bf[0]), fa);
            ldsm4(reinterpret_cast<uint32_t(&)[4]>(bf[4]), fa ^ 64);
            if (cta < 36) {
                uint32_t xv[8];
                ldsm4(reinterpret_cast<uint32_t(&)[4]>(xv[0]), fa + 1024);
                ldsm4(reinterpret_cast<uint32_t(&)[4]>(xv[4]), (fa ^ 64) + 1024);
                ln_partial(xv, sm + OFF_ST + g * 80 + warp * 8, t4 == 0);
            }
#pragma unroll
            for (int i = 0; i < 8; i++) sc[i] = bf[i] = silu2(bf[i]);
        }
        if (warp == 0) TSL(18);
        bar_sync(1, (NCW + 1) * 32);
        if (cta < 36 && warp < 2) ln_combine(sm + OFF_ST + g * 80, mean2, inv);
        const int r = warp * 64 + (lane >> 4) * 8 + (lane & 7), hi8 = (lane >> 3) & 1, box = warp / 3;
#pragma unroll 1
        for (int pass = cta < 90 ? 0 : 1; pass < 2; pass++) {
            const bool pa = pass == 0 && cta < 36;
            const uint32_t ab = sm + OFF_WM + pass * 36864 +
                                (pa ? (box + hi8) * 6144 + r * 32 + ((lane & 4) << 2) : r * 64 + (((2 * hi8) ^ ((r >> 1) & 3)) << 4));
            const uint32_t as = pa ? 512 : 1024, red = sm + OFF_RED + pass * 9216;
            mbar_wait(bars + (pass * 3 + box) * 8, 0);
            if (warp == 8) TSL(pass ? 31 : 19);
            uint32_t a[4][2][4];
#pragma unroll
            for (int i = 0; i < 4; i++) {
                ldsm4t(a[i][0], ab + i * as);
                ldsm4t(a[i][1], (ab ^ 16) + i * as);
            }
            if (pass) {
                bar_sync(8, NCW * 32);
#pragma unroll
                for (int i = 0; i < 8; i++) bf[i] = 0;
                const uint32_t* const src_h = gs + near(D_H + warp * 256, lds32(sm + OFF_WIN + 4)) + lane;
                get<1, 1>(src_h, 0, reinterpret_cast<uint32_t(&)[1]>(bf[0]));
                get<8, 1>(src_h, 32, bf);
                if (warp == 0) TSL(3);
            }
            float acc[2][4] = {};
#pragma unroll
            for (int i = 0; i < 4; i++)
#pragma unroll
                for (int m = 0; m < 2; m++) mma(acc[m], a[i][m][0], a[i][m][1], a[i][m][2], a[i][m][3], bf[2 * i], bf[2 * i + 1]);
            sts128f(red + tid * 16, acc[0]);
            sts128f(red + 4608 + tid * 16, acc[1]);
            bar_sync(3, 288);
            if (warp < 2) {
                float c[4] = {};
                sum_frags<9>(c, red + warp * 4608 + lane * 16, 512);
                uint32_t lo = movm(pack2(c[0], c[1])), hi = movm(pack2(c[2], c[3]));
                if (pass) {
                    put2d(gs + off_q, lo, hi);
                    if (warp == 0) TSL(4);
                } else {
                    const uint32_t hi1 = badd2(hi, ONE2);
                    if (pa) hi = lo = modulate2(xp, mean2, inv, lo, hi1);
                    if (cta >= 72) lo = badd2(lo, ONE2), hi = hi1;
                    st1(gs + off_h, nz(lo));
                    st1(gs + off_h2, nz(hi));
                    if (warp == 0 && pa) TSL(2);
                }
            } else if (tid == 64 && pass == 0) {
                mbar_arrive(bars + BAR_WMF * 8);
            }
        }
    } else {
        if ((uint32_t)__cvta_generic_to_shared(smem_raw) != sm) __trap();
        uint32_t* const ping = g0 + dual(D_PING) + cta * 8;
        if (lane < 16) st1(ping + (lane >> 3) * 1024 + (lane & 7), 0);
        bar_sync(15, NTHREADS);
        uint32_t best[2] = {~0u, ~0u}, v = 0;
#pragma unroll 1
        for (int part = 0; part < 2; part++) {
            if (lane == 0) {
#pragma unroll 1
                for (int r = part ? NPING1 : NPING0; r > 0; r--) {
#pragma unroll
                    for (int k = 0; k < 2; k++) {
                        const uint32_t t0 = clock32(v);
                        v = atomicExch(ping + k * 1024, t0);
                        best[k] = min(best[k], clock32(v) - t0);
                    }
                }
                sts32(sm + OFF_WIN + 4 + 4 * part, ((best[1] < best[0]) ^ __popc(D_PING & 0x16400)) & 1);
            }
            __syncwarp();
            if (part) break;
            TSL(20);
            bar_arrive(8, NCW * 32);
            mbar_wait(bars + 5 * 8, 0);
            uint32_t a[4] = {};
            get<1, 4>(gs + near(D_Q + (sub * HQ + 2 * grp) * 64, lds32(sm + OFF_WIN + 4)) + lane * 4, 0, a);
            sts128(sm + OFF_QS + lane * 16, a[0], a[1], a[2], a[3]);
            __syncwarp();
            TSL(5);
            bar_arrive(4, 288);
        }
#pragma unroll
        for (int i = lane; i < 72; i += 32) cp16(sm + OFF_WR + i * 16, P.wr + i * 8);
        __syncwarp();
        if (cta < 72 && lane < 16) st1(g0 + ((epoch ^ lane >> 3) & 1) * G_SET + G_SIDE + cta * 8 + (lane & 7), lane < 8 ? 1 + lds32(sm + OFF_WIN + 8) : 0);
        asm volatile("cp.async.wait_all;" ::: "memory");
        __syncwarp();
        bar_arrive(2, NCW * 32);
        auto clear_late = [&](uint32_t* set) {
#pragma unroll 1
            for (int c = 0; c < 2; c++, set += 1024) {
                zero4(set + dual(D_O + cta * 128) + lane * 4);
                zero4(set + dual(D_ACT + (grp * 36 + 4 * sub) * 32) + lane * 4);
                if (lane < 8 ? sub < 4 : lane < 16 && cta < 72)
                    zero4(set + dual(lane < 8 ? D_ACT + (grp * 36 + 32 + sub) * 32 : D_X1 + cta * 32) + (lane & 7) * 4);
            }
        };
        auto clear_next = [&] {
            uint32_t* const nx = g0 + (~epoch & 1) * G_SET;
            uint32_t* const q = nx + dual(D_Q + g * (HQ * 64) + cta * 16) + t4 * 4;
            mbar_wait(bars + (BAR_GU + 5) * 8, 0);
            clear_late(nx);
            zero4(q), zero4(q + 1024);
            if (cta < 90) zero4(nx + (cta < 36 ? dual(D_H + 2 * cta * 32) + (lane >> 4) * (1024 - 64) : G_M + 4 * (cta - 36) * 32) + lane * 4);
            if (cta == 0 && lane == 0) st1(nx + G_CNT, 0);
            __syncwarp();
        };
        mbar_wait(bars + (BAR_SYNC + 1) * 8, 0);
        clear_late(gs);
        __syncwarp();
        if (cta >= 72) {
            bar_arrive(5, NCW * 32);
            clear_next();
            return;
        }
        const uint32_t io = pin(4 * (g * (DM / 2) + 4 * cta + t4));
        uint32_t x = __ldg(at(reinterpret_cast<const uint32_t*>(P.x), io)), ga[1] = {};
        get<1, 1>(gs + G_M + cta * 32 + lane, 0, ga);
        const uint32_t src_p = pin(4 * (near(d_part(cta), lds32(sm + OFF_WIN + 8)) + lane * 2));
        const uint32_t dst_x = pin(4 * ((epoch & 1) * G_SET + dual(D_X1 + cta * 32) + lane));
        bar_sync(5, NCW * 32);
        x = badd2(x, bmul2(ga[0], reduce16<0>(at(g0, src_p), [] {})));
        put1d(at(g0, dst_x), x);
        TSL(10);
        clear_next();
        bar_sync(6, NCW * 32);
        const uint4 r0 = lds128(sm + OFF_RT + g * 48), r1 = lds128(sm + OFF_RT + g * 48 + 16);
        float r = __uint_as_float(lds32(sm + OFF_RT + g * 48 + 32));
        r += ((__uint_as_float(r0.x) + __uint_as_float(r0.y)) + (__uint_as_float(r0.z) + __uint_as_float(r0.w))) +
             ((__uint_as_float(r1.x) + __uint_as_float(r1.y)) + (__uint_as_float(r1.z) + __uint_as_float(r1.w)));
        r = sigmoid_f(rbf(r));
        const uint32_t h = lds32(sm + OFF_RED + (cta >> 2) * 512 + lane * 16 + (cta & 3) * 4), rs = pack2(r, r);
        uint32_t gb;
        mbar_wait(bars + (BAR_WD + 4) * 8, 0);
        const uint32_t y = reduce16<1>(at(g0, src_p), [&] {
            TSL(23);
            bar_sync(9, 64);
            gb = lds32(sm + OFF_QS + lane * 4);
        });
        *at(reinterpret_cast<uint32_t*>(P.out), io) = badd2(x, bmul2(gb, badd2(h, bmul2(y, rs))));
        if (cta == 0 && lane == 0) g0[G_EPOCH] = epoch + 1;
        TSL(15);
        if (lane == 0) TL(0, 0);
        return;
    }

    const uint32_t tile = sm + OFF_RING + warp * TILE_BYTES;
    const uint32_t fullb = bars + (BAR_FULL + warp) * 8;
    const uint32_t pw = sm + OFF_P + warp * (2 * P_PITCH);
    if (warp < 8) {
        {
            uint32_t q0[8], q1[8];
            bar_sync(4, 288);
#pragma unroll
            for (int i = 0; i < 8; i++) {
                const float2 v = lds64f(sm + OFF_QS + (g & 1) * 256 + i * 32 + t4 * 8);
                q0[i] = __float_as_uint(v.x), q1[i] = __float_as_uint(v.y);
            }
            uint32_t sp = pw + (t4 & 1) * P_PITCH + ((t4 >> 1) * 8 + g) * 2;
#pragma unroll 1
            for (int it = 0; it < 8; it++, sp += 64) {
                const uint32_t ab = tile + (it & 1) * (8 * TILE_BYTES) + (lane & 15) * 128 + (((lane >> 4) ^ (lane & 7)) << 4);
                mbar_wait(fullb + (it & 1) * 64, (it >> 1) & 1);
                float acc[2][2][4] = {};
#pragma unroll
                for (int ks = 0; ks < 8; ks++)
#pragma unroll
                    for (int m = 0; m < 2; m++) {
                        uint32_t a[4];
                        ldsm4(a, (ab ^ ((ks & 3) << 5)) + (ks >> 2) * 4096 + m * 2048);
                        mma(acc[m][ks & 1], a[0], a[1], a[2], a[3], (ks & 1) ? q1[ks - 1] : q0[ks], (ks & 1) ? q1[ks] : q0[ks + 1]);
                    }
                __syncwarp();
                if (lane == 0) mbar_arrive(fullb + (it & 1) * 64 + (BAR_EMPTY - BAR_FULL) * 8);
#pragma unroll
                for (int m = 0; m < 2; m++) {
                    const float s = sel4(acc[m][0], t4) + sel4(acc[m][1], t4);
                    sts16(sp + m * 32, (uint16_t)pack2(rbf(s) * 0.08838834764831845f, 0.f));
                }
            }
        }
        __syncwarp();
        if (warp == 7) TSL(6);
        const uint32_t pa = pw + (lane >> 4) * P_PITCH + (lane & 15) * 32;
        const uint32_t sa = sm + OFF_SM + (lane >> 4) * 64;
        const uint4 v0 = lds128(pa), v1 = lds128(pa + 16);
        const uint32_t sv[8] = {v0.x, v0.y, v0.z, v0.w, v1.x, v1.y, v1.z, v1.w};
        float e[16];
        float m = -INFINITY;
#pragma unroll
        for (int i = 0; i < 8; i++) {
            e[2 * i] = blo(sv[i]);
            e[2 * i + 1] = bhi(sv[i]);
            m = fmaxf(m, fmaxf(e[2 * i], e[2 * i + 1]));
        }
#pragma unroll
        for (int o = 8; o; o >>= 1) m = fmaxf(m, __shfl_xor_sync(0xffffffffu, m, o));
        float l = 0.f;
#pragma unroll
        for (int i = 0; i < 16; i++) {
            e[i] = ex2((e[i] - m) * LOG2E);
            l += e[i];
        }
#pragma unroll
        for (int o = 8; o; o >>= 1) l += __shfl_xor_sync(0xffffffffu, l, o);
        if ((lane & 15) == 0) sts64(sa + warp * 8, __float_as_uint(m), __float_as_uint(l));
        bar_sync(2, NCW * 32);
        const float2 v = lds64f(sa + (lane & 7) * 8);
        float M = v.x;
#pragma unroll
        for (int o = 4; o; o >>= 1) M = fmaxf(M, __shfl_xor_sync(0xffffffffu, M, o));
        float L = v.y * ex2((v.x - M) * LOG2E);
#pragma unroll
        for (int o = 4; o; o >>= 1) L += __shfl_xor_sync(0xffffffffu, L, o);
        const float sc = ex2((m - M) * LOG2E) * rcp(L);
        sts128(pa, pack2(e[0] * sc, e[1] * sc), pack2(e[2] * sc, e[3] * sc), pack2(e[4] * sc, e[5] * sc), pack2(e[6] * sc, e[7] * sc));
        sts128(pa + 16, pack2(e[8] * sc, e[9] * sc), pack2(e[10] * sc, e[11] * sc), pack2(e[12] * sc, e[13] * sc), pack2(e[14] * sc, e[15] * sc));
        __syncwarp();
    } else {
        bar_sync(2, NCW * 32);
    }

    uint32_t sh[8] = {}, op[8] = {};
    {
        const uint32_t* const src_m = gs + G_M + (72 + warp * 8) * 32 + lane;
        fetch<8, 1>(src_m + 72 * 32, 32, op);
        get<8, 1>(src_m, 32, sh);
        get<8, 1>(src_m + 72 * 32, 32, op);
    }
    const int side = lds32(sm + OFF_WIN + 8), set = (epoch & 1) * G_SET, rr = (lane >> 4) * 8 + (lane & 7);
    const uint32_t dst_o = pin(4 * (set + dual(D_O + cta * 128) + (tid & 0x70) + (tid & 3) * 4 + ((tid >> 2) & 3)));
    const uint32_t src_o = pin(4 * (set + near(D_O + grp * 1024, side) + g * 128 + warp * 16 + t4 * 4));
    const int unit = warp < 8 ? 8 * sub + warp : 64 + sub;
    uint32_t rside[1] = {};
    get<1, 1>(gs + G_SIDE + unit * 8, 0, rside);
    const uint32_t dst_p = pin(4 * (near(d_part(unit), rside[0] - 1) + grp * 64 + lane * 2));
    const uint32_t src_x = pin(4 * (set + near(D_X1 + warp * 256, side) + lane));
    const uint32_t dst_a = pin(4 * (set + dual(D_ACT + (grp * 36 + (warp < 4 ? 4 * sub + warp : 32 + sub)) * 32) + lane));
    const uint32_t src_a = pin(4 * (set + near(D_ACT + (grp * 36 + 4 * warp) * 32, side) + lane));
    const uint32_t rowoff = pin(warp < 8 ? lane * 128 + ((warp ^ (lane & 7)) << 4) : lane * 16), rowstep = warp < 8 ? 4096 : 512;
    const uint32_t l16 = pin(lane * 16);
    const uint32_t ored = pin((warp * 1088 + (t4 & 1) * 576 + ((t4 >> 1) * 8 + g) * 4) | ((tid >> 6) * 64 + tid * 8) << 16);

    if (warp < 8) {
        float acc[8][4] = {};
        uint32_t pp = pw + (lane & 1) * P_PITCH + (lane >> 3) * 16;
#pragma unroll 1
        for (int it = 0; it < 8; it++, pp += 64) {
            const uint32_t ab = tile + (it & 1) * (8 * TILE_BYTES) + ((lane & 7) + (lane >> 4) * 8) * 128 + ((((lane >> 3) & 1) ^ (lane & 7)) << 4);
            uint32_t pb[4];
            ldsm4(pb, pp);
            if (it == 6) st2(at(g0, dst_p), 0, 0);
            mbar_wait(fullb + (it & 1) * 64, (it >> 1) & 1);
#pragma unroll
            for (int ks = 0; ks < 2; ks++)
#pragma unroll
                for (int m = 0; m < 8; m++) {
                    uint32_t a[4];
                    ldsm4t(a, (ab ^ ((m & 3) << 5)) + (m >> 2) * 4096 + ks * 2048);
                    mma(acc[m], a[0], a[1], a[2], a[3], pb[2 * ks], pb[2 * ks + 1]);
                }
            __syncwarp();
            if (lane == 0) mbar_arrive(fullb + (it & 1) * 64 + (BAR_EMPTY - BAR_FULL) * 8);
        }
        if (warp == 7) TSL(7);
        const uint32_t ra = sm + OFF_ORED + (ored & 0xffff);
#pragma unroll
        for (int m = 0; m < 8; m++) sts32(ra + m * 64, __float_as_uint(sel4(acc[m], t4)));
    } else {
        mbar_wait(bars + (BAR_SYNC + 1) * 8, 0);
        st2(at(g0, dst_p), 0, 0);
    }
    bar_sync(5, NCW * 32);
    if (warp < 4) {
        float s[2][2] = {};
#pragma unroll
        for (int w = 0; w < 8; w++) {
            const float2 v = lds64f(sm + OFF_ORED + w * 1088 + (ored >> 16));
            s[w & 1][0] += v.x;
            s[w & 1][1] += v.y;
        }
        put1d(at(g0, dst_o), pack2(s[0][0] + s[1][0], s[0][1] + s[1][1]));
        if (warp == 0) TSL(8);
    }

    project<0>(sm, at(g0, src_o), at(g0, dst_p), sm + (warp < 8 ? OFF_WO : OFF_OX) + rowoff, rowstep, l16, 288, warp, lane);
    if (warp == 0) TSL(9);

    {
        uint32_t h[8] = {}, mean2;
        float inv;
        get<1, 1>(at(g0, src_x), 0, reinterpret_cast<uint32_t(&)[1]>(h[0]));
        get<8, 1>(at(g0, src_x), 32, h);
        if (warp == 0) TSL(11);
        ln_partial(h, sm + OFF_ST + g * 80 + warp * 8, t4 == 0);
        bar_sync(3, 288);
        ln_combine(sm + OFF_ST + g * 80, mean2, inv);
#pragma unroll
        for (int i = 0; i < 8; i++) h[i] = modulate2(h[i], mean2, inv, sh[i], op[i]);
        sts128(sm + OFF_RED + warp * 1024 + lane * 16, h[0], h[1], h[2], h[3]);
        sts128(sm + OFF_RED + warp * 1024 + 512 + lane * 16, h[4], h[5], h[6], h[7]);
        if (warp == 0) TSL(12);
        if (cta < 72) {
            float r = 0.f;
#pragma unroll
            for (int i = 0; i < 8; i++) {
                const uint32_t wr = lds32(sm + OFF_WR + (warp * 32 + i * 4 + t4) * 4);
                r = fmaf(blo(h[i]), blo(wr), fmaf(bhi(h[i]), bhi(wr), r));
            }
            r = quad_sum(r);
            if (t4 == 0) sts32(sm + OFF_RT + g * 48 + warp * 4, __float_as_uint(r));
        }
    }
    bar_sync(3, 288);

    if (warp < (sub < 4 ? 5 : 4)) {
        const int pl = ((lane >> 3) & 1) ^ P.zg;
        const uint32_t ks = warp < 4 ? 1024 : 256;
        uint32_t aa = sm + (warp < 4 ? OFF_GU + rr * 64 + (((lane & 6) << 3) ^ (warp << 4)) : OFF_GX + rr * 16) + pl * 4 * ks;
        float acc[2][4] = {};
#pragma unroll 1
        for (int i = 0; i < 9; i++, aa += 8 * ks) {
            const uint4 b0 = lds128(sm + OFF_RED + i * 1024 + lane * 16), b1 = lds128(sm + OFF_RED + i * 1024 + 512 + lane * 16);
            uint32_t a[4][4];
            mbar_wait(bars + (BAR_GU + i) * 8, 0);
#pragma unroll
            for (int k = 0; k < 4; k++) ldsm4t(a[k], aa + k * ks);
            mma(acc[0], a[0][0], a[0][1], a[0][2], a[0][3], b0.x, b0.y);
            mma(acc[1], a[1][0], a[1][1], a[1][2], a[1][3], b0.z, b0.w);
            mma(acc[0], a[2][0], a[2][1], a[2][2], a[2][3], b1.x, b1.y);
            mma(acc[1], a[3][0], a[3][1], a[3][2], a[3][3], b1.z, b1.w);
        }
        if (warp == 1) TSL(17);
        const uint32_t gate = pack2(acc[0][0] + acc[1][0], acc[0][1] + acc[1][1]), up = pack2(acc[0][2] + acc[1][2], acc[0][3] + acc[1][3]);
        put1d(at(g0, dst_a), movm(bmul2(silu2(gate), up)));
        if (warp == 1) TSL(13);
    } else {
        mbar_wait(bars + (BAR_GU + 8) * 8, 0);
    }

    project<1>(sm, at(g0, src_a), at(g0, dst_p), sm + (warp < 8 ? OFF_WD : OFF_DX) + rowoff, rowstep, l16, cta < 72 ? 320 : 288, warp, lane);
    if (warp == 0) TSL(14);
    if (warp == 8) TSL(27);

    if (cta < 72) {
        float acc[4][4] = {};
        uint32_t w[2][4];
        mbar_wait(bars + (BAR_GB + warp / 3) * 8, 0);
        if (warp == 8) TSL(22);
#pragma unroll
        for (int i = 0; i < 2; i++) ldsm4t(w[i], sm + OFF_GB + warp * 1024 + i * 512 + l16);
#pragma unroll
        for (int i = 0; i < 2; i++) {
            mma(acc[2 * i], sc[4 * i], sc[4 * i + 2], sc[4 * i + 1], sc[4 * i + 3], w[i][0], w[i][1]);
            mma(acc[2 * i + 1], sc[4 * i], sc[4 * i + 2], sc[4 * i + 1], sc[4 * i + 3], w[i][2], w[i][3]);
        }
        float s[2][2] = {{(acc[0][0] + acc[1][2]) + (acc[2][0] + acc[3][2]), (acc[0][1] + acc[1][3]) + (acc[2][1] + acc[3][3])}, {0.f, 0.f}};
        const uint32_t red = sm + OFF_RED + 9216 + (l16 >> 1);
        if (warp) {
            sts64(red + warp * 256, __float_as_uint(s[0][0]), __float_as_uint(s[0][1]));
            bar_arrive(7, 288);
        } else {
            bar_sync(7, 288);
#pragma unroll
            for (int k = 1; k < 9; k++) {
                const float2 v = lds64f(red + k * 256);
                s[k & 1][0] += v.x;
                s[k & 1][1] += v.y;
            }
            sts32(sm + OFF_QS + (l16 >> 2), pack2(s[0][0] + s[1][0], s[0][1] + s[1][1]));
            __syncwarp();
            bar_arrive(9, 64);
            TSL(25);
        }
    }
}

typedef CUresult (*EncodeFn)(CUtensorMap*, CUtensorMapDataType, cuuint32_t, void*, const cuuint64_t*, const cuuint64_t*,
                             const cuuint32_t*, const cuuint32_t*, CUtensorMapInterleave, CUtensorMapSwizzle,
                             CUtensorMapL2promotion, CUtensorMapFloatOOBfill);

void make_map(EncodeFn enc, CUtensorMap* m, void* p, int cols, int rows, int pitch, int bc, int br, int bp, int planes, size_t pstride,
              CUtensorMapSwizzle sw, int promo) {
    cuuint64_t dims[3] = {(cuuint64_t)cols, (cuuint64_t)rows, (cuuint64_t)planes};
    cuuint64_t strides[2] = {(cuuint64_t)pitch * 2, (cuuint64_t)pstride};
    cuuint32_t box[3] = {(cuuint32_t)bc, (cuuint32_t)br, (cuuint32_t)bp};
    cuuint32_t es[3] = {1, 1, 1};
    enc(m, CU_TENSOR_MAP_DATA_TYPE_BFLOAT16, 3, p, dims, strides, box, es, CU_TENSOR_MAP_INTERLEAVE_NONE, sw,
        (CUtensorMapL2promotion)promo, CU_TENSOR_MAP_FLOAT_OOB_FILL_NONE);
}

}

extern "C" void kernel_launch(void* const* d_in, const int* in_sizes, int n_in, void* d_out, int out_size) {
    static EncodeFn enc = nullptr;
    static uint32_t* scratch = nullptr;
    if (!enc) {
        void* fn = nullptr;
        cudaDriverEntryPointQueryResult st;
        cudaGetDriverEntryPoint("cuTensorMapEncodeTiled", &fn, cudaEnableDefault, &st);
        enc = (EncodeFn)fn;
        cudaGetSymbolAddress(&fn, g_scratch);
        scratch = (uint32_t*)(((uintptr_t)fn + 8 * G_SET - 1) & ~(uintptr_t)(8 * G_SET - 1));
        cudaFuncSetAttribute(fused_kernel, cudaFuncAttributeMaxDynamicSharedMemorySize, SMEM_BYTES);
    }
    Params P;
    Maps T;
    const CUtensorMapSwizzle none = CU_TENSOR_MAP_SWIZZLE_NONE;
    const int PROMO_W = CU_TENSOR_MAP_L2_PROMOTION_L2_128B, PROMO_KV = CU_TENSOR_MAP_L2_PROMOTION_L2_256B;
    make_map(enc, &T.m[M_K], d_in[1], 64, NB * HKV * SK, DH, 64, 32, 2, 2, 128, CU_TENSOR_MAP_SWIZZLE_128B, PROMO_KV);
    make_map(enc, &T.m[M_V], d_in[2], 64, NB * HKV * SK, DH, 64, 32, 2, 2, 128, CU_TENSOR_MAP_SWIZZLE_128B, PROMO_KV);
    make_map(enc, &T.m[M_WQ], d_in[3], HQ * DH, DM, HQ * DH, 32, 192, 1, 1, 16, CU_TENSOR_MAP_SWIZZLE_64B, PROMO_W);
    make_map(enc, &T.m[M_WM], d_in[11], 6 * DM, DM, 6 * DM, 32, 192, 1, 1, 16, CU_TENSOR_MAP_SWIZZLE_64B, PROMO_W);
    make_map(enc, &T.m[M_WA], d_in[11], DM, DM, 6 * DM, 16, 192, 2, 2, DM * 2, CU_TENSOR_MAP_SWIZZLE_32B, PROMO_W);
    make_map(enc, &T.m[M_GB], d_in[11], 6 * DM, DM, 6 * DM, 8, 192, 1, 1, 16, none, PROMO_W);
    char *wg = (char*)d_in[7], *wu = (char*)d_in[8], *wo = (char*)d_in[4], *wd = (char*)d_in[9];
    P.zg = wg > wu;
    P.zo = wo > wd;
    const size_t sg = P.zg ? wg - wu : wu - wg, so = P.zo ? wo - wd : wd - wo;
    make_map(enc, &T.m[M_GU], P.zg ? wu : wg, FF, DM, FF, 32, 64, 2, 2, sg, CU_TENSOR_MAP_SWIZZLE_64B, PROMO_W);
    make_map(enc, &T.m[M_GX], P.zg ? wu : wg, FF, DM, FF, 8, 64, 2, 2, sg, none, PROMO_W);
    make_map(enc, &T.m[M_OD], P.zo ? wd : wo, DM, FF, DM, 64, 64, 1, 2, so, CU_TENSOR_MAP_SWIZZLE_128B, PROMO_W);
    make_map(enc, &T.m[M_OX], P.zo ? wd : wo, DM, FF, DM, 8, 64, 1, 2, so, none, PROMO_W);
    P.x = (const __nv_bfloat16*)d_in[0];
    P.wr = (const __nv_bfloat16*)d_in[6];
    P.c = (const __nv_bfloat16*)d_in[10];
    P.k = (const __nv_bfloat16*)d_in[1];
    P.out = (__nv_bfloat16*)d_out;
    P.scratch = scratch;
    void* args[2] = {&P, &T};
    cudaLaunchCooperativeKernel((const void*)fused_kernel, dim3(NCTA), dim3(NTHREADS), args, SMEM_BYTES, cudaStreamPerThread);
}
```

```cpp
#include <cuda_runtime.h>
#include <cuda_bf16.h>
#include <cuda.h>
#include <stdint.h>

typedef unsigned long long u64;

#define TAU 568
#define TAU_W 655
#define L_KV 3200
#define L_WO 3000
#define L_GU 3000
#define L_WD 2900
#define L_LAST 50
#define L_GB 2950
#define W_0 6
#define W_LO 2
#define W_HI 8
#define W_HT 5
#define T_PACE 20
#define NK0 3
#define NK1 2
#define PFK 2
#define T_CLEAR 116
#define NPING0 4
#define NPING1 10

namespace {

constexpr int NB = 8, DM = 576, HQ = 32, HKV = 16, SK = 8192, WIN = 2048, DH = 128, FF = 4608;
constexpr int NCTA = 128;
constexpr int NCW = 10;
constexpr int NTHREADS = (NCW + 2) * 32;
constexpr int TILE_BYTES = 8192, NT = 64;
constexpr int SPIN_LIMIT = 1 << 22;

constexpr int OFF_RING = 0;
constexpr int OFF_WM = 121856;
constexpr int OFF_WQ = OFF_WM + 36864;
constexpr int OFF_GU = 0;
constexpr int OFF_WD = 73728;
constexpr int OFF_GB = 114688;
constexpr int OFF_OX = 131072;
constexpr int OFF_DX = OFF_OX + 4096;
constexpr int OFF_GX = OFF_DX + 4608;
constexpr int OFF_WO = OFF_WQ;
constexpr int OFF_P = OFF_WQ + 36864;
constexpr int P_PITCH = 528;
constexpr int OFF_RED = OFF_P + 16 * P_PITCH;
constexpr int OFF_ORED = OFF_RED + 5 * 4608 - 8704;
constexpr int OFF_ST = OFF_RED + 5 * 4608;
constexpr int OFF_SM = OFF_ST + 640;
constexpr int OFF_RT = OFF_SM + 128;
constexpr int OFF_QS = OFF_RT + 384;
constexpr int OFF_WR = OFF_QS + 512;
constexpr int OFF_WIN = OFF_WR + 1152;
constexpr int OFF_BAR = OFF_WIN + 16;
constexpr int BAR_FULL = 6, BAR_WO = 22, BAR_GU = 26, BAR_WD = 35, BAR_EMPTY = 40, BAR_SYNC = 56, BAR_WMF = 59, BAR_GB = 60, NBAR = 70;
constexpr int SMEM_BYTES = OFF_BAR + NBAR * 8;

constexpr int D_X1 = 0;
constexpr int D_O = 3072;
constexpr int D_ACT = D_O + 512 * 32;
constexpr int D_H = D_ACT + 576 * 32;
constexpr int D_Q = D_H + 3072;
constexpr int G_M = 2 * (D_Q + NB * HQ * 64);
constexpr int G_SIDE = G_M + 216 * 32;
constexpr int G_CNT = G_SIDE + 72 * 8;
constexpr int G_SET = 1 << 18;
__device__ __forceinline__ int d_part(int unit) { return (64 + unit + (unit & 64)) * 1024; }
constexpr int D_PING = 200 * 1024;
constexpr int G_EPOCH = 201 * 2048;
static_assert(G_CNT < 64 * 2048, "scratch layout");
__device__ uint32_t g_scratch[4 * G_SET];
__device__ __forceinline__ int dual(int w) { return w + (w & ~1023); }
__device__ __forceinline__ int near(int w, int side) { return dual(w) + (((__popc(w & 0x16400) ^ side) & 1) << 10); }

#define TL(i, back)
#define TI(i)
#define TS(i)
#define TSL(i)

enum { M_K, M_V, M_GU, M_GX, M_OD, M_OX, M_WQ, M_WM, M_WA, M_GB, NMAP };
struct Params {
    const __nv_bfloat16 *c, *x, *k;
    __nv_bfloat16* out;
    uint32_t* scratch;
    const __nv_bfloat16* wr;
    int zg, zo;
};
struct Maps {
    CUtensorMap m[NMAP];
};

__device__ __forceinline__ void mbar_init(uint32_t bar, int cnt) {
    asm volatile("mbarrier.init.shared::cta.b64 [%0], %1;" ::"r"(bar), "r"(cnt));
}
__device__ __forceinline__ void mbar_expect(uint32_t bar, uint32_t bytes) {
    asm volatile("mbarrier.arrive.expect_tx.shared::cta.b64 _, [%0], %1;" ::"r"(bar), "r"(bytes) : "memory");
}
__device__ __forceinline__ void mbar_arrive(uint32_t bar) {
    asm volatile("mbarrier.arrive.shared::cta.b64 _, [%0];" ::"r"(bar) : "memory");
}
__device__ __forceinline__ void mbar_wait(uint32_t bar, uint32_t parity) {
    asm volatile("{\n.reg .pred p;\n.reg .u32 c;\n"
                 "mbarrier.try_wait.parity.shared::cta.b64 p, [%0], %1;\n@p bra DONE;\nmov.u32 c, %2;\n"
                 "AGAIN:\nmbarrier.try_wait.parity.shared::cta.b64 p, [%0], %1;\nsub.u32 c, c, 1;\n"
                 "setp.eq.or.u32 p, c, 0, p;\n@!p bra AGAIN;\nDONE:\n}"
                 ::"r"(bar), "r"(parity), "n"(SPIN_LIMIT) : "memory");
}
__device__ __forceinline__ bool mbar_test(uint32_t bar, uint32_t parity) {
    uint32_t ok;
    asm volatile("{\n.reg .pred p;\nmbarrier.test_wait.parity.shared::cta.b64 p, [%1], %2;\nselp.u32 %0, 1, 0, p;\n}"
                 : "=r"(ok) : "r"(bar), "r"(parity) : "memory");
    return ok;
}
__device__ __forceinline__ void tma3d_hint(uint32_t dst, const CUtensorMap* m, int x, int y, int z, uint32_t bar, u64 pol) {
    asm volatile("cp.async.bulk.tensor.3d.shared::cluster.global.mbarrier::complete_tx::bytes.L2::cache_hint"
                 " [%0], [%1, {%2, %3, %4}], [%5], %6;"
                 ::"r"(dst), "l"(m), "r"(x), "r"(y), "r"(z), "r"(bar), "l"(pol) : "memory");
}
__device__ __forceinline__ void tma3d(uint32_t dst, const CUtensorMap* m, int x, int y, int z, uint32_t bar) {
    asm volatile("cp.async.bulk.tensor.3d.shared::cluster.global.mbarrier::complete_tx::bytes [%0], [%1, {%2, %3, %4}], [%5];"
                 ::"r"(dst), "l"(m), "r"(x), "r"(y), "r"(z), "r"(bar) : "memory");
}
__device__ __forceinline__ void bar_sync(int id, int n) { asm volatile("bar.sync %0, %1;" ::"r"(id), "r"(n) : "memory"); }
__device__ __forceinline__ void bar_arrive(int id, int n) { asm volatile("bar.arrive %0, %1;" ::"r"(id), "r"(n) : "memory"); }
__device__ __forceinline__ void ldsm4(uint32_t (&r)[4], uint32_t a) {
    asm volatile("ldmatrix.sync.aligned.m8n8.x4.shared.b16 {%0,%1,%2,%3}, [%4];"
                 : "=r"(r[0]), "=r"(r[1]), "=r"(r[2]), "=r"(r[3]) : "r"(a) : "memory");
}
__device__ __forceinline__ void ldsm4t(uint32_t (&r)[4], uint32_t a) {
    asm volatile("ldmatrix.sync.aligned.m8n8.x4.trans.shared.b16 {%0,%1,%2,%3}, [%4];"
                 : "=r"(r[0]), "=r"(r[1]), "=r"(r[2]), "=r"(r[3]) : "r"(a) : "memory");
}
__device__ __forceinline__ void mma(float (&c)[4], uint32_t a0, uint32_t a1, uint32_t a2, uint32_t a3, uint32_t b0, uint32_t b1) {
    asm volatile("mma.sync.aligned.m16n8k16.row.col.f32.bf16.bf16.f32 {%0,%1,%2,%3}, {%4,%5,%6,%7}, {%8,%9}, {%0,%1,%2,%3};"
                 : "+f"(c[0]), "+f"(c[1]), "+f"(c[2]), "+f"(c[3])
                 : "r"(a0), "r"(a1), "r"(a2), "r"(a3), "r"(b0), "r"(b1));
}
__device__ __forceinline__ uint32_t movm(uint32_t a) {
    uint32_t d;
    asm volatile("movmatrix.sync.aligned.m8n8.trans.b16 %0, %1;" : "=r"(d) : "r"(a));
    return d;
}
__device__ __forceinline__ uint32_t lds32(uint32_t a) { uint32_t v; asm volatile("ld.volatile.shared.b32 %0, [%1];" : "=r"(v) : "r"(a) : "memory"); return v; }
__device__ __forceinline__ float2 lds64f(uint32_t a) { float2 v; asm volatile("ld.shared.v2.f32 {%0,%1}, [%2];" : "=f"(v.x), "=f"(v.y) : "r"(a) : "memory"); return v; }
__device__ __forceinline__ uint4 lds128(uint32_t a) { uint4 v; asm volatile("ld.shared.v4.b32 {%0,%1,%2,%3}, [%4];" : "=r"(v.x), "=r"(v.y), "=r"(v.z), "=r"(v.w) : "r"(a) : "memory"); return v; }
__device__ __forceinline__ void sts32(uint32_t a, uint32_t v) { asm volatile("st.shared.b32 [%0], %1;" ::"r"(a), "r"(v) : "memory"); }
__device__ __forceinline__ void sts16(uint32_t a, uint16_t v) { asm volatile("st.shared.b16 [%0], %1;" ::"r"(a), "h"(v) : "memory"); }
__device__ __forceinline__ void sts64(uint32_t a, uint32_t x, uint32_t y) { asm volatile("st.shared.v2.b32 [%0], {%1,%2};" ::"r"(a), "r"(x), "r"(y) : "memory"); }
__device__ __forceinline__ void sts128(uint32_t a, uint32_t x, uint32_t y, uint32_t z, uint32_t w) {
    asm volatile("st.shared.v4.b32 [%0], {%1,%2,%3,%4};" ::"r"(a), "r"(x), "r"(y), "r"(z), "r"(w) : "memory");
}
__device__ __forceinline__ void sts128f(uint32_t a, const float (&c)[4]) {
    sts128(a, __float_as_uint(c[0]), __float_as_uint(c[1]), __float_as_uint(c[2]), __float_as_uint(c[3]));
}

__device__ __forceinline__ float sel4(const float (&c)[4], int t) { return (t & 2) ? ((t & 1) ? c[3] : c[2]) : ((t & 1) ? c[1] : c[0]); }

template <int LUT>
__device__ __forceinline__ uint32_t lop3(uint32_t a, uint32_t b, uint32_t c) {
    uint32_t d;
    asm("lop3.b32 %0, %1, %2, %3, %4;" : "=r"(d) : "r"(a), "r"(b), "r"(c), "n"(LUT));
    return d;
}
__device__ __forceinline__ uint32_t pin(uint32_t v) { return __shfl_xor_sync(0xffffffffu, v, 0); }
template <typename T>
__device__ __forceinline__ T* at(T* base, uint32_t bytes) { return (T*)((const char*)base + bytes); }

__device__ __forceinline__ uint32_t clock32(uint32_t dep) {
    uint32_t t;
    asm volatile("{\n.reg .pred p;\nsetp.eq.u32 p, %1, 0x9e3779b9;\n@p nanosleep.u32 1;\nmov.u32 %0, %clock;\n}" : "=r"(t) : "r"(dep) : "memory");
    return t;
}

__device__ __forceinline__ uint32_t nz(uint32_t v) { return v ? v : 0x80000000u; }
__device__ __forceinline__ void st1(uint32_t* p, uint32_t a) { asm volatile("st.relaxed.gpu.global.b32 [%0], %1;" ::"l"(p), "r"(a) : "memory"); }
__device__ __forceinline__ void st2(uint32_t* p, uint32_t a, uint32_t b) {
    asm volatile("st.relaxed.gpu.global.v2.b32 [%0], {%1,%2};" ::"l"(p), "r"(a), "r"(b) : "memory");
}
__device__ __forceinline__ void zero4(uint32_t* p) { asm volatile("st.relaxed.gpu.global.v4.b32 [%0], {%1,%1,%1,%1};" ::"l"(p), "r"(0) : "memory"); }
__device__ __forceinline__ void put1d(uint32_t* p, uint32_t a) { a = nz(a), st1(p, a), st1(p + 1024, a); }
__device__ __forceinline__ void put2d(uint32_t* p, uint32_t a, uint32_t b) { a = nz(a), b = nz(b), st2(p, a, b), st2(p + 1024, a, b); }
__device__ __forceinline__ uint32_t ld1(const uint32_t* p) {
    uint32_t v;
    asm volatile("ld.relaxed.gpu.global.b32 %0, [%1];" : "=r"(v) : "l"(p) : "memory");
    return v;
}
template <int N, int V>
__device__ __forceinline__ void fetch(const uint32_t* p, int stride, uint32_t (&a)[N * V]) {
#pragma unroll
    for (int i = 0; i < N; i++) {
        if (V == 1)
            asm volatile("{\n.reg .pred p;\nsetp.eq.u32 p, %0, 0;\n@p ld.relaxed.gpu.global.b32 %0, [%1];\n}"
                         : "+r"(a[i]) : "l"(p + i * stride) : "memory");
        if (V == 4)
            asm volatile("{\n.reg .pred p;\nsetp.eq.u32 p, %4, 0;\n@p ld.relaxed.gpu.global.v4.b32 {%0,%1,%2,%3}, [%5];\n}"
                         : "+r"(a[V * i]), "+r"(a[V * i + V / 4]), "+r"(a[V * i + V / 2]), "+r"(a[V * i + V - 1])
                         : "r"(min(min(a[V * i], a[V * i + V / 4]), min(a[V * i + V / 2], a[V * i + V - 1]))), "l"(p + i * stride) : "memory");
    }
}
template <int N>
__device__ __forceinline__ bool missing(const uint32_t (&a)[N]) {
    uint32_t lo = a[0];
#pragma unroll
    for (int i = 1; i < N; i++) lo = min(lo, a[i]);
    return __any_sync(0xffffffffu, lo == 0);
}
template <int N, int V>
__device__ __forceinline__ void get(const uint32_t* p, int stride, uint32_t (&a)[N * V]) {
    int it = 0;
    do fetch<N, V>(p, stride, a);
    while (missing(a) & (++it < SPIN_LIMIT));
}
__device__ __forceinline__ void cp16(uint32_t dst, const void* src) {
    asm volatile("cp.async.cg.shared.global [%0], [%1], 16;" ::"r"(dst), "l"(src) : "memory");
}

__device__ __forceinline__ uint32_t pack2(float lo, float hi) {
    uint32_t r;
    asm("cvt.rn.bf16x2.f32 %0, %1, %2;" : "=r"(r) : "f"(hi), "f"(lo));
    return r;
}
__device__ __forceinline__ float rbf(float x) { return __uint_as_float(pack2(0.f, x)); }
__device__ __forceinline__ float blo(uint32_t v) { return __uint_as_float(v << 16); }
__device__ __forceinline__ float bhi(uint32_t v) { return __uint_as_float(v & 0xffff0000u); }
__device__ __forceinline__ uint32_t badd2(uint32_t a, uint32_t b) { uint32_t r; asm("add.rn.bf16x2 %0, %1, %2;" : "=r"(r) : "r"(a), "r"(b)); return r; }
__device__ __forceinline__ uint32_t bsub2(uint32_t a, uint32_t b) { uint32_t r; asm("sub.rn.bf16x2 %0, %1, %2;" : "=r"(r) : "r"(a), "r"(b)); return r; }
__device__ __forceinline__ uint32_t bmul2(uint32_t a, uint32_t b) { uint32_t r; asm("mul.rn.bf16x2 %0, %1, %2;" : "=r"(r) : "r"(a), "r"(b)); return r; }
__device__ __forceinline__ float ex2(float x) { float r; asm("ex2.approx.ftz.f32 %0, %1;" : "=f"(r) : "f"(x)); return r; }
__device__ __forceinline__ float rcp(float x) { float r; asm("rcp.approx.ftz.f32 %0, %1;" : "=f"(r) : "f"(x)); return r; }
__device__ __forceinline__ float sqrt_f(float x) { float r; asm("sqrt.approx.ftz.f32 %0, %1;" : "=f"(r) : "f"(x)); return r; }
constexpr float LOG2E = 1.4426950408889634f;
constexpr uint32_t ONE2 = 0x3f803f80u;
__device__ __forceinline__ float sigmoid_f(float x) { return rcp(1.0f + ex2(-LOG2E * x)); }
__device__ __forceinline__ uint32_t silu2(uint32_t v) {
    const float a = blo(v), b = bhi(v);
    return pack2(a * sigmoid_f(a), b * sigmoid_f(b));
}
__device__ __forceinline__ float quad_sum(float v) {
    v += __shfl_xor_sync(0xffffffffu, v, 1);
    return v + __shfl_xor_sync(0xffffffffu, v, 2);
}
__device__ __forceinline__ void ln_partial(const uint32_t (&v)[8], uint32_t dst, bool writer) {
    float s0 = 0.f, s1 = 0.f;
#pragma unroll
    for (int i = 0; i < 8; i++) {
        s0 += blo(v[i]);
        s1 += bhi(v[i]);
    }
    const float mean = quad_sum(s0 + s1) * (1.0f / 64);
    s0 = s1 = 0.f;
#pragma unroll
    for (int i = 0; i < 8; i++) {
        const float a = blo(v[i]) - mean, b = bhi(v[i]) - mean;
        s0 = fmaf(a, a, s0);
        s1 = fmaf(b, b, s1);
    }
    s0 = quad_sum(s0 + s1);
    if (writer) sts64(dst, __float_as_uint(mean), __float_as_uint(s0));
}
__device__ __forceinline__ void ln_combine(uint32_t src, uint32_t& mean2, float& inv) {
    float m[10], q0 = 0.f, q1 = 0.f, s = 0.f;
#pragma unroll
    for (int i = 0; i < 5; i++) {
        const uint4 v = lds128(src + i * 16);
        m[2 * i] = __uint_as_float(v.x);
        m[2 * i + 1] = __uint_as_float(v.z);
        q0 += __uint_as_float(v.y);
        if (i < 4) q1 += __uint_as_float(v.w);
    }
    const float mean = (((m[0] + m[1]) + (m[2] + m[3])) + ((m[4] + m[5]) + (m[6] + m[7])) + m[8]) * (1.0f / 9);
#pragma unroll
    for (int i = 0; i < 9; i++) s = fmaf(m[i] - mean, m[i] - mean, s);
    const float var = fmaf(s, 64.f, q0 + q1) * (1.0f / DM);
    mean2 = pack2(mean, mean);
    inv = rcp(rbf(sqrt_f(rbf(rbf(var) + 1e-5f))));
}
__device__ __forceinline__ uint32_t modulate2(uint32_t x, uint32_t mean2, float inv, uint32_t shift, uint32_t onep) {
    const uint32_t d = bsub2(x, mean2);
    return badd2(bmul2(pack2(blo(d) * inv, bhi(d) * inv), onep), shift);
}
template <int N>
__device__ __forceinline__ void sum_frags(float (&c)[4], uint32_t addr, int stride) {
#pragma unroll
    for (int w = 0; w < N; w++) {
        const uint4 v = lds128(addr + w * stride);
        c[0] += __uint_as_float(v.x); c[1] += __uint_as_float(v.y);
        c[2] += __uint_as_float(v.z); c[3] += __uint_as_float(v.w);
    }
}

template <int ST>
__device__ __forceinline__ void project(uint32_t sm, const uint32_t* src, uint32_t* dst, uint32_t wa, uint32_t ws, uint32_t l16, int nsync, int warp, int lane) {
    constexpr int NW = ST ? 9 : 8, NI = ST ? 5 : 4;
    const uint32_t wbar = sm + OFF_BAR + (ST ? BAR_WD : BAR_WO) * 8, stage = sm + (ST ? OFF_WO : OFF_P) + l16;
    if (warp < NW) {
        uint32_t b[4] = {};
        if (ST) get<4, 1>(src, 32, b);
        else get<1, 4>(src, 0, b);
        if (warp == 0) TSL(ST ? 24 : 21);
        sts128(stage + warp * 512, b[0], b[2], b[1], b[3]);
    }
    bar_sync(ST ? 6 : 3, nsync);
    float acc[4][4] = {};
#pragma unroll
    for (int j = 0; j < NI; j++) {
        const int i0 = j == 4 ? 8 : ST ? 2 * ((j + 3) & 3) : 2 * j, n = j == 4 ? 1 : 2;
        uint32_t w[2][4];
        uint4 f[2];
#pragma unroll
        for (int i = 0; i < n; i++) f[i] = lds128(stage + (i0 + i) * 512);
        mbar_wait(wbar + j * 8, 0);
#pragma unroll
        for (int i = 0; i < n; i++) ldsm4t(w[i], wa + (i0 + i) * ws);
#pragma unroll
        for (int i = 0; i < n; i++) {
            mma(acc[2 * i], f[i].x, f[i].y, f[i].z, f[i].w, w[i][0], w[i][1]);
            mma(acc[2 * i + 1], f[i].x, f[i].y, f[i].z, f[i].w, w[i][2], w[i][3]);
        }
    }
    const float s0 = (acc[2][0] + acc[3][2]) + (acc[0][0] + acc[1][2]), s1 = (acc[2][1] + acc[3][3]) + (acc[0][1] + acc[1][3]);
    st2(dst, (__float_as_uint(s0) | 1) ^ ST, (__float_as_uint(s1) | 1) ^ ST);
}

template <int ST, int N, typename F>
__device__ __forceinline__ float2 reduce_parts(const uint32_t* src, F arrived) {
    uint32_t a[2 * N] = {}, bad[N], any;
    int it = 0;
#pragma unroll
    for (int i = 0; i < N; i++) bad[i] = 1;
    do {
#pragma unroll
        for (int i = 0; i < N; i++)
            asm volatile("{\n.reg .pred p;\nsetp.ne.u32 p, %2, 0;\n@p ld.relaxed.gpu.global.v2.b32 {%0,%1}, [%3];\n}"
                         : "+r"(a[2 * i]), "+r"(a[2 * i + 1]) : "r"(bad[i]), "l"(src + i * 64) : "memory");
#pragma unroll
        for (int i = 0; i < N; i++) bad[i] = lop3<ST ? 0xa8 : 0x2a>(a[2 * i], a[2 * i + 1], 1);
        any = 0;
#pragma unroll
        for (int i = 0; i < N; i += 4) any = lop3<0xfe>(any, lop3<0xfe>(bad[i], bad[i + 1], bad[i + 2]), bad[i + 3]);
    } while (__any_sync(0xffffffffu, any != 0) & (++it < SPIN_LIMIT));
    arrived();
    float f[8];
#pragma unroll
    for (int i = 0; i < 8; i++) {
        f[i] = __uint_as_float(a[i]) + __uint_as_float(a[i + 8]);
        if (N == 16) f[i] += __uint_as_float(a[(i + 16) % (2 * N)]) + __uint_as_float(a[(i + 24) % (2 * N)]);
    }
    return make_float2((f[0] + f[2]) + (f[4] + f[6]), (f[1] + f[3]) + (f[5] + f[7]));
}

__global__ void __launch_bounds__(NTHREADS, 1) fused_kernel(const Params P, const __grid_constant__ Maps T) {
    extern __shared__ __align__(1024) char smem_raw[];
    constexpr uint32_t sm = 1024;
    const int tid = threadIdx.x, lane = tid & 31;
    const int cta = blockIdx.x, grp = cta >> 3, sub = cta & 7;
    const uint32_t bars = sm + OFF_BAR;
    const int row0 = (sub * HKV + grp) * SK + (SK - WIN);
    if (tid >> 5 == 9) {
#pragma unroll
        for (int i = 0; i < PFK; i++) asm volatile("prefetch.global.L2 [%0];" ::"l"(P.k + (size_t)row0 * DH + (lane + i * 32) * 64) : "memory");
    }
    u64 pol;
    asm volatile("createpolicy.fractional.L2::evict_first.b64 %0, 1.0;" : "=l"(pol));
    if (tid == NCW * 32) {
        TS(0);
        const int n0 = cta < 90 ? 0 : 3;
#pragma unroll
        for (int i = 0; i < 6; i++) mbar_init(bars + i * 8, 1);
        asm volatile("fence.mbarrier_init.release.cluster;" ::: "memory");
#pragma unroll
        for (int i = 0; i < 3; i++) {
            mbar_expect(bars + (n0 + i) * 8, 12288);
            tma3d(sm + OFF_WM + (n0 + i) * 12288, &T.m[cta < 36 ? M_WA : cta < 90 ? M_WM : M_WQ], cta < 36 ? 16 * cta : 32 * cta,
                  i * 192, 0, bars + (n0 + i) * 8);
            TI(n0 + i);
        }
        TS(26);
    }
    if (tid == NCW * 32 + 32) {
#pragma unroll
        for (int i = 0; i < 4; i++) mbar_init(bars + (BAR_FULL + i) * 8, 1);
        asm volatile("fence.mbarrier_init.release.cluster;" ::: "memory");
#pragma unroll
        for (int t = 0; t < NK0; t++) {
            mbar_expect(bars + (BAR_FULL + t) * 8, TILE_BYTES);
            tma3d_hint(sm + OFF_RING + t * TILE_BYTES, &T.m[M_K], 0, row0 + t * 32, 0, bars + (BAR_FULL + t) * 8, pol);
            TI(6 + t);
        }
    }
    if (tid < 288 && cta < 90) {
#pragma unroll
        for (int i = 0; i < 2; i++) {
            const int row = (lane >> 3) + 4 * i, so = row * DM + (tid >> 5) * 64 + (lane & 7) * 8;
            const uint32_t d = sm + OFF_RED + (tid >> 5) * 2048 + row * 128 + (((lane & 7) ^ row) << 4);
            cp16(d, P.c + so);
            if (cta < 36) cp16(d + 1024, P.x + so);
        }
    }
    uint32_t* const g0 = P.scratch;
    const uint32_t epoch = ld1(g0 + G_EPOCH);
    const int warp = __shfl_sync(0xffffffffu, tid >> 5, 0);

    if (warp >= NCW) {
        const int pw = warp - NCW;
        bar_arrive(1, (NCW + 1) * 32);
        if (pw && lane < M_WQ) asm volatile("prefetch.tensormap [%0];" ::"l"(&T.m[M_WQ - lane]) : "memory");
        if (tid == NCW * 32) sts32(sm + OFF_WIN, 0);
        __syncwarp();
        bar_sync(15, NTHREADS);
        if (lane == 0) {
            if (pw == 0 && cta < 90) {
#pragma unroll 1
                for (int n = 3; n < 6; n++) {
                    mbar_expect(bars + n * 8, 12288);
                    mbar_wait(bars + (n - 3) * 8, 0);
                    tma3d(sm + OFF_WM + n * 12288, &T.m[M_WQ], 32 * cta, (n - 3) * 192, 0, bars + n * 8);
                    TI(n);
                }
            }
#pragma unroll 1
            for (int t = NK0 + (1 - pw) * NK1; t < NK0 + NK1 + 3 * (1 - pw); t++) {
                mbar_expect(bars + (BAR_FULL + t) * 8, TILE_BYTES);
                mbar_wait(bars + (t + (pw ? BAR_FULL - NK1 : 3 - NK0 - NK1)) * 8, 0);
                tma3d_hint(sm + OFF_RING + t * TILE_BYTES, &T.m[M_K], 0, row0 + t * 32, 0, bars + (BAR_FULL + t) * 8, pol);
                TI(6 + t);
            }
            if (pw == 0) {
                auto on_time = [&](int due, uint32_t bar, uint32_t parity) {
                    uint32_t origin;
                    do origin = lds32(sm + OFF_WIN);
                    while (origin && (int)(clock32(0) - origin - due) < 0 && !mbar_test(bar, parity));
                };
#pragma unroll 1
                for (int t = NK0 + NK1 + 3; t < 2 * NT; t++) {
                    if (t == 14 && cta < 90) mbar_wait(bars + BAR_WMF * 8, 0);
                    if (t == 15) TS(30);
                    const uint32_t fb = bars + (BAR_FULL + (t & 15)) * 8;
                    const int hi = t - (lds32(sm + OFF_WIN) ? W_HI : W_0), lo = t - W_LO;
                    mbar_wait(fb + (BAR_EMPTY - BAR_FULL) * 8, (~t >> 4) & 1);
                    mbar_expect(fb, TILE_BYTES);
                    mbar_wait(bars + (BAR_FULL + (hi & 15)) * 8, (hi >> 4) & 1);
                    on_time(t * TAU - L_KV, bars + (BAR_FULL + (lo & 15)) * 8, (lo >> 4) & 1);
                    tma3d_hint(sm + OFF_RING + (t & 15) * TILE_BYTES, &T.m[t >> 6], 0, row0 + (t & (NT - 1)) * 32, 0, fb, pol);
                    TI(6 + t);
                    if (t == T_CLEAR) mbar_arrive(bars + (BAR_SYNC + 1) * 8);
                }
                mbar_wait(bars + BAR_SYNC * 8, 0);
                auto window = [&](int b, int lead) {
                    mbar_wait(bars + (b - W_HT) * 8, b - W_HT < BAR_WO);
                    on_time((2 * NT - 1) * TAU + (b - BAR_WO + 1) * TAU_W - lead, bars + (b - W_LO) * 8, b - W_LO < BAR_WO);
                };
#pragma unroll 1
                for (int i = 0; i < 4; i++) {
                    window(BAR_WO + i, L_WO);
                    tma3d(sm + OFF_WO + i * 8192, &T.m[M_OD], 64 * sub, grp * 256 + i * 64, P.zo, bars + (BAR_WO + i) * 8);
                    tma3d(sm + OFF_OX + i * 1024, &T.m[M_OX], 512 + 8 * sub, grp * 256 + i * 64, P.zo, bars + (BAR_WO + i) * 8);
                    TI(134 + i);
                }
                TS(28);
#pragma unroll 1
                for (int i = 0; i < 9; i++) {
                    mbar_wait(bars + (BAR_EMPTY + i) * 8, 1);
                    window(BAR_GU + i, L_GU);
                    tma3d(sm + OFF_GU + i * 8192, &T.m[M_GU], grp * 288 + 32 * sub, i * 64, 0, bars + (BAR_GU + i) * 8);
                    if (sub < 4) tma3d(sm + OFF_GX + i * 2048, &T.m[M_GX], grp * 288 + 256 + 8 * sub, i * 64, 0, bars + (BAR_GU + i) * 8);
                    TI(138 + i);
                }
                TS(29);
#pragma unroll 1
                for (int i = 0; i < 5; i++) {
                    const int blk = i < 4 ? (i + 3) & 3 : 4, r = min(blk * 64, 224);
                    mbar_wait(bars + (BAR_EMPTY + 9 + blk) * 8, 1);
                    window(BAR_WD + i, L_WD + (i == 4 ? L_LAST : 0));
                    tma3d(sm + OFF_WD + r * 128, &T.m[M_OD], 64 * sub, grp * 288 + r, P.zo ^ 1, bars + (BAR_WD + i) * 8);
                    tma3d(sm + OFF_DX + r * 16, &T.m[M_OX], 512 + 8 * sub, grp * 288 + r, P.zo ^ 1, bars + (BAR_WD + i) * 8);
                    TI(147 + i);
                }
                if (cta < 72) {
                    mbar_wait(bars + (BAR_EMPTY + 14) * 8, 1);
                    mbar_wait(bars + (BAR_EMPTY + 15) * 8, 1);
#pragma unroll
                    for (int i = 0; i < 3; i++) mbar_expect(bars + (BAR_GB + i) * 8, 3072);
                    window(BAR_WD + 5, L_GB);
#pragma unroll
                    for (int i = 0; i < 3; i++) tma3d(sm + OFF_GB + i * 3072, &T.m[M_GB], 5 * DM + 8 * cta, i * 192, 0, bars + (BAR_GB + i) * 8);
                }
            } else {
#pragma unroll 1
                for (int i = BAR_WO; i < BAR_WD + 5; i++) mbar_expect(bars + i * 8, i < BAR_GU || i >= BAR_WD ? 9216 : sub < 4 ? 10240 : 8192);
                mbar_arrive(bars + BAR_SYNC * 8);
                uint32_t* const cnt = g0 + (epoch & 1) * G_SET + G_CNT;
#pragma unroll 1
                for (int t = cta & 3; t < 140; t += 4) {
                    const uint32_t bar = bars + (BAR_FULL + (t < 2 * NT ? t & 15 : t - 112)) * 8;
                    mbar_wait(bar, (t >> 4) & 1);
                    if (t < 2 * NT) mbar_arrive(bar + (BAR_EMPTY - BAR_FULL) * 8);
                    const uint32_t t0 = clock32(0);
                    const int c = (int)atomicAdd(cnt, 1u) - 16;
                    const uint32_t o = t0 + ((clock32(c) - t0) >> 1) - ((c * TAU + max(c - 32 * (2 * NT - 1), 0) * (TAU_W - TAU)) >> 5);
                    if (t >= T_PACE) sts32(sm + OFF_WIN, o | 1);
                    if ((t >> 2) == 8 || (t >> 2) == 24) TL(t >> 2, ((clock32(0) - t0) * 9) >> 4);
                }
            }
        }
        return;
    }

    if (lane == 0) {
#pragma unroll
        for (int i = 0; i < 6; i++) {
            const int b = 10 + warp * 6 + i;
            mbar_init(bars + b * 8, b >= BAR_EMPTY && b < BAR_EMPTY + 16 && ((b ^ cta) & 3) == 0 ? 2 : 1);
        }
        asm volatile("fence.mbarrier_init.release.cluster;" ::: "memory");
    }
    __syncwarp();
    if (warp < 9) bar_arrive(15, NTHREADS);
    const int g = lane >> 2, t4 = lane & 3;
    uint32_t* const gs = g0 + (epoch & 1) * G_SET;

    uint32_t sc[8] = {};
    if (warp < 9) {
        const int off_h = (cta < 36 ? dual(D_H + 2 * cta * 32) : G_M + 4 * (cta - 36) * 32) + tid;
        const int off_h2 = off_h + (cta < 36 ? 1024 : 64);
        const int off_q = dual(D_Q + g * (HQ * 64) + cta * 16) + warp * 8 + t4 * 2;
        uint32_t bf[8] = {}, xp = 0, mean2 = 0;
        float inv = 0.f;
        if (cta < 36) xp = __ldg(reinterpret_cast<const uint32_t*>(P.x) + g * (DM / 2) + 8 * cta + 4 * (warp & 1) + t4);
        if (warp < 2) {
            st2(gs + off_q, 0, 0), st2(gs + off_q + 1024, 0, 0);
            if (cta < 36) st1(gs + off_h, 0), st1(gs + off_h2, 0);
        }
        if (cta < 90) {
            asm volatile("cp.async.wait_all;" ::: "memory");
            __syncwarp();
            const uint32_t fa = sm + OFF_RED + warp * 2048 + (lane & 7) * 128 + (((lane >> 3) ^ (lane & 7)) << 4);
            ldsm4(reinterpret_cast<uint32_t(&)[4]>(bf[0]), fa);
            ldsm4(reinterpret_cast<uint32_t(&)[4]>(bf[4]), fa ^ 64);
            if (cta < 36) {
                uint32_t xv[8];
                ldsm4(reinterpret_cast<uint32_t(&)[4]>(xv[0]), fa + 1024);
                ldsm4(reinterpret_cast<uint32_t(&)[4]>(xv[4]), (fa ^ 64) + 1024);
                ln_partial(xv, sm + OFF_ST + g * 80 + warp * 8, t4 == 0);
            }
#pragma unroll
            for (int i = 0; i < 8; i++) sc[i] = bf[i] = silu2(bf[i]);
        }
        if (warp == 0) TSL(18);
        bar_sync(1, (NCW + 1) * 32);
        if (cta < 36 && warp < 2) ln_combine(sm + OFF_ST + g * 80, mean2, inv);
        const int r = warp * 64 + (lane >> 4) * 8 + (lane & 7), hi8 = (lane >> 3) & 1, box = warp / 3;
#pragma unroll 1
        for (int pass = cta < 90 ? 0 : 1; pass < 2; pass++) {
            const bool pa = pass == 0 && cta < 36;
            const uint32_t ab = sm + OFF_WM + pass * 36864 +
                                (pa ? (box + hi8) * 6144 + r * 32 + ((lane & 4) << 2) : r * 64 + (((2 * hi8) ^ ((r >> 1) & 3)) << 4));
            const uint32_t as = pa ? 512 : 1024, red = sm + OFF_RED + pass * 9216;
            mbar_wait(bars + (pass * 3 + box) * 8, 0);
            if (warp == 8) TSL(pass ? 31 : 19);
            uint32_t a[4][2][4];
#pragma unroll
            for (int i = 0; i < 4; i++) {
                ldsm4t(a[i][0], ab + i * as);
                ldsm4t(a[i][1], (ab ^ 16) + i * as);
            }
            if (pass) {
                bar_sync(8, NCW * 32);
#pragma unroll
                for (int i = 0; i < 8; i++) bf[i] = 0;
                const uint32_t* const src_h = gs + near(D_H + warp * 256, lds32(sm + OFF_WIN + 4)) + lane;
                get<8, 1>(src_h, 32, bf);
                if (warp == 0) TSL(3);
            }
            float acc[2][4] = {};
#pragma unroll
            for (int i = 0; i < 4; i++)
#pragma unroll
                for (int m = 0; m < 2; m++) mma(acc[m], a[i][m][0], a[i][m][1], a[i][m][2], a[i][m][3], bf[2 * i], bf[2 * i + 1]);
            sts128f(red + tid * 16, acc[0]);
            sts128f(red + 4608 + tid * 16, acc[1]);
            bar_sync(3, 288);
            if (warp < 2) {
                float c[4] = {};
                sum_frags<9>(c, red + warp * 4608 + lane * 16, 512);
                uint32_t lo = movm(pack2(c[0], c[1])), hi = movm(pack2(c[2], c[3]));
                if (pass) {
                    put2d(gs + off_q, lo, hi);
                    if (warp == 0) TSL(4);
                } else {
                    const uint32_t hi1 = badd2(hi, ONE2);
                    if (pa) hi = lo = modulate2(xp, mean2, inv, lo, hi1);
                    if (cta >= 72) lo = badd2(lo, ONE2), hi = hi1;
                    st1(gs + off_h, nz(lo));
                    st1(gs + off_h2, nz(hi));
                    if (warp == 0 && pa) TSL(2);
                }
            } else if (tid == 64 && pass == 0) {
                mbar_arrive(bars + BAR_WMF * 8);
            }
        }
    } else {
        if ((uint32_t)__cvta_generic_to_shared(smem_raw) != sm) __trap();
        uint32_t* const ping = g0 + dual(D_PING) + cta * 8;
        if (lane < 16) st1(ping + (lane >> 3) * 1024 + (lane & 7), 0);
        bar_sync(15, NTHREADS);
        uint32_t best[2] = {~0u, ~0u}, v = 0;
#pragma unroll 1
        for (int part = 0; part < 2; part++) {
            if (lane == 0) {
#pragma unroll 1
                for (int r = part ? NPING1 : NPING0; r > 0; r--) {
#pragma unroll
                    for (int k = 0; k < 2; k++) {
                        const uint32_t t0 = clock32(v);
                        v = atomicExch(ping + k * 1024, t0);
                        best[k] = min(best[k], clock32(v) - t0);
                    }
                }
                sts32(sm + OFF_WIN + 4 + 4 * part, ((best[1] < best[0]) ^ __popc(D_PING & 0x16400)) & 1);
            }
            __syncwarp();
            if (part) break;
            TSL(20);
            bar_arrive(8, NCW * 32);
            mbar_wait(bars + 5 * 8, 0);
            uint32_t a[4] = {};
            get<1, 4>(gs + near(D_Q + (sub * HQ + 2 * grp) * 64, lds32(sm + OFF_WIN + 4)) + lane * 4, 0, a);
            sts128(sm + OFF_QS + lane * 16, a[0], a[1], a[2], a[3]);
            __syncwarp();
            TSL(5);
            bar_arrive(4, 288);
        }
#pragma unroll
        for (int i = lane; i < 72; i += 32) cp16(sm + OFF_WR + i * 16, P.wr + i * 8);
        __syncwarp();
        if (cta < 72 && lane < 16) st1(g0 + ((epoch ^ lane >> 3) & 1) * G_SET + G_SIDE + cta * 8 + (lane & 7), lane < 8 ? 1 + lds32(sm + OFF_WIN + 8) : 0);
        asm volatile("cp.async.wait_all;" ::: "memory");
        __syncwarp();
        bar_arrive(2, NCW * 32);
        auto clear_late = [&](uint32_t* set) {
#pragma unroll 1
            for (int c = 0; c < 2; c++, set += 1024) {
                zero4(set + dual(D_O + cta * 128) + lane * 4);
                zero4(set + dual(D_ACT + (grp * 36 + 4 * sub) * 32) + lane * 4);
                if (lane < 8 ? sub < 4 : lane < 16 && cta < 72)
                    zero4(set + dual(lane < 8 ? D_ACT + (grp * 36 + 32 + sub) * 32 : D_X1 + cta * 32) + (lane & 7) * 4);
            }
        };
        auto clear_next = [&] {
            uint32_t* const nx = g0 + (~epoch & 1) * G_SET;
            uint32_t* const q = nx + dual(D_Q + g * (HQ * 64) + cta * 16) + t4 * 4;
            mbar_wait(bars + (BAR_GU + 5) * 8, 0);
            clear_late(nx);
            zero4(q), zero4(q + 1024);
            if (cta < 90) zero4(nx + (cta < 36 ? dual(D_H + 2 * cta * 32) + (lane >> 4) * (1024 - 64) : G_M + 4 * (cta - 36) * 32) + lane * 4);
            if (cta == 0 && lane == 0) st1(nx + G_CNT, 0);
            __syncwarp();
        };
        mbar_wait(bars + (BAR_SYNC + 1) * 8, 0);
        clear_late(gs);
        __syncwarp();
        if (cta >= 72) {
            bar_arrive(5, NCW * 32);
            clear_next();
            return;
        }
        const uint32_t io = pin(4 * (g * (DM / 2) + 4 * cta + t4));
        uint32_t x = __ldg(at(reinterpret_cast<const uint32_t*>(P.x), io)), ga[1] = {};
        get<1, 1>(gs + G_M + cta * 32 + lane, 0, ga);
        const uint32_t src_p = pin(4 * (near(d_part(cta), lds32(sm + OFF_WIN + 8)) + lane * 2));
        const uint32_t dst_x = pin(4 * ((epoch & 1) * G_SET + dual(D_X1 + cta * 32) + lane));
        bar_sync(5, NCW * 32);
        float2 y = reduce_parts<0, 16>(at(g0, src_p), [] {}), y2;
        x = badd2(x, bmul2(ga[0], pack2(y.x, y.y)));
        put1d(at(g0, dst_x), x);
        TSL(10);
        clear_next();
        bar_sync(6, NCW * 32);
        const uint4 r0 = lds128(sm + OFF_RT + g * 48), r1 = lds128(sm + OFF_RT + g * 48 + 16);
        float r = __uint_as_float(lds32(sm + OFF_RT + g * 48 + 32));
        r += ((__uint_as_float(r0.x) + __uint_as_float(r0.y)) + (__uint_as_float(r0.z) + __uint_as_float(r0.w))) +
             ((__uint_as_float(r1.x) + __uint_as_float(r1.y)) + (__uint_as_float(r1.z) + __uint_as_float(r1.w)));
        r = sigmoid_f(rbf(r));
        const uint32_t h = lds32(sm + OFF_RED + (cta >> 2) * 512 + lane * 16 + (cta & 3) * 4), rs = pack2(r, r);
        uint32_t gb;
        mbar_wait(bars + (BAR_WD + 4) * 8, 0);
        y = reduce_parts<1, 8>(at(g0, src_p), [&] {
            TSL(23);
            bar_sync(9, 96);
            gb = lds32(sm + OFF_QS + lane * 4);
            y2 = lds64f(sm + OFF_RED + 12288 + lane * 8);
        });
        *at(reinterpret_cast<uint32_t*>(P.out), io) = badd2(x, bmul2(gb, badd2(h, bmul2(pack2(y.x + y2.x, y.y + y2.y), rs))));
        if (cta == 0 && lane == 0) g0[G_EPOCH] = epoch + 1;
        TSL(15);
        if (lane == 0) TL(0, 0);
        return;
    }

    const uint32_t tile = sm + OFF_RING + warp * TILE_BYTES;
    const uint32_t fullb = bars + (BAR_FULL + warp) * 8;
    const uint32_t pw = sm + OFF_P + warp * (2 * P_PITCH);
    if (warp < 8) {
        {
            uint32_t q0[8], q1[8];
            bar_sync(4, 288);
#pragma unroll
            for (int i = 0; i < 8; i++) {
                const float2 v = lds64f(sm + OFF_QS + (g & 1) * 256 + i * 32 + t4 * 8);
                q0[i] = __float_as_uint(v.x), q1[i] = __float_as_uint(v.y);
            }
            uint32_t sp = pw + (t4 & 1) * P_PITCH + ((t4 >> 1) * 8 + g) * 2;
#pragma unroll 1
            for (int it = 0; it < 8; it++, sp += 64) {
                const uint32_t ab = tile + (it & 1) * (8 * TILE_BYTES) + (lane & 15) * 128 + (((lane >> 4) ^ (lane & 7)) << 4);
                mbar_wait(fullb + (it & 1) * 64, (it >> 1) & 1);
                float acc[2][2][4] = {};
#pragma unroll
                for (int ks = 0; ks < 8; ks++)
#pragma unroll
                    for (int m = 0; m < 2; m++) {
                        uint32_t a[4];
                        ldsm4(a, (ab ^ ((ks & 3) << 5)) + (ks >> 2) * 4096 + m * 2048);
                        mma(acc[m][ks & 1], a[0], a[1], a[2], a[3], (ks & 1) ? q1[ks - 1] : q0[ks], (ks & 1) ? q1[ks] : q0[ks + 1]);
                    }
                __syncwarp();
                if (lane == 0) mbar_arrive(fullb + (it & 1) * 64 + (BAR_EMPTY - BAR_FULL) * 8);
#pragma unroll
                for (int m = 0; m < 2; m++) {
                    const float s = sel4(acc[m][0], t4) + sel4(acc[m][1], t4);
                    sts16(sp + m * 32, (uint16_t)pack2(rbf(s) * 0.08838834764831845f, 0.f));
                }
            }
        }
        __syncwarp();
        if (warp == 7) TSL(6);
        const uint32_t pa = pw + (lane >> 4) * P_PITCH + (lane & 15) * 32;
        const uint32_t sa = sm + OFF_SM + (lane >> 4) * 64;
        const uint4 v0 = lds128(pa), v1 = lds128(pa + 16);
        const uint32_t sv[8] = {v0.x, v0.y, v0.z, v0.w, v1.x, v1.y, v1.z, v1.w};
        float e[16];
        float m = -INFINITY;
#pragma unroll
        for (int i = 0; i < 8; i++) {
            e[2 * i] = blo(sv[i]);
            e[2 * i + 1] = bhi(sv[i]);
            m = fmaxf(m, fmaxf(e[2 * i], e[2 * i + 1]));
        }
#pragma unroll
        for (int o = 8; o; o >>= 1) m = fmaxf(m, __shfl_xor_sync(0xffffffffu, m, o));
        float l = 0.f;
#pragma unroll
        for (int i = 0; i < 16; i++) {
            e[i] = ex2((e[i] - m) * LOG2E);
            l += e[i];
        }
#pragma unroll
        for (int o = 8; o; o >>= 1) l += __shfl_xor_sync(0xffffffffu, l, o);
        if ((lane & 15) == 0) sts64(sa + warp * 8, __float_as_uint(m), __float_as_uint(l));
        bar_sync(2, NCW * 32);
        const float2 v = lds64f(sa + (lane & 7) * 8);
        float M = v.x;
#pragma unroll
        for (int o = 4; o; o >>= 1) M = fmaxf(M, __shfl_xor_sync(0xffffffffu, M, o));
        float L = v.y * ex2((v.x - M) * LOG2E);
#pragma unroll
        for (int o = 4; o; o >>= 1) L += __shfl_xor_sync(0xffffffffu, L, o);
        const float sc = ex2((m - M) * LOG2E) * rcp(L);
        sts128(pa, pack2(e[0] * sc, e[1] * sc), pack2(e[2] * sc, e[3] * sc), pack2(e[4] * sc, e[5] * sc), pack2(e[6] * sc, e[7] * sc));
        sts128(pa + 16, pack2(e[8] * sc, e[9] * sc), pack2(e[10] * sc, e[11] * sc), pack2(e[12] * sc, e[13] * sc), pack2(e[14] * sc, e[15] * sc));
        __syncwarp();
    } else {
        bar_sync(2, NCW * 32);
    }

    uint32_t sh[8] = {}, op[8] = {};
    {
        const uint32_t* const src_m = gs + G_M + (72 + warp * 8) * 32 + lane;
        fetch<8, 1>(src_m + 72 * 32, 32, op);
        get<8, 1>(src_m, 32, sh);
        get<8, 1>(src_m + 72 * 32, 32, op);
    }
    const int side = lds32(sm + OFF_WIN + 8), set = (epoch & 1) * G_SET, rr = (lane >> 4) * 8 + (lane & 7);
    const uint32_t dst_o = pin(4 * (set + dual(D_O + cta * 128) + (tid & 0x70) + (tid & 3) * 4 + ((tid >> 2) & 3)));
    const uint32_t src_o = pin(4 * (set + near(D_O + grp * 1024, side) + g * 128 + warp * 16 + t4 * 4));
    const int unit = warp < 8 ? 8 * sub + warp : 64 + sub;
    uint32_t rside[1] = {};
    get<1, 1>(gs + G_SIDE + unit * 8, 0, rside);
    const uint32_t dst_p = pin(4 * (near(d_part(unit), rside[0] - 1) + grp * 64 + lane * 2));
    const uint32_t src_p = pin(4 * (near(d_part(cta), side) + 512 + lane * 2));
    const uint32_t src_x = pin(4 * (set + near(D_X1 + warp * 256, side) + lane));
    const uint32_t dst_a = pin(4 * (set + dual(D_ACT + (grp * 36 + (warp < 4 ? 4 * sub + warp : 32 + sub)) * 32) + lane));
    const uint32_t src_a = pin(4 * (set + near(D_ACT + (grp * 36 + 4 * warp) * 32, side) + lane));
    const uint32_t rowoff = pin(warp < 8 ? lane * 128 + ((warp ^ (lane & 7)) << 4) : lane * 16), rowstep = warp < 8 ? 4096 : 512;
    const uint32_t l16 = pin(lane * 16);
    const uint32_t ored = pin((warp * 1088 + (t4 & 1) * 576 + ((t4 >> 1) * 8 + g) * 4) | ((tid >> 6) * 64 + tid * 8) << 16);

    if (warp < 8) {
        float acc[8][4] = {};
        uint32_t pp = pw + (lane & 1) * P_PITCH + (lane >> 3) * 16;
#pragma unroll 1
        for (int it = 0; it < 8; it++, pp += 64) {
            const uint32_t ab = tile + (it & 1) * (8 * TILE_BYTES) + ((lane & 7) + (lane >> 4) * 8) * 128 + ((((lane >> 3) & 1) ^ (lane & 7)) << 4);
            uint32_t pb[4];
            ldsm4(pb, pp);
            if (it == 6) st2(at(g0, dst_p), 0, 0);
            mbar_wait(fullb + (it & 1) * 64, (it >> 1) & 1);
#pragma unroll
            for (int ks = 0; ks < 2; ks++)
#pragma unroll
                for (int m = 0; m < 8; m++) {
                    uint32_t a[4];
                    ldsm4t(a, (ab ^ ((m & 3) << 5)) + (m >> 2) * 4096 + ks * 2048);
                    mma(acc[m], a[0], a[1], a[2], a[3], pb[2 * ks], pb[2 * ks + 1]);
                }
            __syncwarp();
            if (lane == 0) mbar_arrive(fullb + (it & 1) * 64 + (BAR_EMPTY - BAR_FULL) * 8);
        }
        if (warp == 7) TSL(7);
        const uint32_t ra = sm + OFF_ORED + (ored & 0xffff);
#pragma unroll
        for (int m = 0; m < 8; m++) sts32(ra + m * 64, __float_as_uint(sel4(acc[m], t4)));
    } else {
        mbar_wait(bars + (BAR_SYNC + 1) * 8, 0);
        st2(at(g0, dst_p), 0, 0);
    }
    bar_sync(5, NCW * 32);
    if (warp < 4) {
        float s[2][2] = {};
#pragma unroll
        for (int w = 0; w < 8; w++) {
            const float2 v = lds64f(sm + OFF_ORED + w * 1088 + (ored >> 16));
            s[w & 1][0] += v.x;
            s[w & 1][1] += v.y;
        }
        put1d(at(g0, dst_o), pack2(s[0][0] + s[1][0], s[0][1] + s[1][1]));
        if (warp == 0) TSL(8);
    }

    project<0>(sm, at(g0, src_o), at(g0, dst_p), sm + (warp < 8 ? OFF_WO : OFF_OX) + rowoff, rowstep, l16, 288, warp, lane);
    if (warp == 0) TSL(9);

    {
        uint32_t h[8] = {}, mean2;
        float inv;
        get<1, 1>(at(g0, src_x), 0, reinterpret_cast<uint32_t(&)[1]>(h[0]));
        get<8, 1>(at(g0, src_x), 32, h);
        if (warp == 0) TSL(11);
        ln_partial(h, sm + OFF_ST + g * 80 + warp * 8, t4 == 0);
        bar_sync(3, 288);
        ln_combine(sm + OFF_ST + g * 80, mean2, inv);
#pragma unroll
        for (int i = 0; i < 8; i++) h[i] = modulate2(h[i], mean2, inv, sh[i], op[i]);
        sts128(sm + OFF_RED + warp * 1024 + lane * 16, h[0], h[1], h[2], h[3]);
        sts128(sm + OFF_RED + warp * 1024 + 512 + lane * 16, h[4], h[5], h[6], h[7]);
        if (warp == 0) TSL(12);
        if (cta < 72) {
            float r = 0.f;
#pragma unroll
            for (int i = 0; i < 8; i++) {
                const uint32_t wr = lds32(sm + OFF_WR + (warp * 32 + i * 4 + t4) * 4);
                r = fmaf(blo(h[i]), blo(wr), fmaf(bhi(h[i]), bhi(wr), r));
            }
            r = quad_sum(r);
            if (t4 == 0) sts32(sm + OFF_RT + g * 48 + warp * 4, __float_as_uint(r));
        }
    }
    bar_sync(3, 288);

    if (warp < (sub < 4 ? 5 : 4)) {
        const int pl = ((lane >> 3) & 1) ^ P.zg;
        const uint32_t ks = warp < 4 ? 1024 : 256;
        uint32_t aa = sm + (warp < 4 ? OFF_GU + rr * 64 + (((lane & 6) << 3) ^ (warp << 4)) : OFF_GX + rr * 16) + pl * 4 * ks;
        float acc[2][4] = {};
#pragma unroll 1
        for (int i = 0; i < 9; i++, aa += 8 * ks) {
            const uint4 b0 = lds128(sm + OFF_RED + i * 1024 + lane * 16), b1 = lds128(sm + OFF_RED + i * 1024 + 512 + lane * 16);
            uint32_t a[4][4];
            mbar_wait(bars + (BAR_GU + i) * 8, 0);
#pragma unroll
            for (int k = 0; k < 4; k++) ldsm4t(a[k], aa + k * ks);
            mma(acc[0], a[0][0], a[0][1], a[0][2], a[0][3], b0.x, b0.y);
            mma(acc[1], a[1][0], a[1][1], a[1][2], a[1][3], b0.z, b0.w);
            mma(acc[0], a[2][0], a[2][1], a[2][2], a[2][3], b1.x, b1.y);
            mma(acc[1], a[3][0], a[3][1], a[3][2], a[3][3], b1.z, b1.w);
        }
        if (warp == 1) TSL(17);
        const uint32_t gate = pack2(acc[0][0] + acc[1][0], acc[0][1] + acc[1][1]), up = pack2(acc[0][2] + acc[1][2], acc[0][3] + acc[1][3]);
        put1d(at(g0, dst_a), movm(bmul2(silu2(gate), up)));
        if (warp == 1) TSL(13);
    } else {
        mbar_wait(bars + (BAR_GU + 8) * 8, 0);
    }

    project<1>(sm, at(g0, src_a), at(g0, dst_p), sm + (warp < 8 ? OFF_WD : OFF_DX) + rowoff, rowstep, l16, cta < 72 ? NCW * 32 : 288, warp, lane);
    if (warp == 0) TSL(14);
    if (warp == 8) TSL(27);

    if (cta < 72) {
        float acc[4][4] = {};
        uint32_t w[2][4];
        mbar_wait(bars + (BAR_GB + warp / 3) * 8, 0);
        if (warp == 8) TSL(22);
#pragma unroll
        for (int i = 0; i < 2; i++) ldsm4t(w[i], sm + OFF_GB + warp * 1024 + i * 512 + l16);
#pragma unroll
        for (int i = 0; i < 2; i++) {
            mma(acc[2 * i], sc[4 * i], sc[4 * i + 2], sc[4 * i + 1], sc[4 * i + 3], w[i][0], w[i][1]);
            mma(acc[2 * i + 1], sc[4 * i], sc[4 * i + 2], sc[4 * i + 1], sc[4 * i + 3], w[i][2], w[i][3]);
        }
        float s[2][2] = {{(acc[0][0] + acc[1][2]) + (acc[2][0] + acc[3][2]), (acc[0][1] + acc[1][3]) + (acc[2][1] + acc[3][3])}, {0.f, 0.f}};
        const uint32_t red = sm + OFF_RED + 9216 + (l16 >> 1);
        if (warp) {
            sts64(red + warp * 256, __float_as_uint(s[0][0]), __float_as_uint(s[0][1]));
            bar_arrive(7, 288);
            if (warp == 1) {
                const float2 y = reduce_parts<1, 8>(at(g0, src_p), [] {});
                sts64(red + 3072, __float_as_uint(y.x), __float_as_uint(y.y));
                __syncwarp();
                bar_arrive(9, 96);
            }
        } else {
            bar_sync(7, 288);
#pragma unroll
            for (int k = 1; k < 9; k++) {
                const float2 v = lds64f(red + k * 256);
                s[k & 1][0] += v.x;
                s[k & 1][1] += v.y;
            }
            sts32(sm + OFF_QS + (l16 >> 2), pack2(s[0][0] + s[1][0], s[0][1] + s[1][1]));
            __syncwarp();
            bar_arrive(9, 96);
            TSL(25);
        }
    }
}

typedef CUresult (*EncodeFn)(CUtensorMap*, CUtensorMapDataType, cuuint32_t, void*, const cuuint64_t*, const cuuint64_t*,
                             const cuuint32_t*, const cuuint32_t*, CUtensorMapInterleave, CUtensorMapSwizzle,
                             CUtensorMapL2promotion, CUtensorMapFloatOOBfill);

void make_map(EncodeFn enc, CUtensorMap* m, void* p, int cols, int rows, int pitch, int bc, int br, int bp, int planes, size_t pstride,
              CUtensorMapSwizzle sw, int promo) {
    cuuint64_t dims[3] = {(cuuint64_t)cols, (cuuint64_t)rows, (cuuint64_t)planes};
    cuuint64_t strides[2] = {(cuuint64_t)pitch * 2, (cuuint64_t)pstride};
    cuuint32_t box[3] = {(cuuint32_t)bc, (cuuint32_t)br, (cuuint32_t)bp};
    cuuint32_t es[3] = {1, 1, 1};
    enc(m, CU_TENSOR_MAP_DATA_TYPE_BFLOAT16, 3, p, dims, strides, box, es, CU_TENSOR_MAP_INTERLEAVE_NONE, sw,
        (CUtensorMapL2promotion)promo, CU_TENSOR_MAP_FLOAT_OOB_FILL_NONE);
}

}

extern "C" void kernel_launch(void* const* d_in, const int* in_sizes, int n_in, void* d_out, int out_size) {
    static EncodeFn enc = nullptr;
    static uint32_t* scratch = nullptr;
    if (!enc) {
        void* fn = nullptr;
        cudaDriverEntryPointQueryResult st;
        cudaGetDriverEntryPoint("cuTensorMapEncodeTiled", &fn, cudaEnableDefault, &st);
        enc = (EncodeFn)fn;
        cudaGetSymbolAddress(&fn, g_scratch);
        scratch = (uint32_t*)(((uintptr_t)fn + 8 * G_SET - 1) & ~(uintptr_t)(8 * G_SET - 1));
        cudaFuncSetAttribute(fused_kernel, cudaFuncAttributeMaxDynamicSharedMemorySize, SMEM_BYTES);
    }
    Params P;
    Maps T;
    const CUtensorMapSwizzle none = CU_TENSOR_MAP_SWIZZLE_NONE;
    const int PROMO_W = CU_TENSOR_MAP_L2_PROMOTION_L2_128B, PROMO_KV = CU_TENSOR_MAP_L2_PROMOTION_L2_256B;
    make_map(enc, &T.m[M_K], d_in[1], 64, NB * HKV * SK, DH, 64, 32, 2, 2, 128, CU_TENSOR_MAP_SWIZZLE_128B, PROMO_KV);
    make_map(enc, &T.m[M_V], d_in[2], 64, NB * HKV * SK, DH, 64, 32, 2, 2, 128, CU_TENSOR_MAP_SWIZZLE_128B, PROMO_KV);
    make_map(enc, &T.m[M_WQ], d_in[3], HQ * DH, DM, HQ * DH, 32, 192, 1, 1, 16, CU_TENSOR_MAP_SWIZZLE_64B, PROMO_W);
    make_map(enc, &T.m[M_WM], d_in[11], 6 * DM, DM, 6 * DM, 32, 192, 1, 1, 16, CU_TENSOR_MAP_SWIZZLE_64B, PROMO_W);
    make_map(enc, &T.m[M_WA], d_in[11], DM, DM, 6 * DM, 16, 192, 2, 2, DM * 2, CU_TENSOR_MAP_SWIZZLE_32B, PROMO_W);
    make_map(enc, &T.m[M_GB], d_in[11], 6 * DM, DM, 6 * DM, 8, 192, 1, 1, 16, none, PROMO_W);
    char *wg = (char*)d_in[7], *wu = (char*)d_in[8], *wo = (char*)d_in[4], *wd = (char*)d_in[9];
    P.zg = wg > wu;
    P.zo = wo > wd;
    const size_t sg = P.zg ? wg - wu : wu - wg, so = P.zo ? wo - wd : wd - wo;
    make_map(enc, &T.m[M_GU], P.zg ? wu : wg, FF, DM, FF, 32, 64, 2, 2, sg, CU_TENSOR_MAP_SWIZZLE_64B, PROMO_W);
    make_map(enc, &T.m[M_GX], P.zg ? wu : wg, FF, DM, FF, 8, 64, 2, 2, sg, none, PROMO_W);
    make_map(enc, &T.m[M_OD], P.zo ? wd : wo, DM, FF, DM, 64, 64, 1, 2, so, CU_TENSOR_MAP_SWIZZLE_128B, PROMO_W);
    make_map(enc, &T.m[M_OX], P.zo ? wd : wo, DM, FF, DM, 8, 64, 1, 2, so, none, PROMO_W);
    P.x = (const __nv_bfloat16*)d_in[0];
    P.wr = (const __nv_bfloat16*)d_in[6];
    P.c = (const __nv_bfloat16*)d_in[10];
    P.k = (const __nv_bfloat16*)d_in[1];
    P.out = (__nv_bfloat16*)d_out;
    P.scratch = scratch;
    void* args[2] = {&P, &T};
    cudaLaunchCooperativeKernel((const void*)fused_kernel, dim3(NCTA), dim3(NTHREADS), args, SMEM_BYTES, cudaStreamPerThread);
}
```
